```python
import torch

def _softmax(x, axis=-1):
    return torch.softmax(x, dim=axis)

def _gelu(x):
    return torch.nn.functional.gelu(x, approximate='tanh')

def _silu(x):
    return torch.nn.functional.silu(x)

def _sigmoid(x):
    return torch.sigmoid(x)

def _layernorm(x, axis=-1, eps=1e-05):
    m = x.mean(dim=axis, keepdim=True)
    v = x.var(dim=axis, keepdim=True, unbiased=False)
    return (x - m) / torch.sqrt(v + eps)

def _scatter_add(tgt, idx, src, axis=0):
    return tgt.clone().index_add_(axis, idx, src)

def _segment_sum(src, seg, n):
    out = torch.zeros((n,) + src.shape[1:], dtype=src.dtype)
    return out.index_add_(0, seg, src)

def _pad(x, pw):
    flat = tuple((v for pair in reversed(pw) for v in pair))
    return torch.nn.functional.pad(x, flat)
kernel_name = 'adaLN_cond__mha_block_cached__moe_arch_mod__prompt'

def setup_inputs():

    _w = lambda a: (lambda t: t.to(torch.bfloat16) if t.is_floating_point() else t)(torch.as_tensor(a))

    def _A_setup():
        B, Sq, D = (1, 2048, 1024)
        H, Sk, Dh = (32, 2048, 128)
        return {'x': _w((lambda *s: torch.randn(*s, dtype=torch.bfloat16) * 0.1)(B, Sq, D)), 'k_cache': _w((lambda *s: torch.randn(*s, dtype=torch.bfloat16) * 0.8)(B, H, Sk, Dh)), 'v_cache': _w((lambda *s: torch.randn(*s, dtype=torch.bfloat16) * 0.8)(B, H, Sk, Dh)), 'wq': _w((lambda *s: torch.randn(*s, dtype=torch.bfloat16) * 0.8)(D, H * Dh) * D ** (-0.5)), 'wo': _w((lambda *s: torch.randn(*s, dtype=torch.bfloat16) * 0.8)(H * Dh, D) * (H * Dh) ** (-0.5))}
    _A_in = _A_setup()

    def _B_setup():
        B, S, D, F, C = (1, 2048, 1024, 3584, 2)
        return {'x': _w((lambda *s: torch.randn(*s, dtype=torch.bfloat16) * 0.1)(B, S, D)), 'w_r': _w((lambda *s: torch.randn(*s, dtype=torch.bfloat16) * 3.2)(D)), 'w_gate': _w((lambda *s: torch.randn(*s, dtype=torch.bfloat16) * 0.2)(D, F)), 'w_up': _w((lambda *s: torch.randn(*s, dtype=torch.bfloat16) * 0.2)(D, F)), 'w_down': _w((lambda *s: torch.randn(*s, dtype=torch.bfloat16) * 0.2)(F, D))}
    _B_in = _B_setup()
    return {'A_x': _A_in['x'], 'A_k_cache': _A_in['k_cache'], 'A_v_cache': _A_in['v_cache'], 'A_wq': _A_in['wq'], 'A_wo': _A_in['wo'], 'B_x': _B_in['x'], 'B_w_r': _B_in['w_r'], 'B_w_gate': _B_in['w_gate'], 'B_w_up': _B_in['w_up'], 'B_w_down': _B_in['w_down'], 'c': _w((lambda *s: torch.randn(*s, dtype=torch.bfloat16) * 0.2)(1, 1024) * 8.0), 'w_mod': _w((lambda *s: torch.randn(*s, dtype=torch.bfloat16) * 0.2)(1024, 6 * 1024) * 1024 ** (-0.5) * 8.0)}

def reference(A_x, A_k_cache, A_v_cache, A_wq, A_wo, B_x, B_w_r, B_w_gate, B_w_up, B_w_down, c, w_mod):

    def _A_ref(x, k_cache, v_cache, wq, wo):
        B, Sq, D = x.shape
        H, Dh = (32, 128)
        q = (lambda x, *d: x.permute(*d))((x @ wq).reshape(B, Sq, H, Dh), 0, 2, 1, 3)
        scores = torch.einsum('bhqd,bhkd->bhqk', q, k_cache) * Dh ** (-0.5)
        p = _softmax(scores, axis=-1)
        o = torch.einsum('bhqk,bhkd->bhqd', p, v_cache)
        return (lambda x, *d: x.permute(*d))(o, 0, 2, 1, 3).reshape(B, Sq, H * Dh) @ wo

    def _B_ref(x, w_r, w_gate, w_up, w_down):
        B, S, D = x.shape
        C = 2
        r = x @ w_r
        idx = torch.argsort(-r, axis=-1)[:, :C]
        idx_e = (lambda x, n, axis: torch.repeat_interleave(x, n, dim=axis))(idx.reshape(B, C, 1), D, axis=2)
        x_sel = (lambda x, i, axis: torch.take_along_dim(x, i, dim=axis))(x, idx_e, axis=1)
        g = _silu(x_sel @ w_gate)
        u = x_sel @ w_up
        y = g * u @ w_down
        r_sel = _sigmoid((lambda x, i, axis: torch.take_along_dim(x, i, dim=axis))(r, idx, axis=1))
        y = y * r_sel.reshape(B, C, 1)
        b_off = (torch.arange(B) * S).reshape(B, 1)
        flat_idx = (idx + b_off).reshape(B * C)
        zero = (x * 0.0).reshape(B * S, D)
        upd = _scatter_add(zero, flat_idx, y.reshape(B * C, D), axis=0)
        return x + upd.reshape(B, S, D)
    x = A_x
    mod = (_silu(c) @ w_mod).reshape(c.shape[0], 6, 1, -1)
    sa, ca, ga, sb, cb, gb = (mod[:, 0].clone(), mod[:, 1].clone(), mod[:, 2].clone(), mod[:, 3].clone(), mod[:, 4].clone(), mod[:, 5].clone())
    h = _layernorm(x, axis=-1) * (1 + ca) + sa
    x = x + ga * _A_ref(h, A_k_cache, A_v_cache, A_wq, A_wo)
    h = _layernorm(x, axis=-1) * (1 + cb) + sb
    x = x + gb * _B_ref(h, B_w_r, B_w_gate, B_w_up, B_w_down)
    return x
```

```cpp
#include <cuda_runtime.h>
#include <cuda_bf16.h>
#include <cuda.h>
#include <stdint.h>

namespace {

typedef __nv_bfloat16 bf16;

constexpr int T_SEQ = 2048, T_D = 1024, T_NH = 32, T_DH = 128, T_DQKV = 4096, T_F = 3584;

__device__ __align__(1024) bf16 g_o[T_SEQ * T_DQKV];
struct __align__(2048) TailMail {
  float4 part1[T_SEQ * 8];
  uint32_t key[256];
  uint4 cand[16 * 2 * 2 * 128];
  uint32_t cnt[32];
  float ypart[(T_F / 32) * 2 * T_D];
};
struct __align__(2048) Scratch {
  TailMail mail;
  float mod[2 * T_D];
  float modu[16 * 512];
  float2 stat[T_SEQ * 2];
  uint32_t gkey[160];
  uint8_t tab[132 * 4096];
  uint8_t col[8 * 1536];
  unsigned int hcnt[17 * 32];
  float scal[4];
};
__device__ Scratch g_scr;
#define g_part1 hm->mail.part1
#define g_key hm->mail.key
#define g_cand hm->mail.cand
#define CNT_Y hm->mail.cnt
#define g_ypart hm->mail.ypart
#define g_col hm->col
#define g_scal hm->scal
#define g_hcnt hm->hcnt

__device__ __forceinline__ uint32_t smem_u32(const void* p) { return (uint32_t)__cvta_generic_to_shared(p); }
__device__ __forceinline__ void mbar_init(uint32_t bar, uint32_t cnt) { asm volatile("mbarrier.init.shared::cta.b64 [%0], %1;" :: "r"(bar), "r"(cnt)); }
__device__ __forceinline__ void mbar_expect_tx(uint32_t bar, uint32_t bytes) { asm volatile("mbarrier.arrive.expect_tx.shared::cta.b64 _, [%0], %1;" :: "r"(bar), "r"(bytes) : "memory"); }
__device__ __forceinline__ void mbar_arrive(uint32_t bar) { asm volatile("mbarrier.arrive.shared::cta.b64 _, [%0];" :: "r"(bar) : "memory"); }
__device__ __forceinline__ void mbar_wait(uint32_t bar, uint32_t parity) {
  asm volatile("{\n.reg .pred p;\nLAB_WAIT:\nmbarrier.try_wait.parity.shared::cta.b64 p, [%0], %1;\n@!p bra LAB_WAIT;\n}\n" :: "r"(bar), "r"(parity) : "memory");
}
__device__ __forceinline__ bool mbar_test(uint32_t bar, uint32_t parity) {
  uint32_t r; asm volatile("{\n.reg .pred p;\nmbarrier.test_wait.parity.shared::cta.b64 p, [%1], %2;\nselp.u32 %0, 1, 0, p;\n}\n" : "=r"(r) : "r"(bar), "r"(parity) : "memory");
  return r != 0;
}
__device__ __forceinline__ void fence_mbar_init() { asm volatile("fence.mbarrier_init.release.cluster;" ::: "memory"); }
__device__ __forceinline__ uint64_t policy_evict_first() {
  uint64_t p; asm volatile("createpolicy.fractional.L2::evict_first.b64 %0, 1.0;" : "=l"(p)); return p;
}
__device__ __forceinline__ void tma_load_2d_hint(uint32_t dst, const CUtensorMap* map, int c0, int c1, uint32_t bar, uint64_t pol) {
  asm volatile("cp.async.bulk.tensor.2d.shared::cluster.global.mbarrier::complete_tx::bytes.L2::cache_hint [%0], [%1, {%3, %4}], [%2], %5;"
    :: "r"(dst), "l"(map), "r"(bar), "r"(c0), "r"(c1), "l"(pol) : "memory");
}
__device__ __forceinline__ void tma_load_3d_hint(uint32_t dst, const CUtensorMap* map, int c1, int c2, uint32_t bar, uint64_t pol) {
  asm volatile("cp.async.bulk.tensor.3d.shared::cluster.global.mbarrier::complete_tx::bytes.L2::cache_hint [%0], [%1, {%6, %3, %4}], [%2], %5;"
    :: "r"(dst), "l"(map), "r"(bar), "r"(c1), "r"(c2), "l"(pol), "r"(0) : "memory");
}
__device__ __forceinline__ void tma_store_2d(const CUtensorMap* map, uint32_t src, int c0, int c1) {
  asm volatile("cp.async.bulk.tensor.2d.global.shared::cta.bulk_group [%0, {%2, %3}], [%1];" :: "l"(map), "r"(src), "r"(c0), "r"(c1) : "memory");
}
__device__ __forceinline__ void prefetch_tmap(const CUtensorMap* map) { asm volatile("prefetch.tensormap [%0];" :: "l"(map) : "memory"); }
__device__ __forceinline__ void l2_prefetch_bulk(const void* p, uint32_t bytes) {
  asm volatile("cp.async.bulk.prefetch.L2.global [%0], %1;" :: "l"(p), "r"(bytes) : "memory");
}
__device__ __forceinline__ void bulk_commit() { asm volatile("cp.async.bulk.commit_group;" ::: "memory"); }
template<int N> __device__ __forceinline__ void bulk_wait_read() { asm volatile("cp.async.bulk.wait_group.read %0;" :: "n"(N) : "memory"); }
template<int N> __device__ __forceinline__ void bulk_wait() { asm volatile("cp.async.bulk.wait_group %0;" :: "n"(N) : "memory"); }
__device__ __forceinline__ void named_bar_sync(int id, int nthreads) { asm volatile("bar.sync %0, %1;" :: "r"(id), "r"(nthreads) : "memory"); }
__device__ __forceinline__ void named_bar_arrive(int id, int nthreads) { asm volatile("bar.arrive %0, %1;" :: "r"(id), "r"(nthreads) : "memory"); }
__device__ __forceinline__ void named_bar_arrive_if(bool c, int id, int nthreads) { asm volatile("{\n.reg .pred p;\nsetp.ne.u32 p, %2, 0;\n@p bar.arrive %0, %1;\n}" :: "r"(id), "r"(nthreads), "r"((uint32_t)c) : "memory"); }
__device__ __forceinline__ void wgmma_fence() { asm volatile("wgmma.fence.sync.aligned;" ::: "memory"); }
__device__ __forceinline__ void wgmma_commit() { asm volatile("wgmma.commit_group.sync.aligned;" ::: "memory"); }
template<int N> __device__ __forceinline__ void wgmma_wait() { asm volatile("wgmma.wait_group.sync.aligned %0;" :: "n"(N) : "memory"); }
template<int R> __device__ __forceinline__ void reg_alloc() { asm volatile("setmaxnreg.inc.sync.aligned.u32 %0;" :: "n"(R)); }
template<int R> __device__ __forceinline__ void reg_dealloc() { asm volatile("setmaxnreg.dec.sync.aligned.u32 %0;" :: "n"(R)); }
__device__ __forceinline__ bool elect_one() {
  uint32_t pred; asm volatile("{\n.reg .pred p;\nelect.sync _|p, 0xffffffff;\nselp.u32 %0, 1, 0, p;\n}\n" : "=r"(pred)); return pred != 0;
}
__device__ __forceinline__ uint32_t pack_bf16(float lo, float hi) {
  uint32_t r; asm("cvt.rn.bf16x2.f32 %0, %1, %2;" : "=r"(r) : "f"(hi), "f"(lo)); return r;
}
__device__ __forceinline__ void stmatrix_x4(uint32_t addr, uint32_t r0, uint32_t r1, uint32_t r2, uint32_t r3) {
  asm volatile("stmatrix.sync.aligned.m8n8.x4.shared.b16 [%0], {%1, %2, %3, %4};" :: "r"(addr), "r"(r0), "r"(r1), "r"(r2), "r"(r3) : "memory");
}
__device__ __forceinline__ void fence_proxy_async() { asm volatile("fence.proxy.async.shared::cta;" ::: "memory"); }
__device__ __forceinline__ float ex2_approx(float x) { float y; asm("ex2.approx.ftz.f32 %0, %1;" : "=f"(y) : "f"(x)); return y; }
template<int N> __device__ __forceinline__ void fence_regs(float (&r)[N]) {
  #pragma unroll
  for (int i = 0; i < N; i++) asm volatile("" : "+f"(r[i]) :: "memory");
}
template<int N> __device__ __forceinline__ void zero_regs(float (&r)[N]) {
  #pragma unroll
  for (int i = 0; i < N; i += 2) asm volatile("mov.b64 {%0, %1}, 0;" : "=f"(r[i]), "=f"(r[i + 1]));
}
__device__ __forceinline__ float rbf(float x) { return __uint_as_float(pack_bf16(0.f, x)); }
__device__ __forceinline__ float bflo(uint32_t v) { return __uint_as_float(v << 16); }
__device__ __forceinline__ float bfhi(uint32_t v) { return __uint_as_float(v & 0xffff0000u); }

#define TL_START(k) do {} while (0)
#define TL_END(k, cond) do {} while (0)
#define TL_CTA(i, cond) do {} while (0)
#define FS(slot, k) do {} while (0)
#define QS(idx) do {} while (0)
#define QDUMP() do {} while (0)
#define TL_MARK2(k, cond) do {} while (0)
#define TL_CLK(k, i, cond) do {} while (0)

#define HS(k) do {} while (0)
#define HSD(k, dep) do {} while (0)
#define HSDUMP() do {} while (0)
#define PS(k, cond) do {} while (0)
#define PSV(k, cond, v) do {} while (0)
template <int OFFA, int OFFB>
__device__ __forceinline__ void wgmma_m64n256k16_ss_tb(float (&d)[128], uint32_t a_lo, uint32_t b_lo, int scaleD) {
  asm volatile("{\n.reg .pred p;\n.reg .b32 ta, tb;\n.reg .b64 da, db;\nsetp.ne.b32 p, %130, 0;\n"
    "add.u32 ta, %128, %131;\nadd.u32 tb, %129, %132;\n"
    "mov.b64 da, {ta, 0x40000040};\nmov.b64 db, {tb, 0x40000040};\n"
    "wgmma.mma_async.sync.aligned.m64n256k16.f32.bf16.bf16 "
    "{%0, %1, %2, %3, %4, %5, %6, %7, %8, %9, %10, %11, %12, %13, %14, %15, %16, %17, %18, %19, %20, %21, %22, %23, %24, %25, %26, %27, %28, %29, %30, %31, %32, %33, %34, %35, %36, %37, %38, %39, %40, %41, %42, %43, %44, %45, %46, %47, %48, %49, %50, %51, %52, %53, %54, %55, %56, %57, %58, %59, %60, %61, %62, %63, %64, %65, %66, %67, %68, %69, %70, %71, %72, %73, %74, %75, %76, %77, %78, %79, %80, %81, %82, %83, %84, %85, %86, %87, %88, %89, %90, %91, %92, %93, %94, %95, %96, %97, %98, %99, %100, %101, %102, %103, %104, %105, %106, %107, %108, %109, %110, %111, %112, %113, %114, %115, %116, %117, %118, %119, %120, %121, %122, %123, %124, %125, %126, %127}, "
    "da, db, p, 1, 1, 0, 1;\n}\n"
    : "+f"(d[0]), "+f"(d[1]), "+f"(d[2]), "+f"(d[3]), "+f"(d[4]), "+f"(d[5]), "+f"(d[6]), "+f"(d[7]), "+f"(d[8]), "+f"(d[9]), "+f"(d[10]), "+f"(d[11]), "+f"(d[12]), "+f"(d[13]), "+f"(d[14]), "+f"(d[15]), "+f"(d[16]), "+f"(d[17]), "+f"(d[18]), "+f"(d[19]), "+f"(d[20]), "+f"(d[21]), "+f"(d[22]), "+f"(d[23]), "+f"(d[24]), "+f"(d[25]), "+f"(d[26]), "+f"(d[27]), "+f"(d[28]), "+f"(d[29]), "+f"(d[30]), "+f"(d[31]), "+f"(d[32]), "+f"(d[33]), "+f"(d[34]), "+f"(d[35]), "+f"(d[36]), "+f"(d[37]), "+f"(d[38]), "+f"(d[39]), "+f"(d[40]), "+f"(d[41]), "+f"(d[42]), "+f"(d[43]), "+f"(d[44]), "+f"(d[45]), "+f"(d[46]), "+f"(d[47]), "+f"(d[48]), "+f"(d[49]), "+f"(d[50]), "+f"(d[51]), "+f"(d[52]), "+f"(d[53]), "+f"(d[54]), "+f"(d[55]), "+f"(d[56]), "+f"(d[57]), "+f"(d[58]), "+f"(d[59]), "+f"(d[60]), "+f"(d[61]), "+f"(d[62]), "+f"(d[63]), "+f"(d[64]), "+f"(d[65]), "+f"(d[66]), "+f"(d[67]), "+f"(d[68]), "+f"(d[69]), "+f"(d[70]), "+f"(d[71]), "+f"(d[72]), "+f"(d[73]), "+f"(d[74]), "+f"(d[75]), "+f"(d[76]), "+f"(d[77]), "+f"(d[78]), "+f"(d[79]), "+f"(d[80]), "+f"(d[81]), "+f"(d[82]), "+f"(d[83]), "+f"(d[84]), "+f"(d[85]), "+f"(d[86]), "+f"(d[87]), "+f"(d[88]), "+f"(d[89]), "+f"(d[90]), "+f"(d[91]), "+f"(d[92]), "+f"(d[93]), "+f"(d[94]), "+f"(d[95]), "+f"(d[96]), "+f"(d[97]), "+f"(d[98]), "+f"(d[99]), "+f"(d[100]), "+f"(d[101]), "+f"(d[102]), "+f"(d[103]), "+f"(d[104]), "+f"(d[105]), "+f"(d[106]), "+f"(d[107]), "+f"(d[108]), "+f"(d[109]), "+f"(d[110]), "+f"(d[111]), "+f"(d[112]), "+f"(d[113]), "+f"(d[114]), "+f"(d[115]), "+f"(d[116]), "+f"(d[117]), "+f"(d[118]), "+f"(d[119]), "+f"(d[120]), "+f"(d[121]), "+f"(d[122]), "+f"(d[123]), "+f"(d[124]), "+f"(d[125]), "+f"(d[126]), "+f"(d[127])
    : "r"(a_lo), "r"(b_lo), "r"(scaleD), "n"(OFFA), "n"(OFFB));
}

template <int OFFA, int OFFB>
__device__ __forceinline__ void wgmma_m64n128k16_ss_tb(float (&d)[64], uint32_t a_lo, uint32_t b_lo, int scaleD) {
  asm volatile("{\n.reg .pred p;\n.reg .b32 ta, tb;\n.reg .b64 da, db;\nsetp.ne.b32 p, %66, 0;\n"
    "add.u32 ta, %64, %67;\nadd.u32 tb, %65, %68;\n"
    "mov.b64 da, {ta, 0x40000040};\nmov.b64 db, {tb, 0x40000040};\n"
    "wgmma.mma_async.sync.aligned.m64n128k16.f32.bf16.bf16 "
    "{%0, %1, %2, %3, %4, %5, %6, %7, %8, %9, %10, %11, %12, %13, %14, %15, %16, %17, %18, %19, %20, %21, %22, %23, %24, %25, %26, %27, %28, %29, %30, %31, %32, %33, %34, %35, %36, %37, %38, %39, %40, %41, %42, %43, %44, %45, %46, %47, %48, %49, %50, %51, %52, %53, %54, %55, %56, %57, %58, %59, %60, %61, %62, %63}, "
    "da, db, p, 1, 1, 0, 1;\n}\n"
    : "+f"(d[0]), "+f"(d[1]), "+f"(d[2]), "+f"(d[3]), "+f"(d[4]), "+f"(d[5]), "+f"(d[6]), "+f"(d[7]), "+f"(d[8]), "+f"(d[9]), "+f"(d[10]), "+f"(d[11]), "+f"(d[12]), "+f"(d[13]), "+f"(d[14]), "+f"(d[15]), "+f"(d[16]), "+f"(d[17]), "+f"(d[18]), "+f"(d[19]), "+f"(d[20]), "+f"(d[21]), "+f"(d[22]), "+f"(d[23]), "+f"(d[24]), "+f"(d[25]), "+f"(d[26]), "+f"(d[27]), "+f"(d[28]), "+f"(d[29]), "+f"(d[30]), "+f"(d[31]), "+f"(d[32]), "+f"(d[33]), "+f"(d[34]), "+f"(d[35]), "+f"(d[36]), "+f"(d[37]), "+f"(d[38]), "+f"(d[39]), "+f"(d[40]), "+f"(d[41]), "+f"(d[42]), "+f"(d[43]), "+f"(d[44]), "+f"(d[45]), "+f"(d[46]), "+f"(d[47]), "+f"(d[48]), "+f"(d[49]), "+f"(d[50]), "+f"(d[51]), "+f"(d[52]), "+f"(d[53]), "+f"(d[54]), "+f"(d[55]), "+f"(d[56]), "+f"(d[57]), "+f"(d[58]), "+f"(d[59]), "+f"(d[60]), "+f"(d[61]), "+f"(d[62]), "+f"(d[63])
    : "r"(a_lo), "r"(b_lo), "r"(scaleD), "n"(OFFA), "n"(OFFB));
}

template <int OFFB>
__device__ __forceinline__ void wgmma_m64n256k16_rs_tb(float (&d)[128], uint32_t a0, uint32_t a1, uint32_t a2, uint32_t a3, uint32_t b_lo, int scaleD) {
  asm volatile("{\n.reg .pred p;\n.reg .b32 tb;\n.reg .b64 db;\nsetp.ne.b32 p, %133, 0;\n"
    "add.u32 tb, %132, %134;\n"
    "mov.b64 db, {tb, 0x40000040};\n"
    "wgmma.mma_async.sync.aligned.m64n256k16.f32.bf16.bf16 "
    "{%0, %1, %2, %3, %4, %5, %6, %7, %8, %9, %10, %11, %12, %13, %14, %15, %16, %17, %18, %19, %20, %21, %22, %23, %24, %25, %26, %27, %28, %29, %30, %31, %32, %33, %34, %35, %36, %37, %38, %39, %40, %41, %42, %43, %44, %45, %46, %47, %48, %49, %50, %51, %52, %53, %54, %55, %56, %57, %58, %59, %60, %61, %62, %63, %64, %65, %66, %67, %68, %69, %70, %71, %72, %73, %74, %75, %76, %77, %78, %79, %80, %81, %82, %83, %84, %85, %86, %87, %88, %89, %90, %91, %92, %93, %94, %95, %96, %97, %98, %99, %100, %101, %102, %103, %104, %105, %106, %107, %108, %109, %110, %111, %112, %113, %114, %115, %116, %117, %118, %119, %120, %121, %122, %123, %124, %125, %126, %127}, "
    "{%128, %129, %130, %131}, db, p, 1, 1, 1;\n}\n"
    : "+f"(d[0]), "+f"(d[1]), "+f"(d[2]), "+f"(d[3]), "+f"(d[4]), "+f"(d[5]), "+f"(d[6]), "+f"(d[7]), "+f"(d[8]), "+f"(d[9]), "+f"(d[10]), "+f"(d[11]), "+f"(d[12]), "+f"(d[13]), "+f"(d[14]), "+f"(d[15]), "+f"(d[16]), "+f"(d[17]), "+f"(d[18]), "+f"(d[19]), "+f"(d[20]), "+f"(d[21]), "+f"(d[22]), "+f"(d[23]), "+f"(d[24]), "+f"(d[25]), "+f"(d[26]), "+f"(d[27]), "+f"(d[28]), "+f"(d[29]), "+f"(d[30]), "+f"(d[31]), "+f"(d[32]), "+f"(d[33]), "+f"(d[34]), "+f"(d[35]), "+f"(d[36]), "+f"(d[37]), "+f"(d[38]), "+f"(d[39]), "+f"(d[40]), "+f"(d[41]), "+f"(d[42]), "+f"(d[43]), "+f"(d[44]), "+f"(d[45]), "+f"(d[46]), "+f"(d[47]), "+f"(d[48]), "+f"(d[49]), "+f"(d[50]), "+f"(d[51]), "+f"(d[52]), "+f"(d[53]), "+f"(d[54]), "+f"(d[55]), "+f"(d[56]), "+f"(d[57]), "+f"(d[58]), "+f"(d[59]), "+f"(d[60]), "+f"(d[61]), "+f"(d[62]), "+f"(d[63]), "+f"(d[64]), "+f"(d[65]), "+f"(d[66]), "+f"(d[67]), "+f"(d[68]), "+f"(d[69]), "+f"(d[70]), "+f"(d[71]), "+f"(d[72]), "+f"(d[73]), "+f"(d[74]), "+f"(d[75]), "+f"(d[76]), "+f"(d[77]), "+f"(d[78]), "+f"(d[79]), "+f"(d[80]), "+f"(d[81]), "+f"(d[82]), "+f"(d[83]), "+f"(d[84]), "+f"(d[85]), "+f"(d[86]), "+f"(d[87]), "+f"(d[88]), "+f"(d[89]), "+f"(d[90]), "+f"(d[91]), "+f"(d[92]), "+f"(d[93]), "+f"(d[94]), "+f"(d[95]), "+f"(d[96]), "+f"(d[97]), "+f"(d[98]), "+f"(d[99]), "+f"(d[100]), "+f"(d[101]), "+f"(d[102]), "+f"(d[103]), "+f"(d[104]), "+f"(d[105]), "+f"(d[106]), "+f"(d[107]), "+f"(d[108]), "+f"(d[109]), "+f"(d[110]), "+f"(d[111]), "+f"(d[112]), "+f"(d[113]), "+f"(d[114]), "+f"(d[115]), "+f"(d[116]), "+f"(d[117]), "+f"(d[118]), "+f"(d[119]), "+f"(d[120]), "+f"(d[121]), "+f"(d[122]), "+f"(d[123]), "+f"(d[124]), "+f"(d[125]), "+f"(d[126]), "+f"(d[127])
    : "r"(a0), "r"(a1), "r"(a2), "r"(a3), "r"(b_lo), "r"(scaleD), "n"(OFFB));
}

template <int OFFB>
__device__ __forceinline__ void wgmma_m64n128k16_rs_tb(float (&d)[64], uint32_t a0, uint32_t a1, uint32_t a2, uint32_t a3, uint32_t b_lo, int scaleD) {
  asm volatile("{\n.reg .pred p;\n.reg .b32 tb;\n.reg .b64 db;\nsetp.ne.b32 p, %69, 0;\n"
    "add.u32 tb, %68, %70;\n"
    "mov.b64 db, {tb, 0x40000040};\n"
    "wgmma.mma_async.sync.aligned.m64n128k16.f32.bf16.bf16 "
    "{%0, %1, %2, %3, %4, %5, %6, %7, %8, %9, %10, %11, %12, %13, %14, %15, %16, %17, %18, %19, %20, %21, %22, %23, %24, %25, %26, %27, %28, %29, %30, %31, %32, %33, %34, %35, %36, %37, %38, %39, %40, %41, %42, %43, %44, %45, %46, %47, %48, %49, %50, %51, %52, %53, %54, %55, %56, %57, %58, %59, %60, %61, %62, %63}, "
    "{%64, %65, %66, %67}, db, p, 1, 1, 1;\n}\n"
    : "+f"(d[0]), "+f"(d[1]), "+f"(d[2]), "+f"(d[3]), "+f"(d[4]), "+f"(d[5]), "+f"(d[6]), "+f"(d[7]), "+f"(d[8]), "+f"(d[9]), "+f"(d[10]), "+f"(d[11]), "+f"(d[12]), "+f"(d[13]), "+f"(d[14]), "+f"(d[15]), "+f"(d[16]), "+f"(d[17]), "+f"(d[18]), "+f"(d[19]), "+f"(d[20]), "+f"(d[21]), "+f"(d[22]), "+f"(d[23]), "+f"(d[24]), "+f"(d[25]), "+f"(d[26]), "+f"(d[27]), "+f"(d[28]), "+f"(d[29]), "+f"(d[30]), "+f"(d[31]), "+f"(d[32]), "+f"(d[33]), "+f"(d[34]), "+f"(d[35]), "+f"(d[36]), "+f"(d[37]), "+f"(d[38]), "+f"(d[39]), "+f"(d[40]), "+f"(d[41]), "+f"(d[42]), "+f"(d[43]), "+f"(d[44]), "+f"(d[45]), "+f"(d[46]), "+f"(d[47]), "+f"(d[48]), "+f"(d[49]), "+f"(d[50]), "+f"(d[51]), "+f"(d[52]), "+f"(d[53]), "+f"(d[54]), "+f"(d[55]), "+f"(d[56]), "+f"(d[57]), "+f"(d[58]), "+f"(d[59]), "+f"(d[60]), "+f"(d[61]), "+f"(d[62]), "+f"(d[63])
    : "r"(a0), "r"(a1), "r"(a2), "r"(a3), "r"(b_lo), "r"(scaleD), "n"(OFFB));
}

template <int OFFB>
__device__ __forceinline__ void wgmma_m64n128k16_rs(float (&d)[64], uint32_t a0, uint32_t a1, uint32_t a2, uint32_t a3, uint32_t b_lo, int scaleD) {
  asm volatile("{\n.reg .pred p;\n.reg .b32 tb;\n.reg .b64 db;\nsetp.ne.b32 p, %69, 0;\n"
    "add.u32 tb, %68, %70;\n"
    "mov.b64 db, {tb, 0x40000040};\n"
    "wgmma.mma_async.sync.aligned.m64n128k16.f32.bf16.bf16 "
    "{%0, %1, %2, %3, %4, %5, %6, %7, %8, %9, %10, %11, %12, %13, %14, %15, %16, %17, %18, %19, %20, %21, %22, %23, %24, %25, %26, %27, %28, %29, %30, %31, %32, %33, %34, %35, %36, %37, %38, %39, %40, %41, %42, %43, %44, %45, %46, %47, %48, %49, %50, %51, %52, %53, %54, %55, %56, %57, %58, %59, %60, %61, %62, %63}, "
    "{%64, %65, %66, %67}, db, p, 1, 1, 0;\n}\n"
    : "+f"(d[0]), "+f"(d[1]), "+f"(d[2]), "+f"(d[3]), "+f"(d[4]), "+f"(d[5]), "+f"(d[6]), "+f"(d[7]), "+f"(d[8]), "+f"(d[9]), "+f"(d[10]), "+f"(d[11]), "+f"(d[12]), "+f"(d[13]), "+f"(d[14]), "+f"(d[15]), "+f"(d[16]), "+f"(d[17]), "+f"(d[18]), "+f"(d[19]), "+f"(d[20]), "+f"(d[21]), "+f"(d[22]), "+f"(d[23]), "+f"(d[24]), "+f"(d[25]), "+f"(d[26]), "+f"(d[27]), "+f"(d[28]), "+f"(d[29]), "+f"(d[30]), "+f"(d[31]), "+f"(d[32]), "+f"(d[33]), "+f"(d[34]), "+f"(d[35]), "+f"(d[36]), "+f"(d[37]), "+f"(d[38]), "+f"(d[39]), "+f"(d[40]), "+f"(d[41]), "+f"(d[42]), "+f"(d[43]), "+f"(d[44]), "+f"(d[45]), "+f"(d[46]), "+f"(d[47]), "+f"(d[48]), "+f"(d[49]), "+f"(d[50]), "+f"(d[51]), "+f"(d[52]), "+f"(d[53]), "+f"(d[54]), "+f"(d[55]), "+f"(d[56]), "+f"(d[57]), "+f"(d[58]), "+f"(d[59]), "+f"(d[60]), "+f"(d[61]), "+f"(d[62]), "+f"(d[63])
    : "r"(a0), "r"(a1), "r"(a2), "r"(a3), "r"(b_lo), "r"(scaleD), "n"(OFFB));
}

__device__ __forceinline__ uint4 ldg_nc_v4(const void* p) {
  uint4 v;
    asm volatile("{\n.reg .b64 pol;\ncreatepolicy.fractional.L2::evict_first.b64 pol, 1.0;\n"
                 "ld.global.nc.L1::no_allocate.L2::cache_hint.v4.u32 {%0, %1, %2, %3}, [%4], pol;\n}\n" : "=r"(v.x), "=r"(v.y), "=r"(v.z), "=r"(v.w) : "l"(p));
  return v;
}
__device__ __forceinline__ uint64_t pol_normal() {
  uint64_t p; asm volatile("createpolicy.fractional.L2::evict_normal.b64 %0, 1.0;" : "=l"(p)); return p;
}
__device__ __forceinline__ float rcp_approx(float x) { float y; asm("rcp.approx.ftz.f32 %0, %1;" : "=f"(y) : "f"(x)); return y; }
__device__ __forceinline__ float sigmoid_f(float v) { return rcp_approx(1.0f + ex2_approx(v * -1.4426950408889634f)); }
__device__ __forceinline__ float silu_bf(float v) { return rbf(v * sigmoid_f(v)); }
__device__ __forceinline__ uint32_t rank_key(float r, int idx) {
  const uint32_t b = __float_as_uint(r) >> 16;
  const uint32_t u = (r != r) ? 0u : ((b & 0x8000u) ? (~b & 0xffffu) : (b | 0x8000u));
  return (u << 16) | (0xffffu - (uint32_t)idx);
}
__device__ __forceinline__ void warp_top2(uint32_t& k1, uint32_t& k2) {
  const uint32_t m1 = __reduce_max_sync(0xffffffffu, k1);
  k2 = __reduce_max_sync(0xffffffffu, k1 == m1 ? k2 : k1);
  k1 = m1;
}
__device__ __forceinline__ uint32_t bmul2(uint32_t a, uint32_t b) { uint32_t r; asm("mul.rn.bf16x2 %0, %1, %2;" : "=r"(r) : "r"(a), "r"(b)); return r; }
__device__ __forceinline__ uint32_t badd2(uint32_t a, uint32_t b) { uint32_t r; asm("add.rn.bf16x2 %0, %1, %2;" : "=r"(r) : "r"(a), "r"(b)); return r; }
__device__ __forceinline__ uint32_t bsub2(uint32_t a, uint32_t b) { uint32_t r; asm("sub.rn.bf16x2 %0, %1, %2;" : "=r"(r) : "r"(a), "r"(b)); return r; }
__device__ __forceinline__ float sqrt_approx(float x) { float y; asm("sqrt.approx.f32 %0, %1;" : "=f"(y) : "f"(x)); return y; }
__device__ __forceinline__ uint32_t ln_norm2(uint32_t x1, uint32_t mb2, float inv) {
  const uint32_t d = bsub2(x1, mb2);
  return pack_bf16(bflo(d) * inv, bfhi(d) * inv);
}
__device__ __forceinline__ uint32_t ln_mod2(uint32_t x1, uint32_t mb2, float inv, uint32_t c1, uint32_t sb) { return badd2(bmul2(ln_norm2(x1, mb2, inv), c1), sb); }
__device__ __forceinline__ void ldmatrix_x4(uint32_t addr, uint32_t& r0, uint32_t& r1, uint32_t& r2, uint32_t& r3) {
  asm volatile("ldmatrix.sync.aligned.m8n8.x4.shared.b16 {%0, %1, %2, %3}, [%4];" : "=r"(r0), "=r"(r1), "=r"(r2), "=r"(r3) : "r"(addr) : "memory");
}
__device__ __forceinline__ uint4 ldg_stream_v4(const void* p, uint64_t pol) {
  uint4 v; asm volatile("ld.global.nc.L1::no_allocate.L2::cache_hint.L2::128B.v4.u32 {%0, %1, %2, %3}, [%4], %5;" : "=r"(v.x), "=r"(v.y), "=r"(v.z), "=r"(v.w) : "l"(p), "l"(pol)); return v;
}
__device__ __forceinline__ void bulk_load_hint(uint32_t dst, const void* src, uint32_t bytes, uint32_t bar, uint64_t pol) {
  asm volatile("cp.async.bulk.shared::cluster.global.mbarrier::complete_tx::bytes.L2::cache_hint [%0], [%1], %2, [%3], %4;"
    :: "r"(dst), "l"(src), "r"(bytes), "r"(bar), "l"(pol) : "memory");
}
__device__ __forceinline__ void red_release_add(unsigned int* p, unsigned int v) { asm volatile("red.release.gpu.global.add.u32 [%0], %1;" :: "l"(p), "r"(v) : "memory"); }
__device__ __forceinline__ unsigned int ld_acquire(const unsigned int* p) { unsigned int v; asm volatile("ld.acquire.gpu.global.u32 %0, [%1];" : "=r"(v) : "l"(p) : "memory"); return v; }
__device__ __forceinline__ void spin_until(const unsigned int* p, unsigned int target) {
  #pragma unroll 1
  for (unsigned int i = 0; i < (1u << 22); i++) { if (ld_acquire(p) >= target) return; }
}
__device__ __forceinline__ float lds_f32(uint32_t a) { float v; asm volatile("ld.shared.f32 %0, [%1];" : "=f"(v) : "r"(a) : "memory"); return v; }
__device__ __forceinline__ float2 lds_f32x2(uint32_t a) { float2 v; asm volatile("ld.shared.v2.f32 {%0, %1}, [%2];" : "=f"(v.x), "=f"(v.y) : "r"(a) : "memory"); return v; }
__device__ __forceinline__ uint2 lds_u32x2(uint32_t a) { uint2 v; asm volatile("ld.shared.v2.u32 {%0, %1}, [%2];" : "=r"(v.x), "=r"(v.y) : "r"(a) : "memory"); return v; }
__device__ __forceinline__ uint32_t lds_u32(uint32_t a) { uint32_t v; asm volatile("ld.shared.u32 %0, [%1];" : "=r"(v) : "r"(a) : "memory"); return v; }
__device__ __forceinline__ void sts_u32(uint32_t a, uint32_t v) { asm volatile("st.shared.u32 [%0], %1;" :: "r"(a), "r"(v) : "memory"); }
__device__ __forceinline__ void sts_u32x2(uint32_t a, uint32_t x, uint32_t y) { asm volatile("st.shared.v2.u32 [%0], {%1, %2};" :: "r"(a), "r"(x), "r"(y) : "memory"); }
__device__ __forceinline__ void sts_f32(uint32_t a, float v) { asm volatile("st.shared.f32 [%0], %1;" :: "r"(a), "f"(v) : "memory"); }
__device__ __forceinline__ void sts_f32x4(uint32_t a, float x, float y, float z, float w) { asm volatile("st.shared.v4.f32 [%0], {%1, %2, %3, %4};" :: "r"(a), "f"(x), "f"(y), "f"(z), "f"(w) : "memory"); }

__device__ __forceinline__ uint4 lds_u32x4(uint32_t a) { uint4 v; asm volatile("ld.shared.v4.u32 {%0, %1, %2, %3}, [%4];" : "=r"(v.x), "=r"(v.y), "=r"(v.z), "=r"(v.w) : "r"(a) : "memory"); return v; }
__device__ __forceinline__ void sts_u32x4(uint32_t a, uint32_t x, uint32_t y, uint32_t z, uint32_t w) { asm volatile("st.shared.v4.u32 [%0], {%1, %2, %3, %4};" :: "r"(a), "r"(x), "r"(y), "r"(z), "r"(w) : "memory"); }
__device__ __forceinline__ void st_tagged(float* p, float v) {
  const uint32_t b = __float_as_uint(v);
  asm volatile("st.relaxed.gpu.global.u32 [%0], %1;" :: "l"(p), "r"(b == 0u ? 0x80000000u : b) : "memory");
}
__device__ __forceinline__ void st_tagged4(float* p, float x, float y, float z, float w) {
  const uint32_t a = __float_as_uint(x), b = __float_as_uint(y), c = __float_as_uint(z), d = __float_as_uint(w);
  asm volatile("st.relaxed.gpu.global.v4.u32 [%0], {%1, %2, %3, %4};" :: "l"(p), "r"(a == 0u ? 0x80000000u : a), "r"(b == 0u ? 0x80000000u : b),
               "r"(c == 0u ? 0x80000000u : c), "r"(d == 0u ? 0x80000000u : d) : "memory");
}
__device__ __forceinline__ void st_relaxed2(void* p, uint32_t a, uint32_t b) { asm volatile("st.relaxed.gpu.global.v2.u32 [%0], {%1, %2};" :: "l"(p), "r"(a), "r"(b) : "memory"); }
__device__ __forceinline__ float4 ld_tagged4(const float* p) {
  float4 v; asm volatile("ld.relaxed.gpu.global.v4.f32 {%0, %1, %2, %3}, [%4];" : "=f"(v.x), "=f"(v.y), "=f"(v.z), "=f"(v.w) : "l"(p) : "memory"); return v;
}
__device__ __forceinline__ bool tagged4(const float4& v) {
  return __float_as_uint(v.x) != 0u && __float_as_uint(v.y) != 0u && __float_as_uint(v.z) != 0u && __float_as_uint(v.w) != 0u;
}
__device__ __forceinline__ void hint_arrive(uint32_t* p) { asm volatile("red.relaxed.gpu.global.add.u32 [%0], 1;" :: "l"(p) : "memory"); }
__device__ __forceinline__ void hint_wait(const uint32_t* p, uint32_t target) {
  uint32_t v = 0u;
  #pragma unroll 1
  for (unsigned int i = 0; i < (1u << 22) && v < target; i++) asm volatile("ld.relaxed.gpu.global.u32 %0, [%1];" : "=r"(v) : "l"(p) : "memory");
}
__device__ __forceinline__ void fence_proxy_async_global() { asm volatile("fence.proxy.async.global;" ::: "memory"); }

__device__ __forceinline__ void mma_bf16(float (&d)[4], uint32_t a0, uint32_t a1, uint32_t a2, uint32_t a3, uint32_t b0, uint32_t b1) {
  asm volatile("mma.sync.aligned.m16n8k16.row.col.f32.bf16.bf16.f32 {%0, %1, %2, %3}, {%4, %5, %6, %7}, {%8, %9}, {%0, %1, %2, %3};"
               : "+f"(d[0]), "+f"(d[1]), "+f"(d[2]), "+f"(d[3]) : "r"(a0), "r"(a1), "r"(a2), "r"(a3), "r"(b0), "r"(b1));
}
__device__ __forceinline__ uint32_t bfma2(uint32_t a, uint32_t b, uint32_t c) { uint32_t r; asm("fma.rn.bf16x2 %0, %1, %2, %3;" : "=r"(r) : "r"(a), "r"(b), "r"(c)); return r; }
#define PRE_T 1000
#define WDLY 3000
#define GDLY 4000
#define GDLY2 8000
#define ST1_T 6000
#define A_T 4500
#define QT0 0
#define QTO 0
#define QTN 0
#define QARR 4
#define WCH 4
#define QORD 0
#define PACE 128
#define EREL 0
#define EA0 1
#define PINQ 1
#define PINS 0
#define SYN_G 0
#define SYN_S 2
#define GSLP 50
#define DROPN 2
#define SERP 1
#define DYN 1
#define ASLP 8000
#define CPCM 1
#define ZMMA 0
#define LATEF 0
#define NDUM 16
#define XDLY 1000
#define SDLY 5800
#define EPOLL 1
__device__ __forceinline__ uint32_t clock_lo() { uint32_t c; asm volatile("mov.u32 %0, %%clock;" : "=r"(c) :: "memory"); return c; }
__device__ __forceinline__ void wait_clock(uint32_t t0, uint32_t n) {
  #pragma unroll 1
  while (clock_lo() - t0 < n) {}
}
__device__ __forceinline__ float2 ld_tagged2(const float2* p) {
  float2 v; asm volatile("ld.relaxed.gpu.global.v2.f32 {%0, %1}, [%2];" : "=f"(v.x), "=f"(v.y) : "l"(p) : "memory"); return v;
}
template <int N, int NW>
__device__ __forceinline__ float gemv64(const uint4 (&w)[N], const uint32_t (&sv)[N / 2], uint32_t scr, int t2) {
  const int lane = t2 & 31, g = lane >> 2;
  const uint32_t lo = (g & 1) ? 0x1044u : 0x4410u, hi = (g & 1) ? 0x3244u : 0x4432u;
  const uint32_t lo0 = g < 2 ? lo : 0x4444u, hi0 = g < 2 ? hi : 0x4444u, lo1 = (g & 6) == 2 ? lo : 0x4444u, hi1 = (g & 6) == 2 ? hi : 0x4444u;
  float d[2][4] = {{0.f, 0.f, 0.f, 0.f}, {0.f, 0.f, 0.f, 0.f}};
  #pragma unroll
  for (int i = 0; i < N; i++)
    mma_bf16(d[i & 1], w[i].x, w[i].y, w[i].z, w[i].w, __byte_perm(sv[i >> 1], 0u, (i & 1) ? hi0 : lo0), __byte_perm(sv[i >> 1], 0u, (i & 1) ? hi1 : lo1));
  if ((lane & 2) == 0) sts_f32x4(scr + (t2 >> 5) * 256 + g * 32 + (lane & 1) * 16, d[0][0] + d[1][0], d[0][1] + d[1][1], d[0][2] + d[1][2], d[0][3] + d[1][3]);
  named_bar_sync(NW == 8 ? 5 : 3, NW * 32);
  float sum = 0.f;
  if (t2 < 64) {
    #pragma unroll
    for (int i = 0; i < NW; i += 2) sum += lds_f32(scr + i * 256 + t2 * 4) + lds_f32(scr + i * 256 + 256 + t2 * 4);
  }
  return sum;
}
__device__ __forceinline__ uint32_t silu2(uint32_t c) { return pack_bf16(silu_bf(bflo(c)), silu_bf(bfhi(c))); }
__device__ __forceinline__ void head_first(Scratch* hm, uint32_t scr, int t2, const bf16* __restrict__ cvec, const bf16* __restrict__ w_mod) {
  const int row = (blockIdx.x >> 3) * 64 + (t2 >> 5) * 16 + (t2 & 3) * 4;
  const bf16* wp = w_mod + (size_t)row * (6 * T_D) + (blockIdx.x & 4) * 256 + (blockIdx.x & 3) * 64 + (t2 & 28) * 2;
  uint4 w[4];
  #pragma unroll
  for (int i = 0; i < 4; i++) w[i] = ldg_nc_v4(wp + i * 6 * T_D);
  const uint2 c = *reinterpret_cast<const uint2*>(cvec + row);
  const uint32_t sv[2] = {silu2(c.x), silu2(c.y)};
  const float sum = gemv64<4, 4>(w, sv, scr, t2);
  if (t2 < 64) st_tagged(hm->modu + (blockIdx.x >> 3) * 512 + (blockIdx.x & 7) * 64 + t2, sum);
  HS(1);
}
__device__ __forceinline__ void head_stats(Scratch* hm, uint32_t xs, uint32_t b_x, int tid) {
  const int lane = tid & 31, w = tid >> 5, g = lane >> 2;
  float d[4][4] = {{0.f, 0.f, 0.f, 0.f}, {0.f, 0.f, 0.f, 0.f}, {0.f, 0.f, 0.f, 0.f}, {0.f, 0.f, 0.f, 0.f}};
  const uint32_t xa = xs + ((w & 1) * 8 + g) * 2048 + (w >> 1) * 1024 + (g & 1) * 64 + (lane & 3) * 16;
  float2* dst = hm->stat + ((blockIdx.x * 2 + (w & 1)) * 2 + (w >> 1)) * 8 + g;
  mbar_wait(b_x, 0);
  #pragma unroll
  for (int j = 0; j < 16; j++) {
    const uint4 v = lds_u32x4((xa ^ ((j & 1) * 64)) + (j >> 1) * 128);
    mma_bf16(d[2 * (j & 1)], v.x, 0x3F803F80u, v.y, 0x3F803F80u, v.x, v.y);
    mma_bf16(d[2 * (j & 1) + 1], v.z, 0x3F803F80u, v.w, 0x3F803F80u, v.z, v.w);
  }
  #pragma unroll
  for (int e = 0; e < 4; e++) d[0][e] = (d[0][e] + d[1][e]) + (d[2][e] + d[3][e]);
  const uint32_t sm = __float_as_uint((g & 1) ? d[0][3] : d[0][2]), sq = __float_as_uint((g & 1) ? d[0][1] : d[0][0]);
  if ((lane & 3) == (g >> 1)) st_relaxed2(dst, sm == 0u ? 0x80000000u : sm, sq == 0u ? 0x80000000u : sq);
  HSD(3, sm);
}
__device__ __forceinline__ void put_table(uint32_t tab, int l, bool ca, const float4& v) {
  uint32_t m0 = pack_bf16(v.x, v.y), m1 = pack_bf16(v.z, v.w);
  if (ca) { m0 = badd2(m0, 0x3F803F80u); m1 = badd2(m1, 0x3F803F80u); }
  tab += (l >> 2) * 64 + (l & 1) * 32 + (l & 2) * 2 + (ca ? 0 : 8);
  sts_u32(tab, m0); sts_u32(tab + 16, m1);
}
__device__ __forceinline__ void head_gather(Scratch* hm, uint32_t tab, int tid) {
  float4 p[16];
  #pragma unroll 1
  for (unsigned int spin = 0; spin < (1u << 22); spin++) {
    uint32_t m = 0xffffffffu;
    #pragma unroll
    for (int k = 0; k < 16; k++) p[k] = ld_tagged4(hm->modu + k * 512 + tid * 4);
    #pragma unroll
    for (int k = 0; k < 16; k++) m = min(min(m, min(__float_as_uint(p[k].x), __float_as_uint(p[k].y))), min(__float_as_uint(p[k].z), __float_as_uint(p[k].w)));
    if (m != 0u) break;
  }
  #pragma unroll
  for (int o = 1; o < 16; o <<= 1)
    #pragma unroll
    for (int k = 0; k < 16; k += 2 * o) { p[k].x += p[k + o].x; p[k].y += p[k + o].y; p[k].z += p[k + o].z; p[k].w += p[k + o].w; }
  put_table(tab, tid & 63, tid >= 64, p[0]);
  __syncwarp();
  HS(2);
}
__device__ __forceinline__ float mod_cols(uint32_t sbase, uint32_t sc, uint32_t bar, uint32_t par, int t2, const CUtensorMap* tm, int col) {
  fence_proxy_async();
  named_bar_sync(5, 256);
  if (t2 == 0) {
    const uint64_t pol = policy_evict_first();
    mbar_expect_tx(bar, 131072);
    #pragma unroll 1
    for (int i = 0; i < 4; i++) tma_load_2d_hint(sbase + (i == 3 ? 5 : i) * 32768, tm, col, i * 256, bar, pol);
  }
  __syncwarp();
  const int w8 = t2 >> 5, t = t2 & 3, g = (t2 >> 2) & 7;
  const uint32_t wa = sbase + (w8 >= 6 ? w8 + 4 : w8) * 16384 + t * 256;
  uint4 w[32];
  uint32_t sv[16];
  #pragma unroll
  for (int i = 0; i < 16; i++) sv[i] = lds_u32(sc + w8 * 256 + i * 16 + t * 4);
  mbar_wait(bar, par);
  #pragma unroll
  for (int i = 0; i < 32; i++) w[i] = lds_u32x4(wa + (i >> 1) * 1024 + (i & 1) * 128 + ((g ^ (t * 2 + (i & 1))) << 4));
  return gemv64<32, 8>(w, sv, sc + 2048, t2);
}
__device__ __forceinline__ uint32_t ln_stat(float sm, float sq) {
  const float mean = sm * (1.0f / T_D), var = fmaxf(fmaf(-mean, mean, sq * (1.0f / T_D)), 0.f);
  return pack_bf16(mean, sqrt_approx(rbf(rbf(var) + 1e-05f)));
}
__device__ __forceinline__ void gather_table(Scratch* hm, uint32_t t0, uint32_t tab0, uint32_t b_tab, int a, int lane) {
  wait_clock(t0, GDLY2);
  #pragma unroll 1
  for (int r = 2; r < 8; r++) {
    float4 v;
    #pragma unroll 1
    for (unsigned int spin = 0; spin < (1u << 22); spin++) {
      v = ld_tagged4(hm->mod + a * T_D + r * 128 + lane * 4);
      if (tagged4(v)) break;
      if (GSLP) __nanosleep(GSLP);
    }
    put_table(tab0 + r * 512, lane, a, v);
    if (r == 7) {
      fence_proxy_async();
      named_bar_sync(8, 64);
      if (a == 0 && elect_one()) {
        asm volatile("cp.async.bulk.global.shared::cta.bulk_group [%0], [%1], 4096;" :: "l"(hm->tab + blockIdx.x * 4096), "r"(tab0) : "memory");
        bulk_commit();
        bulk_wait<0>();
      }
    }
    __syncwarp();
    if (lane == 0) mbar_arrive(b_tab + 8 * r);
    if (r < 6) HS(2 + r);
  }
}

__device__ __forceinline__ uint32_t assign_tile(Scratch* hm, uint32_t t0, int lane) {
  uint32_t me; asm("mov.u32 %0, %%smid;" : "=r"(me));
  me = (me & 255u) + 1u;
  if (lane == 0) asm volatile("st.relaxed.gpu.global.u32 [%0], %1;" :: "l"(hm->gkey + blockIdx.x), "r"((t0 & ~511u) | me) : "memory");
  uint32_t k[5];
  #pragma unroll 1
  for (unsigned int spin = 0; spin < (1u << 20); spin++) {
    __nanosleep(ASLP);
    #pragma unroll
    for (int m = 0; m < 5; m++) asm volatile("ld.relaxed.gpu.global.u32 %0, [%1];" : "=r"(k[m]) : "l"(hm->gkey + m * 32 + lane) : "memory");
    if (__all_sync(0xffffffffu, k[0] != 0u && k[1] != 0u && k[2] != 0u && k[3] != 0u && (k[4] != 0u || lane >= 4))) break;
  }
  uint32_t sz = 0u, g = 0u, rank = 0u;
  #pragma unroll 1
  for (int i = 0; i < 16; i++) {
    const uint32_t v = __reduce_max_sync(0xffffffffu, max(max(max(k[0], k[1]), max(k[2], k[3])), k[4]));
    uint32_t n = 0u;
    #pragma unroll
    for (int m = 0; m < 5; m++)
      if (k[m] != 0u && (v - k[m] < 4096u || i == 15)) { n += 1u + ((k[m] & 511u) < me ? 256u : 0u) + ((k[m] & 511u) == me ? 65536u : 0u); k[m] = 0u; }
    n = __reduce_add_sync(0xffffffffu, n);
    if (lane == i) sz = n & 255u;
    if (n >> 16) { g = i; rank = (n >> 8) & 255u; }
  }
  #pragma unroll 1
  for (int d = 0; d < 4; d += DROPN)
    if ((__reduce_max_sync(0xffffffffu, sz * 32u + lane) & 31u) == (uint32_t)lane) sz -= DROPN;
  const uint32_t gs = __shfl_sync(0xffffffffu, sz, g);
  const uint32_t off = __reduce_add_sync(0xffffffffu, (sz != 16u) * 32u + lane < (gs != 16u) * 32u + g ? sz : 0u);
  return rank < gs ? off + rank : 128u;
}

__device__ __forceinline__ void mod_rest(Scratch* hm, uint32_t sbase, uint32_t bar, int t2, int j, const bf16* __restrict__ cvec, const CUtensorMap* tm, const bf16* __restrict__ w_r) {
  const uint32_t scr = sbase + 4 * 32768 + 8192;
  const uint2 c4 = *reinterpret_cast<const uint2*>(cvec + t2 * 4);
  sts_u32x2(scr + t2 * 8, silu2(c4.x), silu2(c4.y));
  const int kind = j >> 1;
  float dot = 0.f;
  #pragma unroll 1
  for (int b = -3; b < 8; b++) {
    const int c0 = b < 0 ? (j & 1) * T_D + (b + 4) * 256 + (kind ^ 2) * 64 : 2 * T_D + j * 512 + b * 64;
    float v = mod_cols(sbase, scr, bar, (b & 1) ^ 1, t2, tm, c0);
    if (t2 < 64) {
      if (b < 0) st_tagged(hm->mod + c0 + t2, v);
      else {
        const int col = (c0 + t2) & 1023;
        uint8_t* dst = g_col + (col >> 7) * 1536;
        v = rbf(v);
        if (kind == 2) v = rbf(1.0f + v);
        const float vw = v * __bfloat162float(w_r[col]);
        dot += vw;
        if (kind == 2) {
          const int c = col & 127, i = (c & ~15) + ((c >> 1) & 3) * 4 + ((c >> 3) & 1) * 2 + (c & 1);
          reinterpret_cast<bf16*>(dst)[i] = __float2bfloat16_rn(vw);
          reinterpret_cast<bf16*>(dst)[128 + i] = __float2bfloat16_rn(vw - rbf(vw));
        }
        reinterpret_cast<bf16*>(dst + 512 + (kind == 0 ? 0 : kind == 2 ? 256 : kind == 1 ? 512 : 768))[col & 127] = __float2bfloat16_rn(v);
      }
    }
  }
  #pragma unroll
  for (int o = 16; o > 0; o >>= 1) dot += __shfl_xor_sync(0xffffffffu, dot, o);
  if (t2 == 32) sts_f32(scr + 4096, dot);
  fence_proxy_async();
  named_bar_sync(5, 256);
  if (t2 == 0 && (kind == 1 || kind == 2)) g_scal[(kind == 2 ? 0 : 2) + (j & 1)] = dot + lds_f32(scr + 4096);
}

constexpr int AT_NBLK = T_SEQ / 128;
constexpr float AT_HEAD = 7.0f;
constexpr int WO_LATE = 12;
#define QSTG 3
constexpr int QP_STAG = QSTG;
constexpr int AT_SPLIT = 28, AT_PIN = 8, PINB = 4;
constexpr int AT_NFULL = 124;
constexpr int AT_PREG = 40, AT_CREG = 232;
constexpr uint32_t AT_SQ = 5 * 32768;
constexpr float AT_C = 0.08838834764831845f * 1.4426950408889634f;
constexpr float AT_RAW_LO = -16.0f, AT_RAW_HI = 24.0f;
constexpr float AT_RAW_SUM = 281474976710656.0f, AT_RAW_MIN = 9.094947017729282e-13f;
constexpr uint32_t AT_SBAR = AT_SQ + 65536 + 256;
constexpr uint32_t AT_SMEM = AT_SQ + 65536 + 3072;

__device__ __forceinline__ uint32_t ring_slot(uint32_t t) { return t - 5u * ((t * 205u) >> 10); }
__device__ __forceinline__ uint32_t qp_pos(uint32_t j, uint32_t it) { return 4u * it + (j & 3u) + ((j & 3u) == 3u ? it : 0u); }
__device__ __forceinline__ uint32_t ring_par(uint32_t t) { return ((t * 205u) >> 10) & 1u; }
__device__ __forceinline__ void softmax_rowmax(const float (&s)[64], float& mx0, float& mx1) {
  float a0 = fmaxf(s[0], s[1]), a1 = fmaxf(s[4], s[5]), a2 = fmaxf(s[8], s[9]), a3 = fmaxf(s[12], s[13]);
  float b0 = fmaxf(s[2], s[3]), b1 = fmaxf(s[6], s[7]), b2 = fmaxf(s[10], s[11]), b3 = fmaxf(s[14], s[15]);
  #pragma unroll
  for (int j = 4; j < 16; j += 4) {
    a0 = fmaxf(a0, fmaxf(s[4 * j + 0], s[4 * j + 1]));  b0 = fmaxf(b0, fmaxf(s[4 * j + 2], s[4 * j + 3]));
    a1 = fmaxf(a1, fmaxf(s[4 * j + 4], s[4 * j + 5]));  b1 = fmaxf(b1, fmaxf(s[4 * j + 6], s[4 * j + 7]));
    a2 = fmaxf(a2, fmaxf(s[4 * j + 8], s[4 * j + 9]));  b2 = fmaxf(b2, fmaxf(s[4 * j + 10], s[4 * j + 11]));
    a3 = fmaxf(a3, fmaxf(s[4 * j + 12], s[4 * j + 13])); b3 = fmaxf(b3, fmaxf(s[4 * j + 14], s[4 * j + 15]));
  }
  mx0 = fmaxf(fmaxf(a0, a1), fmaxf(a2, a3));
  mx1 = fmaxf(fmaxf(b0, b1), fmaxf(b2, b3));
  mx0 = fmaxf(mx0, __shfl_xor_sync(0xffffffffu, mx0, 1));
  mx1 = fmaxf(mx1, __shfl_xor_sync(0xffffffffu, mx1, 1));
  mx0 = fmaxf(mx0, __shfl_xor_sync(0xffffffffu, mx0, 2));
  mx1 = fmaxf(mx1, __shfl_xor_sync(0xffffffffu, mx1, 2));
}
__device__ __forceinline__ void softmax_sub(float (&s)[64], float mc0, float mc1) {
  #pragma unroll
  for (int j = 0; j < 16; j++) { s[4 * j] -= mc0; s[4 * j + 1] -= mc0; s[4 * j + 2] -= mc1; s[4 * j + 3] -= mc1; }
}
template <int LO, int HI>
__device__ __forceinline__ void softmax_exp(float (&s)[64]) {
  #pragma unroll
  for (int i = LO; i < HI; i++) s[i] = ex2_approx(s[i]);
}
__device__ __forceinline__ bool softmax_mode(const float (&s)[64], float& mc0, float& mc1) {
  softmax_rowmax(s, mc0, mc1);
  const bool raw = __all_sync(0xffffffffu, mc0 >= AT_RAW_LO && mc0 <= AT_RAW_HI && mc1 >= AT_RAW_LO && mc1 <= AT_RAW_HI);
  mc0 += AT_HEAD; mc1 += AT_HEAD;
  return raw;
}
__device__ __forceinline__ void rowsum_p(const uint32_t (&p)[32], uint32_t& t0, uint32_t& t1) {
  uint32_t a[16];
  #pragma unroll
  for (int i = 0; i < 8; i++) { a[2 * i] = badd2(p[4 * i], p[4 * i + 2]); a[2 * i + 1] = badd2(p[4 * i + 1], p[4 * i + 3]); }
  #pragma unroll
  for (int i = 0; i < 4; i++) { a[2 * i] = badd2(a[4 * i], a[4 * i + 2]); a[2 * i + 1] = badd2(a[4 * i + 1], a[4 * i + 3]); }
  t0 = badd2(badd2(a[0], a[2]), badd2(a[4], a[6]));
  t1 = badd2(badd2(a[1], a[3]), badd2(a[5], a[7]));
}
__device__ __forceinline__ void add_rowsum(const uint32_t (&p)[32], float& l0, float& l1) {
  uint32_t t0, t1;
  rowsum_p(p, t0, t1);
  l0 += bflo(t0) + bfhi(t0); l1 += bflo(t1) + bfhi(t1);
}
__device__ __forceinline__ void pack_p(uint32_t (&p)[32], const float (&s)[64]) {
  #pragma unroll
  for (int i = 0; i < 32; i++) p[i] = pack_bf16(s[2 * i], s[2 * i + 1]);
}
__device__ __noinline__ void attn_rows_exact(uint32_t sq, int warp, int lane, const bf16* __restrict__ kh, const bf16* __restrict__ vh) {
  #pragma unroll 1
  for (int r = 16 * warp; r < 16 * warp + 16; r++) {
    const uint32_t ad = (lane >> 4) * 16384 + r * 128 + ((((lane & 15) >> 1) ^ (r & 7)) << 4) + (lane & 1) * 8;
    uint2 qv; asm volatile("ld.shared.v2.u32 {%0, %1}, [%2];" : "=r"(qv.x), "=r"(qv.y) : "r"(sq + ad) : "memory");
    const float q0 = bflo(qv.x), q1 = bfhi(qv.x), q2 = bflo(qv.y), q3 = bfhi(qv.y);
    float m = -INFINITY, l = 0.f, o0 = 0.f, o1 = 0.f, o2 = 0.f, o3 = 0.f;
    #pragma unroll 1
    for (int key = 0; key < T_SEQ; key++) {
      const uint2 kv = *reinterpret_cast<const uint2*>(kh + (size_t)key * T_DH + lane * 4);
      const uint2 vv = *reinterpret_cast<const uint2*>(vh + (size_t)key * T_DH + lane * 4);
      float sc = (q0 * bflo(kv.x) + q1 * bfhi(kv.x)) + (q2 * bflo(kv.y) + q3 * bfhi(kv.y));
      #pragma unroll
      for (int o = 16; o > 0; o >>= 1) sc += __shfl_xor_sync(0xffffffffu, sc, o);
      const float mn = fmaxf(m, sc);
      const float al = (m == mn) ? 1.0f : ex2_approx(m - mn), p = rbf(ex2_approx(sc - mn));
      m = mn;
      l = fmaf(l, al, p);
      o0 = fmaf(o0, al, p * bflo(vv.x)); o1 = fmaf(o1, al, p * bfhi(vv.x));
      o2 = fmaf(o2, al, p * bflo(vv.y)); o3 = fmaf(o3, al, p * bfhi(vv.y));
    }
    const float inv = rcp_approx(l);
    asm volatile("st.shared.v2.u32 [%0], {%1, %2};" :: "r"(sq + ad), "r"(pack_bf16(o0 * inv, o1 * inv)), "r"(pack_bf16(o2 * inv, o3 * inv)) : "memory");
  }
}
__device__ __forceinline__ void issue_qk(float (&s)[64], const uint32_t (&q)[32], uint32_t k_lo) {
  wgmma_fence();
  wgmma_m64n128k16_rs<0>(s, q[0], q[1], q[2], q[3], k_lo, 0);
  wgmma_m64n128k16_rs<2>(s, q[4], q[5], q[6], q[7], k_lo, 1);
  wgmma_m64n128k16_rs<4>(s, q[8], q[9], q[10], q[11], k_lo, 1);
  wgmma_m64n128k16_rs<6>(s, q[12], q[13], q[14], q[15], k_lo, 1);
  wgmma_m64n128k16_rs<1024>(s, q[16], q[17], q[18], q[19], k_lo, 1);
  wgmma_m64n128k16_rs<1026>(s, q[20], q[21], q[22], q[23], k_lo, 1);
  wgmma_m64n128k16_rs<1028>(s, q[24], q[25], q[26], q[27], k_lo, 1);
  wgmma_m64n128k16_rs<1030>(s, q[28], q[29], q[30], q[31], k_lo, 1);
  wgmma_commit();
}
__device__ __forceinline__ void issue_pv(float (&o)[64], const uint32_t (&p)[32], uint32_t v_lo, int accumulate) {
  wgmma_fence();
  wgmma_m64n128k16_rs_tb<0>(o, p[0], p[1], p[2], p[3], v_lo, accumulate);
  wgmma_m64n128k16_rs_tb<128>(o, p[4], p[5], p[6], p[7], v_lo, 1);
  wgmma_m64n128k16_rs_tb<256>(o, p[8], p[9], p[10], p[11], v_lo, 1);
  wgmma_m64n128k16_rs_tb<384>(o, p[12], p[13], p[14], p[15], v_lo, 1);
  wgmma_m64n128k16_rs_tb<512>(o, p[16], p[17], p[18], p[19], v_lo, 1);
  wgmma_m64n128k16_rs_tb<640>(o, p[20], p[21], p[22], p[23], v_lo, 1);
  wgmma_m64n128k16_rs_tb<768>(o, p[24], p[25], p[26], p[27], v_lo, 1);
  wgmma_m64n128k16_rs_tb<896>(o, p[28], p[29], p[30], p[31], v_lo, 1);
  wgmma_commit();
}
__device__ __forceinline__ void rescale_o(float (&o)[64], float al0, float al1) {
  #pragma unroll
  for (int j = 0; j < 16; j++) { o[4 * j] *= al0; o[4 * j + 1] *= al0; o[4 * j + 2] *= al1; o[4 * j + 3] *= al1; }
}

__device__ __forceinline__ void stage_o(const float (&o)[64], float i0, float i1, uint32_t dst, int lane) {
  #pragma unroll
  for (int J = 0; J < 16; J += 2)
    stmatrix_x4(dst + (J >> 3) * 16384 + ((((J & 7) + (lane >> 4)) ^ (lane & 7)) << 4),
                pack_bf16(o[4 * J + 0] * i0, o[4 * J + 1] * i0), pack_bf16(o[4 * J + 2] * i1, o[4 * J + 3] * i1),
                pack_bf16(o[4 * J + 4] * i0, o[4 * J + 5] * i0), pack_bf16(o[4 * J + 6] * i1, o[4 * J + 7] * i1));
}
__device__ __forceinline__ bool finish_l(float& l0, float& l1) {
  l0 += __shfl_xor_sync(0xffffffffu, l0, 1); l1 += __shfl_xor_sync(0xffffffffu, l1, 1);
  l0 += __shfl_xor_sync(0xffffffffu, l0, 2); l1 += __shfl_xor_sync(0xffffffffu, l1, 2);
  const bool redo = __any_sync(0xffffffffu, !(l0 <= AT_RAW_SUM && l1 <= AT_RAW_SUM && l0 >= AT_RAW_MIN && l1 >= AT_RAW_MIN));
  l0 = rcp_approx(l0); l1 = rcp_approx(l1);
  return redo;
}
__device__ __forceinline__ void stage_qregs(const uint32_t (&q)[32], uint32_t dst, int lane) {
  #pragma unroll
  for (int J = 0; J < 16; J += 2)
    stmatrix_x4(dst + (J >> 3) * 16384 + ((((J & 7) + (lane >> 4)) ^ (lane & 7)) << 4), q[2 * J], q[2 * J + 1], q[2 * J + 2], q[2 * J + 3]);
}
__device__ __forceinline__ void store_o(const CUtensorMap* tmO, uint32_t src, int head, int row) {
  tma_store_2d(tmO, src, head * T_DH, row);
  tma_store_2d(tmO, src + 16384, head * T_DH + 64, row);
  bulk_commit();
}
struct GemvSel { uint32_t lo0, hi0, lo1, hi1; };
__device__ __forceinline__ GemvSel gemv_sel(int lane) {
  const uint32_t lo = (lane & 8) ? 0x1044u : 0x4410u, hi = (lane & 8) ? 0x3244u : 0x4432u;
  GemvSel s; s.lo0 = (lane & 16) ? 0x4444u : lo; s.hi0 = (lane & 16) ? 0x4444u : hi; s.lo1 = (lane & 16) ? lo : 0x4444u; s.hi1 = (lane & 16) ? hi : 0x4444u;
  return s;
}
#define GEMV_B0(j, h, s) __byte_perm((j) < 2 ? (h).x : (h).y, 0u, ((j) & 1) ? (s).hi0 : (s).lo0)
#define GEMV_B1(j, h, s) __byte_perm((j) < 2 ? (h).x : (h).y, 0u, ((j) & 1) ? (s).hi1 : (s).lo1)
__device__ __forceinline__ float4 gemv_out(const float (&d)[4], int lane) {
  const bool tk = lane & 1;
  const float r0 = __shfl_xor_sync(0xffffffffu, tk ? d[0] : d[1], 1), r1 = __shfl_xor_sync(0xffffffffu, tk ? d[2] : d[3], 1);
  return tk ? make_float4(r0, d[1], r1, d[3]) : make_float4(d[0], r0, d[2], r1);
}
#define OG_NG 8
#define OG_GRP (64 / OG_NG)
constexpr int OG_ST = 5, OG_NKB = T_DQKV / 64, OG_MOE = T_F / 32;
constexpr int OG_POS = 8;
constexpr uint32_t OG_STAGE = 32768;
constexpr uint32_t OG_SWD = AT_SQ;
constexpr uint32_t OG_SCOL = AT_SBAR + 512;
constexpr uint32_t OG_SMISC = AT_SBAR + 2048;
constexpr uint32_t OG_XSLOT = ((OG_POS + OG_NKB) % OG_ST) * OG_STAGE;
constexpr uint32_t OG_OSLOT = ((OG_POS + OG_NKB + 1) % OG_ST) * OG_STAGE;
constexpr uint32_t OG_SH2 = ((OG_POS + OG_NKB + 2) % OG_ST) * OG_STAGE;
constexpr uint32_t OG_SRED = ((OG_POS + OG_NKB + 3) % OG_ST) * OG_STAGE;
constexpr uint32_t OG_SSTAT = OG_SRED + 16384;
constexpr uint32_t OG_SGU = OG_SRED + 8192;
constexpr uint32_t OG_SFIN = OG_SGU + 256;
#define OGM 2
#define OG_MT(b) ((((b) >> OGM) & 15) ^ (SERP && ((b) & 64) ? 15 : 0))
#define OG_NT(b) (((b) & ((1 << OGM) - 1)) + (((b) >> (4 + OGM)) << OGM))
#define TAIL_SETUP \
  const uint32_t bar_full = sbase + AT_SBAR, bar_empty = bar_full + 40; \
  const uint32_t bar_wd = bar_full + 168, bar_col = bar_full + 176, bar_out = bar_full + 184, bar_end = bar_full + 192; \
  const uint32_t bar_key = bar_full + 200, bar_h2 = bar_full + 208, bar_sel = bar_full + 216; \
  const int mt = OG_MT(bx), nt = OG_NT(bx); \
  const int m0 = mt * 128, n0 = nt * 128; \
  const bool has_moe = (int)bx < OG_MOE; \
  (void)bar_empty; (void)bar_wd; (void)bar_col; (void)bar_out; (void)bar_end; (void)bar_key; (void)bar_h2; (void)bar_sel; (void)m0; (void)n0; (void)has_moe;

__device__ __forceinline__ void tail_producer(Scratch* hm, uint32_t bx, uint32_t sbase, uint32_t ph, uint32_t obpar, uint64_t pol, const CUtensorMap* tmA, const CUtensorMap* tmB,
                                              const CUtensorMap* tmX, const bf16* __restrict__ w_down) {
  TAIL_SETUP
  const uint32_t b_q0 = bar_full + 80, b_ob = bar_full + 96, b_acq = bar_full + 264;
  uint32_t stage = OG_POS % OG_ST;
  if (has_moe) mbar_expect_tx(bar_wd, 65536);
  mbar_expect_tx(bar_col, 1536 + 16);
  #pragma unroll 1
  for (int kb = 0; kb <= OG_NKB; kb++) {
    const uint32_t fb = bar_full + 8 * stage, sa = sbase + stage * OG_STAGE, sb = sa + 16384;
    mbar_wait(bar_empty + 8 * stage, ph);
    mbar_expect_tx(fb, OG_STAGE);
    if (kb < OG_NKB) {
      tma_load_2d_hint(sb, tmB, n0, kb * 64, fb, pol);
      tma_load_2d_hint(sb + 8192, tmB, n0 + 64, kb * 64, fb, pol);
      if ((kb & 31) == 0) { mbar_wait(b_acq, kb >> 5); fence_proxy_async_global(); }
      tma_load_2d_hint(sa, tmA, kb * 64, m0, fb, pol);
    } else {
      tma_load_2d_hint(sa, tmX, n0, m0, fb, pol);
      tma_load_2d_hint(sb, tmX, n0 + 64, m0, fb, pol);
    }
    if (kb == 32) {
      bulk_load_hint(sbase + OG_SCOL, g_col + nt * 1536, 1536, bar_col, pol);
      bulk_load_hint(sbase + OG_SMISC, g_scal, 16, bar_col, pol);
    }
    if (kb == 6) { mbar_wait(b_q0, obpar); mbar_wait(b_ob, obpar); }
    if (has_moe && (kb & 7) == 6 && kb < 64)
      bulk_load_hint(sbase + OG_SWD + (kb >> 3) * 8224, (const uint8_t*)w_down + (size_t)bx * 65536 + (kb >> 3) * 8192, 8192, bar_wd, pol);
    if (++stage == OG_ST) { stage = 0; ph ^= 1; }
  }
}

__device__ __forceinline__ uint32_t out2(uint32_t x1, uint32_t mb2, uint32_t ih, uint32_t il, uint32_t c1, uint32_t sb, uint32_t gb) {
  const uint32_t d = bsub2(x1, mb2);
  const uint32_t h2 = badd2(bmul2(bfma2(d, ih, bmul2(d, il)), c1), sb);
  return badd2(x1, bmul2(gb, bfma2(h2, 0u, h2)));
}
__device__ __forceinline__ void tail_exchange(Scratch* hm, uint32_t bx, uint32_t sbase, uint32_t tx, const CUtensorMap* tmOut, bf16* __restrict__ out) {
    TAIL_SETUP
    mbar_wait(bar_end, 0);
    const int lane = tx & 31;
    TL_MARK2(22, lane == 0);
    if (tx < 32) {
      uint32_t k1 = 0u, k2 = 0u;
      #pragma unroll 1
      for (unsigned int spin = 0; spin < (1u << 22) && k1 == 0u; spin++) asm volatile("ld.relaxed.gpu.global.u32 %0, [%1];" : "=r"(k1) : "l"(g_key + lane) : "memory");
      __syncwarp();
      TL_MARK2(28, lane == 0);
      warp_top2(k1, k2);
      if (lane == 0) {
        const uint32_t r1 = 0xffffu - (k1 & 0xffffu), r2 = 0xffffu - (k2 & 0xffffu);
        sts_u32x4(sbase + OG_SMISC + 64, r1, r2, (r1 >> 7) * 2, (r2 >> 7) * 2 + ((r1 >> 7) == (r2 >> 7)));
        sts_u32x2(sbase + OG_SMISC + 192, k1, k2);
        mbar_arrive(bar_sel);
      }
    } else if (tx < 96) {
          mbar_wait(bar_key, 0);
          const uint4 kk = lds_u32x4(sbase + OG_SSTAT + 1024 + lane * 16);
          uint32_t k1 = max(kk.x, kk.y), k2 = min(kk.x, kk.y);
          k2 = max(max(k2, min(kk.z, kk.w)), min(k1, max(kk.z, kk.w))); k1 = max(k1, max(kk.z, kk.w));
          warp_top2(k1, k2);
          if (tx < 64) {
            if (lane == 0 && nt == (mt & 7)) st_relaxed2(g_key + mt * 2, k1, k2);
            TL_MARK2(27, lane == 0);
          } else {
            const uint32_t r = (~((lane & 16) ? k2 : k1)) & 127u, ch = lane & 15;
            const uint2 st = lds_u32x2(sbase + OG_SSTAT + r * 8);
            const uint4 xc = lds_u32x4(sbase + OG_XSLOT + (ch >> 3) * 16384 + r * 128 + (((ch ^ r) & 7) << 4));
            const uint4 c1 = lds_u32x4(sbase + OG_SCOL + 768 + ch * 16), sh = lds_u32x4(sbase + OG_SCOL + 1024 + ch * 16);
            const float inr = __uint_as_float(st.y);
            float* dst = reinterpret_cast<float*>(g_cand + (mt * 2 + (lane >> 4)) * 256 + nt * 16 + ch);
            st_tagged4(dst + 512, __uint_as_float(ln_mod2(xc.x, st.x, inr, c1.x, sh.x)), __uint_as_float(ln_mod2(xc.y, st.x, inr, c1.y, sh.y)),
                       __uint_as_float(ln_mod2(xc.z, st.x, inr, c1.z, sh.z)), __uint_as_float(ln_mod2(xc.w, st.x, inr, c1.w, sh.w)));
            st_tagged4(dst, __uint_as_float(xc.x), __uint_as_float(xc.y), __uint_as_float(xc.z), __uint_as_float(xc.w));
          }
    }
    mbar_wait(bar_sel, 0);
    const int sel0 = (int)lds_u32(sbase + OG_SMISC + 64), sel1 = (int)lds_u32(sbase + OG_SMISC + 68);
    mbar_wait(bar_out, 0);
    if ((sel0 >> 7) == mt || (sel1 >> 7) == mt) {
      #pragma unroll 2
      for (int i = 0; i < 16; i++) {
        const int r = i * 8 + (tx >> 4), ch = tx & 15;
        if (m0 + r != sel0 && m0 + r != sel1)
          *reinterpret_cast<uint4*>(out + (size_t)(m0 + r) * T_D + n0 + ch * 8) =
              lds_u32x4(sbase + OG_OSLOT + (ch >> 3) * 16384 + r * 128 + (((ch & 7) ^ (r & 7)) << 4));
      }
    } else if (tx == 0) {
      tma_store_2d(tmOut, sbase + OG_OSLOT, n0, m0);
      tma_store_2d(tmOut, sbase + OG_OSLOT + 16384, n0 + 64, m0);
      bulk_commit();
    }
    if (bx == 0 && tx < 68) g_hcnt[32 * (tx >> 2) + (tx & 3)] = 0u;
    if (tx < 64) hm->modu[bx * 64 + tx] = 0.f;
    else if (tx < 96) hm->stat[bx * 32 + tx - 64] = make_float2(0.f, 0.f);
    else if (tx < 112) hm->mod[bx * 16 + tx - 96] = 0.f;
    else if (tx < 114 && bx < 66) hm->gkey[bx * 2 + tx - 112] = 0u;
    {
      const int tk = bx >> 6, c0 = (bx & 63) * 16;
      const uint32_t gb2 = *reinterpret_cast<const uint32_t*>(g_col + (c0 >> 7) * 1536 + 512 + 768 + ((c0 & 127) + (tx & 14)) * 2);
      const uint32_t* xp = reinterpret_cast<const uint32_t*>(g_cand + lds_u32(sbase + OG_SMISC + 72 + tk * 4) * 256) + ((c0 + (tx & 14)) >> 1);
      uint32_t x2 = 0u;
      #pragma unroll 1
      for (unsigned int spin = 0; spin < (1u << 20) && x2 == 0u; spin++) asm volatile("ld.relaxed.gpu.global.u32 %0, [%1];" : "=r"(x2) : "l"(xp) : "memory");
      const float* src = g_ypart + (size_t)((tx >> 2) * 2 + tk) * T_D + c0 + (tx & 3) * 4;
      const bool four = tx < (OG_MOE - 96) * 4;
      mbar_wait(bar_h2, 0);
      if (tx == 0) hint_wait(CNT_Y, (uint32_t)OG_MOE);
      named_bar_sync(10, 128);
      float4 p0, p1, p2, p3;
      #pragma unroll 1
      for (unsigned int spin = 0; spin < (1u << 20); spin++) {
        p0 = ld_tagged4(src); p1 = ld_tagged4(src + 64 * T_D); p2 = ld_tagged4(src + 128 * T_D); p3 = ld_tagged4(four ? src + 192 * T_D : src);
        if (tagged4(p0) && tagged4(p1) && tagged4(p2) && tagged4(p3)) break;
      }
      if (four) { p2.x += p3.x; p2.y += p3.y; p2.z += p3.z; p2.w += p3.w; }
      p0.x = (p0.x + p1.x) + p2.x; p0.y = (p0.y + p1.y) + p2.y; p0.z = (p0.z + p1.z) + p2.z; p0.w = (p0.w + p1.w) + p2.w;
      #pragma unroll
      for (int o = 4; o <= 16; o <<= 1) {
        p0.x += __shfl_xor_sync(0xffffffffu, p0.x, o); p0.y += __shfl_xor_sync(0xffffffffu, p0.y, o);
        p0.z += __shfl_xor_sync(0xffffffffu, p0.z, o); p0.w += __shfl_xor_sync(0xffffffffu, p0.w, o);
      }
      if (lane < 4) sts_f32x4(sbase + OG_SFIN + (tx >> 5) * 64 + lane * 16, p0.x, p0.y, p0.z, p0.w);
      named_bar_sync(10, 128);
      TL_MARK2(21, tx == 0);
      if (tx < 16) {
        const uint32_t ya = sbase + OG_SFIN + tx * 4, key = lds_u32(sbase + OG_SMISC + 192 + tk * 4);
        float y = (lds_f32(ya) + lds_f32(ya + 64)) + (lds_f32(ya + 128) + lds_f32(ya + 192));
        const float r = bfhi((key & 0x80000000u) ? key ^ 0x80000000u : ~key);
        const float rs = rbf(sigmoid_f(r));
        const uint32_t h2p = lds_u32(sbase + OG_SH2 + tk * 2048 + (c0 + (tx & 14)) * 2);
        const float fh = (lane & 1) ? bfhi(h2p) : bflo(h2p);
        y = rbf(y);
        y = rbf(y * rs);
        const float upd = rbf(rbf(fh * 0.0f) + y);
        out[(size_t)(tk ? sel1 : sel0) * T_D + c0 + tx] =
            __float2bfloat16_rn(((lane & 1) ? bfhi(x2) : bflo(x2)) + rbf(((lane & 1) ? bfhi(gb2) : bflo(gb2)) * rbf(fh + upd)));
      }
      if (tx == 0) bulk_wait_read<0>();
    }
    TL_END(4, tx == 0);
    PS(6, tx == 0);
}

__device__ __forceinline__ void tail_consumer(Scratch* hm, uint32_t bx, uint32_t sbase, int t2, int cwg, const bf16* __restrict__ w_gate, const bf16* __restrict__ w_up) {
    TAIL_SETUP
    const int tid = threadIdx.x & 127;
    const int warp = tid >> 5, lane = tid & 31, w8 = t2 >> 5;
    const uint32_t dbase = (sbase & 0x3FFFFu) >> 4;
    const uint32_t a_base = dbase + ((cwg * 8192) >> 4) + (1u << 16);
    const uint32_t b_base = dbase + (16384 >> 4) + (512u << 16);
    TL_MARK2(25, threadIdx.x == 128);
    const uint64_t pol = policy_evict_first();
    const bf16* pw = ((lane & 16) ? w_up : w_gate) + (size_t)(w8 * 128 + (lane & 3) * 4) * T_F + (has_moe ? bx : 0) * 32 + ((lane >> 2) & 3) * 8;
    uint4 wv[32];
    float acc[64];
    {
      uint32_t stage = OG_POS % OG_ST, phase = (OG_POS / OG_ST) & 1, prev = 0;
      #pragma unroll
      for (int g = 0; g < OG_NG; g++) {
        #pragma unroll
        for (int j = 0; j < 4; j++) wv[4 * g + j] = ldg_stream_v4(pw + (size_t)(16 * g + j) * T_F, pol);
        #pragma unroll 1
        for (int kb = g * OG_GRP; kb < (g == OG_NG - 1 ? OG_NKB : (g + 1) * OG_GRP); kb++) {
          mbar_wait(bar_full + 8 * stage, phase);
          const uint32_t a_lo = a_base + stage * (OG_STAGE >> 4), b_lo = b_base + stage * (OG_STAGE >> 4);
          wgmma_fence();
          wgmma_m64n128k16_ss_tb<0, 0>(acc, a_lo, b_lo, kb != 0);
          wgmma_m64n128k16_ss_tb<2, 128>(acc, a_lo, b_lo, 1);
          wgmma_m64n128k16_ss_tb<4, 256>(acc, a_lo, b_lo, 1);
          wgmma_m64n128k16_ss_tb<6, 384>(acc, a_lo, b_lo, 1);
          wgmma_commit();
          wgmma_wait<1>();
          if (kb > 0 && tid == 0) mbar_arrive(bar_empty + 8 * prev);
          prev = stage;
          if (++stage == OG_ST) { stage = 0; phase ^= 1; }
        }
      }
    }
    mbar_wait(bar_col, 0);
    mbar_wait(bar_full + 8 * ((OG_POS + OG_NKB) % OG_ST), ((OG_POS + OG_NKB) / OG_ST) & 1);
    wgmma_wait<0>();
    fence_regs(acc);
    if (tid == 0) mbar_arrive(bar_end);
    TL_MARK2(9, lane == 0);
    PS(5, threadIdx.x == 256);
    const int q2 = 2 * (lane & 3);
    const uint32_t frag = (64 * cwg + 16 * warp + (lane & 7) + 8 * ((lane >> 3) & 1)) * 128;
    const int fsw = lane & 7, fhi = lane >> 4;
    {
      float dl[4] = {0.f, 0.f, 0.f, 0.f}, da[4] = {0.f, 0.f, 0.f, 0.f}, db[4] = {0.f, 0.f, 0.f, 0.f};
      const uint32_t tb = sbase + OG_SCOL + (lane & 8) * 32 + (lane & 3) * 8, g = lane >> 2;
      const uint32_t msk = (g == 1 || g == 2) ? 0xffffffffu : 0u, one = g == 0 ? 0x3F803F80u : 0u;
      #pragma unroll
      for (int J = 0; J < 16; J += 2) {
        const uint32_t ad = sbase + OG_XSLOT + (J >> 3) * 16384 + frag + ((((J & 7) + fhi) ^ fsw) << 4);
        uint32_t xr[4];
        ldmatrix_x4(ad, xr[0], xr[1], xr[2], xr[3]);
        const uint2 cw = lds_u32x2(tb + J * 16);
        #pragma unroll
        for (int h = 0; h < 2; h++) {
          const uint32_t ga = lds_u32(sbase + OG_SCOL + 512 + (8 * (J + h) + q2) * 2);
          xr[2 * h] = badd2(xr[2 * h], bmul2(ga, pack_bf16(acc[4 * (J + h)], acc[4 * (J + h) + 1])));
          xr[2 * h + 1] = badd2(xr[2 * h + 1], bmul2(ga, pack_bf16(acc[4 * (J + h) + 2], acc[4 * (J + h) + 3])));
        }
        stmatrix_x4(ad, xr[0], xr[1], xr[2], xr[3]);
        mma_bf16(dl, xr[0], xr[1], xr[2], xr[3], (cw.x & msk) | one, (cw.y & msk) | one);
        mma_bf16(da, xr[0], xr[1], xr[2], xr[3], xr[0], xr[2]);
        mma_bf16(db, xr[0], xr[1], xr[2], xr[3], xr[1], xr[3]);
      }
      {
        const int dsrc = (lane & ~3) + (g >> 1);
        const float qa = __shfl_sync(0xffffffffu, (g & 1) ? da[1] : da[0], dsrc), qb = __shfl_sync(0xffffffffu, (g & 1) ? db[3] : db[2], dsrc);
        const float e0 = __shfl_xor_sync(0xffffffffu, (lane & 1) ? dl[0] : dl[2], 1), e1 = __shfl_xor_sync(0xffffffffu, dl[3], 1);
        if ((lane & 3) < 2) {
          const bool hi = lane & 1;
          st_tagged4(reinterpret_cast<float*>(g_part1 + ((mt * 8 + w8) * 8 + nt) * 16 + g + (hi ? 8 : 0)),
                     hi ? e0 : dl[0], hi ? qb : qa, hi ? e1 + dl[2] : dl[1] + e0, 1.0f);
        }
      }
    }
    TL_MARK2(10, lane == 0);
    uint4 wd[16];
    if (has_moe) mbar_wait(bar_wd, 0);
    #pragma unroll
    for (int i = 0; i < 16; i++) wd[i] = lds_u32x4(sbase + OG_SWD + (((i >> 2) & 1) * 4 + (lane & 3)) * 8224 + (i & 3) * 2048 + w8 * 256 + (i >> 3) * 128 + (lane >> 2) * 16);
    {
      const float* src = reinterpret_cast<const float*>(g_part1 + ((mt * 8 + w8) * 8 + (lane & 1) * 4) * 16 + (lane >> 1));
      float4 v, v1, v2, v3;
      #pragma unroll 1
      for (unsigned int spin = 0; spin < (1u << 22); spin++) {
        v = ld_tagged4(src); v1 = ld_tagged4(src + 64); v2 = ld_tagged4(src + 128); v3 = ld_tagged4(src + 192);
        if (tagged4(v) & tagged4(v1) & tagged4(v2) & tagged4(v3)) break;
        __nanosleep(100);
      }
      __syncwarp();
      TL_MARK2(26, lane == 0);
      v.x = (v.x + v1.x) + (v2.x + v3.x); v.y = (v.y + v1.y) + (v2.y + v3.y); v.z = (v.z + v1.z) + (v2.z + v3.z);
      v.x += __shfl_xor_sync(0xffffffffu, v.x, 1); v.y += __shfl_xor_sync(0xffffffffu, v.y, 1); v.z += __shfl_xor_sync(0xffffffffu, v.z, 1);
      const float mean = v.x * (1.0f / T_D);
      const float var = fmaxf(fmaf(-mean, mean, v.y * (1.0f / T_D)), 0.f);
      const uint32_t mb2 = pack_bf16(mean, mean);
      const float inv = rcp_approx(rbf(sqrt_approx(rbf(rbf(var) + 1e-05f))));
      {
        const float2 cwp = lds_f32x2(sbase + OG_SMISC), sbp = lds_f32x2(sbase + OG_SMISC + 8);
        const uint32_t key = rank_key(rbf(fmaf(fmaf(-bflo(mb2), cwp.x + cwp.y, v.z), inv, sbp.x + sbp.y)), m0 + 16 * w8 + (lane >> 1));
        mbar_wait(bar_end, 0);
        if (lane & 1) sts_u32(sbase + OG_SSTAT + 1024 + (16 * w8 + (lane >> 1)) * 4, key);
        else sts_u32x2(sbase + OG_SSTAT + (16 * w8 + (lane >> 1)) * 8, mb2, __float_as_uint(inv));
        __syncwarp();
        if (lane == 0) mbar_arrive(bar_key);
      }
      const uint32_t ih = pack_bf16(inv, inv), il = pack_bf16(inv - bflo(ih), inv - bflo(ih));
      const uint32_t mba = __shfl_sync(0xffffffffu, mb2, 2 * (lane >> 2)), mbb = __shfl_sync(0xffffffffu, mb2, 2 * (lane >> 2) + 16);
      const uint32_t iha = __shfl_sync(0xffffffffu, ih, 2 * (lane >> 2)), ihb = __shfl_sync(0xffffffffu, ih, 2 * (lane >> 2) + 16);
      const uint32_t ila = __shfl_sync(0xffffffffu, il, 2 * (lane >> 2)), ilb = __shfl_sync(0xffffffffu, il, 2 * (lane >> 2) + 16);
      #pragma unroll 2
      for (int J = 0; J < 16; J += 2) {
        const uint32_t off = (J >> 3) * 16384 + frag + ((((J & 7) + fhi) ^ fsw) << 4);
        uint32_t xr[4];
        ldmatrix_x4(sbase + OG_XSLOT + off, xr[0], xr[1], xr[2], xr[3]);
        #pragma unroll
        for (int h = 0; h < 2; h++) {
          const uint32_t ca = sbase + OG_SCOL + 512 + (8 * (J + h) + q2) * 2;
          const uint32_t c1 = lds_u32(ca + 256), sh = lds_u32(ca + 512), gb = lds_u32(ca + 768);
          xr[2 * h] = out2(xr[2 * h], mba, iha, ila, c1, sh, gb);
          xr[2 * h + 1] = out2(xr[2 * h + 1], mbb, ihb, ilb, c1, sh, gb);
        }
        stmatrix_x4(sbase + OG_OSLOT + off, xr[0], xr[1], xr[2], xr[3]);
      }
      fence_proxy_async();
      __syncwarp();
      if (lane == 0) mbar_arrive(bar_out);
      TL_MARK2(24, lane == 0);
    }
    {
      mbar_wait(bar_sel, 0);
      TL_MARK2(12, lane == 0);
      const float* src = reinterpret_cast<const float*>(g_cand + lds_u32(sbase + OG_SMISC + 72 + cwg * 4) * 256 + 128 + tid);
      float4 hf;
      #pragma unroll 1
      for (unsigned int spin = 0; spin < (1u << 20); spin++) { hf = ld_tagged4(src); if (tagged4(hf)) break; }
      const uint4 hv = make_uint4(__float_as_uint(hf.x), __float_as_uint(hf.y), __float_as_uint(hf.z), __float_as_uint(hf.w));
      sts_u32x4(sbase + OG_SH2 + t2 * 16, hv.x, hv.y, hv.z, hv.w);
    }
    named_bar_sync(9, 256);
    if (t2 == 0) mbar_arrive(bar_h2);
    TL_MARK2(13, lane == 0);
    if (has_moe) {
      const GemvSel sel = gemv_sel(lane);
      {
        float d[4][4];
        #pragma unroll
        for (int c = 0; c < 4; c++) { d[c][0] = 0.f; d[c][1] = 0.f; d[c][2] = 0.f; d[c][3] = 0.f; }
        #pragma unroll
        for (int st = 0; st < 8; st++) {
          const uint2 hb = lds_u32x2(sbase + OG_SH2 + ((lane >> 2) & 1) * 2048 + (w8 * 128 + st * 16 + (lane & 3) * 4) * 2);
          #pragma unroll
          for (int j = 0; j < 4; j++) mma_bf16(d[j], wv[4 * st + j].x, wv[4 * st + j].y, wv[4 * st + j].z, wv[4 * st + j].w, GEMV_B0(j, hb, sel), GEMV_B1(j, hb, sel));
        }
        #pragma unroll
        for (int e = 0; e < 4; e++) d[0][e] = (d[0][e] + d[1][e]) + (d[2][e] + d[3][e]);
        const float4 r = gemv_out(d[0], lane);
        sts_f32x4(sbase + OG_SRED + w8 * 512 + (((lane >> 4) * 2 + (lane & 1)) * 32 + ((lane >> 2) & 3) * 8 + (lane & 2) * 2) * 4, r.x, r.y, r.z, r.w);
      }
      named_bar_sync(9, 256);
      if (t2 < 64) {
        float gp[8], up[8];
        #pragma unroll
        for (int w = 0; w < 8; w++) { gp[w] = lds_f32(sbase + OG_SRED + w * 512 + t2 * 4); up[w] = lds_f32(sbase + OG_SRED + w * 512 + 256 + t2 * 4); }
        const float gs = ((gp[0] + gp[1]) + (gp[2] + gp[3])) + ((gp[4] + gp[5]) + (gp[6] + gp[7]));
        const float us = ((up[0] + up[1]) + (up[2] + up[3])) + ((up[4] + up[5]) + (up[6] + up[7]));
        asm volatile("st.shared.u16 [%0], %1;" :: "r"(sbase + OG_SGU + t2 * 2), "h"((uint16_t)pack_bf16(silu_bf(rbf(gs)) * rbf(us), 0.f)) : "memory");
      }
      named_bar_sync(9, 256);
      TL_MARK2(20, threadIdx.x == 128);
      float d[4][4];
      #pragma unroll
      for (int c = 0; c < 4; c++) { d[c][0] = 0.f; d[c][1] = 0.f; d[c][2] = 0.f; d[c][3] = 0.f; }
      #pragma unroll
      for (int st = 0; st < 2; st++) {
        const uint2 g = lds_u32x2(sbase + OG_SGU + ((lane >> 2) & 1) * 64 + st * 32 + (lane & 3) * 8);
        #pragma unroll
        for (int j = 0; j < 4; j++) {
          const uint32_t b0 = GEMV_B0(j, g, sel), b1 = GEMV_B1(j, g, sel);
          mma_bf16(d[j & 1], wd[4 * st + j].x, wd[4 * st + j].y, wd[4 * st + j].z, wd[4 * st + j].w, b0, b1);
          mma_bf16(d[2 + (j & 1)], wd[8 + 4 * st + j].x, wd[8 + 4 * st + j].y, wd[8 + 4 * st + j].z, wd[8 + 4 * st + j].w, b0, b1);
        }
      }
      #pragma unroll
      for (int e = 0; e < 4; e++) { d[0][e] += d[1][e]; d[2][e] += d[3][e]; }
      const float4 y0 = gemv_out(d[0], lane), y1 = gemv_out(d[2], lane);
      float* yp = g_ypart + (size_t)(bx * 2 + (lane & 1)) * T_D + w8 * 128 + (lane >> 2) * 8 + (lane & 2) * 2;
      st_tagged4(yp, y0.x, y0.y, y0.z, y0.w);
      st_tagged4(yp + 64, y1.x, y1.y, y1.z, y1.w);
      named_bar_sync(9, 256);
      if (t2 == 0) hint_arrive(CNT_Y);
    }
    TL_MARK2(14, threadIdx.x == 128);
    TL_CLK(4, 1, threadIdx.x == 128);
}

__device__ __noinline__ void store_warp(Scratch* hm, uint32_t sbase, const CUtensorMap* tmO, int item0, int n_items) {
  if (elect_one()) {
    const uint32_t bars = sbase + AT_SBAR, b_q0 = bars + 80, b_ob = bars + 96, b_ordy = bars + 104, b_acq = bars + 264;
    mbar_wait(bars + 232, 0);
    const uint32_t bx = lds_u32(bars + 240);
    const unsigned int* cnt = &g_hcnt[32 * (1 + OG_MT(bx)) + 2];
    #pragma unroll 1
    for (int q = 0; q < 4 * n_items; q++) {
      const int item = item0 + (q >> 2) * 128, h = (q >> 1) & 1, w = q & 1;
      const bool last = (q >> 2) == n_items - 1;
      mbar_wait(b_ordy + 8 * (q & 3), q >> 2);
      store_o(tmO, (h ? (last ? sbase + AT_SQ + 32768 : sbase + 2 * 32768) : sbase + AT_SQ) + w * 8192, (item >> 4) * 2 + h, (item & 15) * 128 + w * 64);
      if (w) {
        bulk_wait_read<0>();
        mbar_arrive(h ? b_ob : b_q0);
        bulk_wait<0>();
        fence_proxy_async_global();
        red_release_add(&g_hcnt[32 * (1 + (item & 15)) + 2 + (item >> 7)], 1u);
        if (bx < 128 && q == (n_items == 2 ? 5 : 3)) { spin_until(cnt, 16u); mbar_arrive(b_acq); }
      }
    }
    if (bx < 128) { spin_until(&g_hcnt[0], 8u); spin_until(cnt + 1, 16u); mbar_arrive(b_acq); }
  }
}

__global__ void __launch_bounds__(384, 1)
fused_kernel(const bf16* __restrict__ x, const bf16* __restrict__ cvec, const bf16* __restrict__ w_mod, Scratch* hm, uint32_t zero,
            const uint8_t* __restrict__ pf_wo, const bf16* __restrict__ kc, const bf16* __restrict__ vc, const bf16* __restrict__ w_r,
            const bf16* __restrict__ w_gate, const bf16* __restrict__ w_up, const bf16* __restrict__ w_down, bf16* __restrict__ out,
            const __grid_constant__ CUtensorMap tmM, const __grid_constant__ CUtensorMap tmW, const __grid_constant__ CUtensorMap tmK,
            const __grid_constant__ CUtensorMap tmV, const __grid_constant__ CUtensorMap tmO, const __grid_constant__ CUtensorMap tmOl, const __grid_constant__ CUtensorMap tmWo,
            const __grid_constant__ CUtensorMap tmX, const __grid_constant__ CUtensorMap tmOut)
{
  extern __shared__ __align__(1024) uint8_t smem_raw[];
  const uint32_t sbase = smem_u32(smem_raw);
  const uint32_t bars = sbase + AT_SBAR;
  const uint32_t b_full = bars, b_empty = bars + 40;
  const uint32_t b_q0 = bars + 80, b_q1 = bars + 88;
  const uint32_t b_ob = bars + 96;
  const uint32_t b_ordy = bars + 104;
  const uint32_t b_pin = bars + 136;
  const uint32_t b_a0 = bars + 144;
  const uint32_t b_x = bars + 160;
  const uint32_t b_w = bars + 152, b_go = bars + 224;
  const uint32_t b_bx = bars + 232, s_bx = bars + 240;
  const uint32_t b_tab = bars + 272;
  const int wg = __shfl_sync(0xffffffffu, threadIdx.x >> 7, 0);
  const bool single = blockIdx.x >= AT_NFULL;
  const int item0 = __shfl_sync(0xffffffffu, blockIdx.x < 128 ? (int)blockIdx.x : (int)blockIdx.x + 124, 0), n_items = __shfl_sync(0xffffffffu, single ? 1 : 2, 0);
  const uint32_t t0 = clock_lo();
  TL_START(3);
  HS(0);
  if (threadIdx.x == 0) {
    if (sbase & 1023u) __trap();
    for (int i = 0; i < 5; i++) { mbar_init(b_full + 8 * i, 1); mbar_init(b_empty + 8 * i, 2); }
    mbar_init(b_q0, 1); mbar_init(b_q1, 8); mbar_init(b_ob, 1);
    for (int i = 0; i < 4; i++) mbar_init(b_ordy + 8 * i, 4);
    mbar_init(b_pin, 1); mbar_init(b_a0, 8); mbar_init(b_x, 1); mbar_init(b_w, 1); mbar_init(b_go, 1); mbar_init(b_bx, 1);
    for (int i = 0; i < 8; i++) mbar_init(b_tab + 8 * i, i < 2 ? 1 : 2);
    mbar_init(bars + 168, 1); mbar_init(bars + 176, 1); mbar_init(bars + 184, 8); mbar_init(bars + 192, 2);
    mbar_init(bars + 200, 8); mbar_init(bars + 208, 1); mbar_init(bars + 216, 1); mbar_init(bars + 264, 1);
    fence_mbar_init();
    if (blockIdx.x < 128) {
      HS(1);
      wait_clock(t0, XDLY);
      mbar_expect_tx(b_x, 32768);
      bulk_load_hint(sbase + 3 * 32768, x + (size_t)blockIdx.x * 16 * T_D, 32768, b_x, pol_normal());
    }
    mbar_arrive(b_tab); mbar_arrive(b_tab + 8);
  }

  if (wg == 0) {
    reg_dealloc<AT_PREG>();
    if (threadIdx.x < 32) { __syncwarp(); named_bar_arrive(6, 128); named_bar_arrive(11, 160); named_bar_arrive(12, 160); }
    if (threadIdx.x >= 64) {
      named_bar_sync(6, 128);
      gather_table(hm, t0, sbase + 4 * 32768, b_tab, (threadIdx.x >> 5) & 1, threadIdx.x & 31);
      if (threadIdx.x >= 96) {
        const uint32_t v = DYN ? assign_tile(hm, t0, threadIdx.x & 31) : blockIdx.x;
        if (threadIdx.x == 96) { sts_u32(s_bx, v); mbar_arrive(b_bx); }
      }
    } else if (threadIdx.x >= 32) {
      named_bar_sync(6, 128);
      store_warp(hm, sbase, &tmO, item0, n_items);
      __syncwarp();
    } else {
     if (elect_one()) {
      const uint64_t pol = policy_evict_first();
      prefetch_tmap(&tmW); prefetch_tmap(&tmX); prefetch_tmap(&tmWo); prefetch_tmap(&tmOl);
      if (single) { prefetch_tmap(&tmM); mbar_wait(b_go, 0); }
      uint32_t slot = 0, ph = 1;
      #pragma unroll 1
      for (int it = 0; it < n_items; it++) {
        const int item = item0 + it * 128, hp = item >> 4, qt = item & 15;
        const bool first = it == 0;
        const uint64_t polx = first ? pol_normal() : pol;
        const uint32_t ab = first ? 16384 : 16384 + 256;
        auto load_a = [&](int i, uint32_t fb) {
          tma_load_2d_hint(sbase + AT_SQ + (i & 3) * 16384, &tmX, i * 64, qt * 128, fb, polx);
          if (!first) bulk_load_hint(sbase + OG_SCOL + (i & 3) * 256, hm->tab + blockIdx.x * 4096 + i * 256, 256, fb, pol);
        };
        #pragma unroll 1
        for (int j = 0; j < T_D / 64; j++) {
          const uint32_t sl = ring_slot(qp_pos(j, it)), fb = b_full + 8 * sl;
          mbar_wait(b_empty + 8 * sl, ring_par(qp_pos(j, it)) ^ ((j >> 2) & 1) ^ 1);
          mbar_expect_tx(fb, 32768 + (j == 0 ? 2 * ab : j == T_D / 64 - 1 ? 0 : ab));
          if (j < 4 && first) {
            if (j < 2) wait_clock(t0, j ? ST1_T : PRE_T);
            if (j == 3) mbar_wait(b_a0, 0);
            HS(2 + j);
          }
          tma_load_3d_hint(sbase + sl * 32768, &tmW, j * 64, hp * 4, fb, pol);
          if (j == 0) {
            if (first) wait_clock(t0, A_T);
            else { mbar_wait(b_q0, 0); mbar_wait(b_q1, 0); }
            load_a(0, fb);
          }
          if (j == 3) mbar_wait(b_a0, it);
          if (j < T_D / 64 - 1) load_a(j + 1, fb);
        }
        #pragma unroll 1
        for (int j = 0; j < 4 * AT_NBLK; j++) {
          const bool isv = (j > 0 && !(j & 1)) || j == 4 * AT_NBLK - 1;
          const int row = hp * 2 * T_SEQ + (isv ? (j - 1) >> 1 : (j + 1) >> 1) * 128;
          const uint32_t fb = b_full + 8 * slot;
          mbar_wait(b_empty + 8 * slot, ph);
          if (!first && j == 3) mbar_wait(b_ob, 0);
          mbar_expect_tx(fb, 32768);
          tma_load_2d_hint(sbase + slot * 32768, isv ? &tmV : &tmK, 0, row, fb, pol);
          tma_load_2d_hint(sbase + slot * 32768 + 16384, isv ? &tmV : &tmK, 64, row, fb, pol);
          if (it == 1 && isv && j >= 2 * WO_LATE && j < 2 * WO_LATE + 32 && blockIdx.x < 64)
            l2_prefetch_bulk(pf_wo + (size_t)blockIdx.x * 131072 + ((j >> 1) - WO_LATE) * 8192, 8192);
          if (++slot == 5) { slot = 0; ph ^= 1; }
        }
      }
      mbar_wait(b_bx, 0);
      const uint32_t bx = lds_u32(s_bx);
      if (bx < 128) {
        if (single) mbar_wait(b_go, 1);
        tail_producer(hm, bx, sbase, 0, n_items - 1, pol, &tmOl, &tmWo, &tmX, w_down);
      }
     }
    }
    __syncwarp();
    PSV(0, threadIdx.x == 96, t0);
    mbar_wait(b_bx, 0);
    const uint32_t bx = __shfl_sync(0xffffffffu, lds_u32(s_bx), 0);
    if (bx < 128) tail_exchange(hm, bx, sbase, __shfl_sync(0xffffffffu, threadIdx.x, threadIdx.x), &tmOut, out);
  } else {
    if (wg == 1 && blockIdx.x < 128) head_first(hm, sbase + 4 * 32768 + 4096, threadIdx.x - 128, cvec, w_mod);
    named_bar_sync(10 + wg, 160);
    if (wg == 2 && blockIdx.x < 128) head_stats(hm, sbase + 3 * 32768, b_x, threadIdx.x - 256);
    if (single) {
      wait_clock(t0, WDLY);
      mod_rest(hm, sbase, b_w, threadIdx.x - 128, (int)blockIdx.x - AT_NFULL, cvec, &tmM, w_r);
      if (threadIdx.x == 128) mbar_arrive(b_go);
    }
    if (wg == 1) { wait_clock(t0, GDLY); head_gather(hm, sbase + 4 * 32768, threadIdx.x - 128); }
    reg_alloc<AT_CREG>();
    const int cwg = wg - 1;
    const int tid = threadIdx.x & 127;
    const int warp = tid >> 5, lane = tid & 31;
    const uint32_t dbase = (sbase & 0x3FFFFu) >> 4;
    const uint32_t k_base = dbase + (1u << 16);
    const uint32_t v_base = dbase + (1024u << 16);
    const uint32_t w_base = dbase + (512u << 16);
    const uint32_t frag = cwg * 8192 + (16 * warp + (lane & 7) + 8 * ((lane >> 3) & 1)) * 128;
    if (cwg == 1) named_bar_arrive(1, 256);
    bool raw = false;
    uint32_t rw[16], sta = 0, stb = 0, xa = 0, xt = 0;
    uint4 tb[4];
    #pragma unroll
    for (int i = 0; i < 4; i++) { rw[4 * i] = 0; rw[4 * i + 1] = 0; rw[4 * i + 2] = 0; rw[4 * i + 3] = 0; tb[i] = make_uint4(0u, 0u, 0u, 0u); }
    auto qp_fetch = [&](int j, uint32_t tmask) {
      #pragma unroll
      for (int st = 0; st < 4; st++) {
        ldmatrix_x4((xa ^ (st * 32)) + (j & 3) * 16384, rw[4 * st], rw[4 * st + 1], rw[4 * st + 2], rw[4 * st + 3]);
        tb[st] = lds_u32x4(xt + (j & tmask) * 256 + st * 64);
      }
    };
    auto qp_first = [&](uint32_t tab) {
      uint32_t ln2; asm volatile("mov.u32 %0, %%tid.x;" : "=r"(ln2));
      xa = sbase + AT_SQ + ((ln2 - 128) >> 5) * 2048 + (ln2 & 15) * 128 + ((((ln2 >> 4) & 1) ^ (ln2 & 7)) << 4);
      xt = tab + (ln2 & 3) * 16;
      qp_fetch(0, 0);
      const uint32_t a = sbase + OG_SMISC + 256 + ((ln2 - 128) >> 5) * 64 + (ln2 & 28);
      sta = lds_u32(a); stb = lds_u32(a + 32);
    };
    #pragma unroll 1
    for (int it = 0; it < n_items; it++) {
      const int item = item0 + it * 128, hp = item >> 4;
      const bool more = it + 1 < n_items;
      constexpr int nkb = T_D / 64;
      const int ta = __shfl_sync(0xffffffffu, 4 * it, 0);
      float acc[128], c0, c1;
      {
        FS(2 * it, 0);
        uint32_t af[2][16];
        const uint32_t tmask = ta ? 3 : 15;
        zero_regs(acc);
        #pragma unroll
        for (int i = 0; i < 16; i++) af[1][i] = 0u;
        if (it == 0) {
          uint32_t ln2; asm volatile("mov.u32 %0, %%tid.x;" : "=r"(ln2));
          const float2* stp = hm->stat + (item & 15) * 256 + ((ln2 - 128) >> 5) * 32 + (ln2 & 3) * 8 + ((ln2 >> 2) & 7);
          HS(4);
          wait_clock(t0, SDLY);
          float2 sv = ld_tagged2(stp);
          named_bar_sync(5, 256);
          mbar_wait(b_full, 0);
          HS(5);
          qp_first(sbase + 4 * 32768);
          #pragma unroll 1
          for (unsigned int spin = 0; spin < (1u << 22); spin++) {
            if (__all_sync(0xffffffffu, (__float_as_uint(sv.x) != 0u) & (__float_as_uint(sv.y) != 0u))) break;
            sv = ld_tagged2(stp);
          }
          HS(6);
          if ((ln2 & 31) == 0) mbar_arrive(b_a0 + (rw[3] & rw[7] & rw[11] & rw[15] & zero));
          const uint32_t st = ln_stat(sv.x + __shfl_xor_sync(0xffffffffu, sv.x, 1), sv.y + __shfl_xor_sync(0xffffffffu, sv.y, 1)), so = __shfl_xor_sync(0xffffffffu, st, 2);
          sta = (ln2 & 2) ? so : st; stb = (ln2 & 2) ? st : so;
          sts_u32(sbase + OG_SMISC + 256 + ((ln2 - 128) >> 5) * 64 + (ln2 & 28) + (ln2 & 2) * 16, st);
        }
        const uint32_t mean_a = __byte_perm(sta, 0u, 0x1010), mean_b = __byte_perm(stb, 0u, 0x1010), sd_a = __byte_perm(sta, 0u, 0x3232), sd_b = __byte_perm(stb, 0u, 0x3232);
        c0 = AT_C * rcp_approx(bfhi(sta)); c1 = AT_C * rcp_approx(bfhi(stb));
        uint32_t prev = b_pin - 40;
        #pragma unroll 1
        for (int j2 = 0; j2 < nkb; j2 += 2) {
          #pragma unroll
          for (int u = 0; u < 2; u++) {
            const int j = j2 + u;
            const uint32_t slot = ring_slot(qp_pos(j, ta >> 2)), par = ring_par(qp_pos(j, ta >> 2)) ^ ((j >> 2) & 1), bt = b_tab + 4 * ((j + 1) & 15);
            bool ok = mbar_test(b_full + 8 * slot, par);
            if (u == 1) ok &= mbar_test(bt, 0);
            if (u == 1 && zero) {
              #pragma unroll
              for (int i = 0; i < NDUM; i += 4) sts_u32x4(xt + i * 4, af[1][i], af[1][i + 1], af[1][i + 2], af[1][i + 3]);
            }
            #pragma unroll
            for (int st = 0; st < 4; st++) {
              af[u][4 * st + 0] = bfma2(bsub2(rw[4 * st + 0], mean_a), tb[st].x, bmul2(tb[st].z, sd_a));
              af[u][4 * st + 1] = bfma2(bsub2(rw[4 * st + 1], mean_b), tb[st].x, bmul2(tb[st].z, sd_b));
              af[u][4 * st + 2] = bfma2(bsub2(rw[4 * st + 2], mean_a), tb[st].y, bmul2(tb[st].w, sd_a));
              af[u][4 * st + 3] = bfma2(bsub2(rw[4 * st + 3], mean_b), tb[st].y, bmul2(tb[st].w, sd_b));
            }
            if (!ok) { mbar_wait(b_full + 8 * slot, par); if (u == 1) mbar_wait(bt, 0); }
            qp_fetch(j + 1, tmask);
            if (QP_STAG > 0 && cwg == 1 && j == nkb - QP_STAG) {
              named_bar_sync(7, 256);
            }
            const bool turn = QTN > 0 && (uint32_t)(j - QT0) <= (uint32_t)(QTN - 1);
            if (turn) named_bar_sync(1 + cwg, 256);
            const uint32_t b_lo = w_base + slot * 2048;
            wgmma_fence();
            wgmma_m64n256k16_rs_tb<0>(acc, af[u][0], af[u][1], af[u][2], af[u][3], b_lo, 1);
            wgmma_m64n256k16_rs_tb<128>(acc, af[u][4], af[u][5], af[u][6], af[u][7], b_lo, 1);
            wgmma_m64n256k16_rs_tb<256>(acc, af[u][8], af[u][9], af[u][10], af[u][11], b_lo, 1);
            if (QARR == 3) named_bar_arrive_if(turn, 1 + (cwg ^ 1), 256);
            wgmma_m64n256k16_rs_tb<384>(acc, af[u][12], af[u][13], af[u][14], af[u][15], b_lo, 1);
            wgmma_commit();
            if (QARR == 4) named_bar_arrive_if(turn, 1 + (cwg ^ 1), 256);
            if (QP_STAG > 0 && cwg == 0 && j == nkb - 1) named_bar_arrive(7, 256);
            if (LATEF && j == 0 && it != 0) {
              fence_proxy_async();
              __syncwarp();
              if (lane == 0) mbar_arrive(b_ordy + 16 + 8 * cwg);
            }
            if (j == 0 && it == 0) HS(7);
            wgmma_wait<1>();
            if (tid == 0) mbar_arrive(prev + 40);
            prev = b_full + 8 * slot;
          }
        }
        wgmma_wait<0>();
        fence_regs(acc);
        FS(2 * it, 1);
        TL_MARK2(29, threadIdx.x == 256 && it == 0);
        PS(1 + 2 * it, threadIdx.x == 256);
        if (tid == 0) mbar_arrive(b_empty + 24);
      }
      float o[64], s[64];
      uint32_t p[32], q[32];
      #pragma unroll
      for (int i = 0; i < 32; i++) q[i] = pack_bf16(acc[2 * i] * ((i & 1) ? c1 : c0), acc[2 * i + 1] * ((i & 1) ? c1 : c0));
      zero_regs(s);
      const uint32_t sq = sbase + AT_SQ + cwg * 8192;
      const bool last_wg1 = cwg == 1 && !more;
      float mc0, mc1, al0 = 1.0f, al1 = 1.0f, l0 = 0.f, l1 = 0.f, lp0 = 0.f, lp1 = 0.f;
      bool redo0 = false;
      FS(2 * it, 2);
      {
        uint32_t dep = zero;
        #pragma unroll
        for (int i = 0; i < 32; i += PINQ) dep &= q[i];
        mbar_wait(b_full + 8 * ring_slot(ta) + dep, ring_par(ta));
      }
      named_bar_sync(1 + cwg, 256);
      FS(2 * it, 3);
      issue_qk(s, q, k_base + ring_slot(ta) * 2048);
      named_bar_arrive(1 + (cwg ^ 1), 256);
      const uint32_t rdy = (uint32_t)mbar_test(b_full + 8 * ring_slot(ta + 1), ring_par(ta + 1));
      bool ready = rdy & mbar_test(b_full + 8 * ring_slot(ta + 2), ring_par(ta + 2));
      stage_o(*reinterpret_cast<const float (*)[64]>(&acc[64]), c0, c1, sbase + AT_SQ + 32768 + frag, lane);
      wgmma_wait<0>();
      fence_regs(s);
      if (tid == 0) mbar_arrive(b_empty + 8 * ring_slot(ta));
      mc0 = 0.f; mc1 = 0.f;
      if (!raw) {
        raw = softmax_mode(s, mc0, mc1);
        if (__builtin_expect(!raw, 0)) softmax_sub(s, mc0, mc1);
      }
      softmax_exp<0, 64>(s);
      stage_qregs(q, sbase + AT_SQ + frag, lane);
      pack_p(p, s);
      zero_regs(o);
      FS(2 * it, 4);
      uint32_t ks = ring_slot(ta + 1), vs = ring_slot(ta + 2), kp = ring_par(ta + 1), vp = ring_par(ta + 2);
      auto finish_head = [&]() {
        FS(2 * it, 5);
        redo0 = finish_l(lp0, lp1);
        if (!redo0) {
          stage_o(o, lp0, lp1, sbase + AT_SQ + frag, lane);
          fence_proxy_async();
          __syncwarp();
          if (lane == 0) mbar_arrive(b_ordy + 8 * cwg);
        }
        FS(2 * it + 1, 4);
      };
      if (!ready) { mbar_wait(b_full + 8 * ks, kp); mbar_wait(b_full + 8 * vs, vp); }
      #pragma unroll 1
      for (int n = 1; n < 2 * AT_NBLK; n++) {
        named_bar_sync(1 + cwg, 256);
        issue_qk(s, q, k_base + ks * 2048);
        if (n == AT_NBLK + 1) finish_head();
        issue_pv(o, p, v_base + vs * 2048, (n & 15) != 1);
        if (!(last_wg1 && n == 2 * AT_NBLK - 1)) named_bar_arrive(1 + (cwg ^ 1), 256);
        wgmma_wait<1>();
        fence_regs(s);
        if (tid == 0) mbar_arrive(b_empty + 8 * ks);
        if (__builtin_expect(!raw || (n + 1) >> 1 == AT_NBLK / 2, 0)) {
          if (n == AT_NBLK - 1) {
            #pragma unroll
            for (int J = 0; J < 16; J += 2)
              ldmatrix_x4(sbase + AT_SQ + 32768 + frag + (J >> 3) * 16384 + ((((J & 7) + (lane >> 4)) ^ (lane & 7)) << 4), q[2 * J], q[2 * J + 1], q[2 * J + 2], q[2 * J + 3]);
          }
          if (n == AT_NBLK && lane == 0) mbar_arrive(b_q1);
          if (!raw) {
            const float m0 = mc0, m1 = mc1;
            const bool ok = softmax_mode(s, mc0, mc1);
            if (n == AT_NBLK) raw = ok;
            else {
              mc0 = mc0 - AT_HEAD > m0 ? mc0 : m0; mc1 = mc1 - AT_HEAD > m1 ? mc1 : m1;
              al0 = ex2_approx(m0 - mc0); al1 = ex2_approx(m1 - mc1);
            }
            if (!raw) softmax_sub(s, mc0, mc1);
          }
        }
        softmax_exp<0, AT_SPLIT>(s);
        add_rowsum(p, l0, l1);
        if (tid == 0) {
          uint32_t dep = zero & __float_as_uint(l0) & __float_as_uint(l1);
          #pragma unroll
          for (int i = AT_SPLIT - AT_PIN - PINB; i < AT_SPLIT - PINB; i += 2) dep &= __float_as_uint(s[i]) & __float_as_uint(s[i + 1]);
          mbar_arrive(b_pin + dep);
        }
        wgmma_wait<0>();
        fence_regs(o);
        if (tid == 0) mbar_arrive(b_empty + 8 * vs);
        ks += 2; if (ks >= 5) { ks -= 5; kp ^= 1; }
        vs += 2; if (vs >= 5) { vs -= 5; vp ^= 1; }
        ready = mbar_test(b_full + 8 * ks, kp) & mbar_test(b_full + 8 * vs, vp);
        softmax_exp<AT_SPLIT, 64>(s);
        pack_p(p, s);
        if (n == AT_NBLK) { lp0 = l0; lp1 = l1; l0 = 0.f; l1 = 0.f; }
        if (__builtin_expect(!raw || !ready, 0)) {
        if (!raw && __any_sync(0xffffffffu, al0 != 1.0f || al1 != 1.0f)) {
          rescale_o(o, al0, al1);
          l0 *= al0; l1 *= al1;
          al0 = 1.0f; al1 = 1.0f;
        }
        if (!ready && n < 2 * AT_NBLK - 1) {
          mbar_wait(b_full + 8 * ks, kp);
          mbar_wait(b_full + 8 * vs, vp);
        }
        }
      }
      FS(2 * it + 1, 5);
      const uint32_t vl = ring_slot(ta + 63);
      vs = ring_slot(ta + 62);
      const uint32_t ob = more ? sbase + vs * 32768 : sbase + AT_SQ + 32768;
      mbar_wait(b_full + 8 * vl, ring_par(ta + 63));
      issue_pv(o, p, v_base + vl * 2048, 1);
      add_rowsum(p, l0, l1);
      const bool overflow = finish_l(l0, l1);
      if (more && !redo0) mbar_wait(b_full + 32, 0);
      mbar_wait(b_empty + 8 * vs, ring_par(ta + 62));
      wgmma_wait<0>();
      fence_regs(o);
      qp_first(sbase + OG_SCOL);
      if (tid == 0) mbar_arrive(b_empty + 8 * vl);
      FS(2 * it + 1, 6);
      if (overflow) stage_qregs(q, ob + frag, lane);
      else stage_o(o, l0, l1, ob + frag, lane);
      if (__builtin_expect(overflow || redo0, 0)) {
        __syncwarp();
        #pragma unroll 1
        for (int h = redo0 ? 0 : 1; h < (overflow ? 2 : 1); h++)
          attn_rows_exact(h ? ob + cwg * 8192 : sq, warp, lane, kc + (size_t)(hp * 2 + h) * T_SEQ * T_DH, vc + (size_t)(hp * 2 + h) * T_SEQ * T_DH);
        fence_proxy_async();
        __syncwarp();
        if (lane == 0 && redo0) mbar_arrive(b_ordy + 8 * cwg);
        if (more) mbar_wait(b_full + 32, 0);
        qp_first(sbase + OG_SCOL);
        raw = false;
      }
      if (!LATEF || !more) {
        fence_proxy_async();
        __syncwarp();
        if (lane == 0) mbar_arrive(b_ordy + 16 + 8 * cwg);
      }
      if (lane == 0) {
        mbar_arrive(b_a0 + (rw[3] & rw[7] & rw[11] & rw[15] & zero));
      }
      named_bar_sync(3 + cwg, 128);
      FS(2 * it + 1, 7);
      PS(2 + 2 * it, threadIdx.x == 256);
    }
    if (single) {
      #pragma unroll 1
      for (int i = (blockIdx.x - AT_NFULL) * 256 + threadIdx.x - 128; i < (int)(sizeof(TailMail) / 16); i += 8 * 256) reinterpret_cast<uint4*>(&hm->mail)[i] = make_uint4(0u, 0u, 0u, 0u);
      named_bar_sync(5, 256);
      if (threadIdx.x == 128) {
        red_release_add(&g_hcnt[0], 1u);
        #pragma unroll 1
        for (int i = 4; i < 8; i++) {
          mbar_arrive(b_full + 8 * ring_slot(i));
          mbar_arrive(b_empty + 8 * ring_slot(i)); mbar_arrive(b_empty + 8 * ring_slot(i));
        }
        mbar_arrive(b_go);
      }
      named_bar_sync(5, 256);
    }
    TL_CLK(3, 1, threadIdx.x == 128);
    TL_CTA(1, threadIdx.x == 256);
    TL_END(3, tid == 0);
    __syncwarp();
    QDUMP();
    TL_MARK2(19, tid == 0 && !single);
    mbar_wait(b_bx, 0);
    const uint32_t bx = __shfl_sync(0xffffffffu, lds_u32(s_bx), 0);
    if (bx < 128) {
      tail_consumer(hm, bx, sbase, (int)threadIdx.x - 128, cwg, w_gate, w_up);
    }
  }
}

typedef CUresult (*PFN_encodeTiled)(CUtensorMap*, CUtensorMapDataType, cuuint32_t, void*, const cuuint64_t*, const cuuint64_t*,
                                    const cuuint32_t*, const cuuint32_t*, CUtensorMapInterleave, CUtensorMapSwizzle,
                                    CUtensorMapL2promotion, CUtensorMapFloatOOBfill);

CUtensorMap make_map_2d(PFN_encodeTiled enc, const void* ptr, uint64_t inner, uint64_t outer, uint64_t stride_bytes, uint32_t box_inner, uint32_t box_outer) {
  CUtensorMap m;
  cuuint64_t gd[2] = {inner, outer}; cuuint64_t gs[1] = {stride_bytes};
  cuuint32_t bx[2] = {box_inner, box_outer}; cuuint32_t es[2] = {1, 1};
  enc(&m, CU_TENSOR_MAP_DATA_TYPE_BFLOAT16, 2, const_cast<void*>(ptr), gd, gs, bx, es, CU_TENSOR_MAP_INTERLEAVE_NONE,
      CU_TENSOR_MAP_SWIZZLE_128B, CU_TENSOR_MAP_L2_PROMOTION_L2_128B, CU_TENSOR_MAP_FLOAT_OOB_FILL_NONE);
  return m;
}

CUtensorMap make_map_3d(PFN_encodeTiled enc, const void* ptr, uint64_t cols, uint64_t rows, uint32_t box_rows, uint32_t chunks) {
  CUtensorMap m;
  cuuint64_t gd[3] = {64, rows, cols / 64}; cuuint64_t gs[2] = {cols * 2, 128};
  cuuint32_t bx[3] = {64, box_rows, chunks}; cuuint32_t es[3] = {1, 1, 1};
  enc(&m, CU_TENSOR_MAP_DATA_TYPE_BFLOAT16, 3, const_cast<void*>(ptr), gd, gs, bx, es, CU_TENSOR_MAP_INTERLEAVE_NONE,
      CU_TENSOR_MAP_SWIZZLE_128B, CU_TENSOR_MAP_L2_PROMOTION_L2_128B, CU_TENSOR_MAP_FLOAT_OOB_FILL_NONE);
  return m;
}

}

extern "C" void kernel_launch(void* const* d_in, const int* in_sizes, int n_in, void* d_out, int out_size) {
  const bf16* x      = (const bf16*)d_in[0];
  const bf16* kc     = (const bf16*)d_in[1];
  const bf16* vc     = (const bf16*)d_in[2];
  const bf16* wq     = (const bf16*)d_in[3];
  const bf16* wo     = (const bf16*)d_in[4];
  const bf16* w_r    = (const bf16*)d_in[6];
  const bf16* w_gate = (const bf16*)d_in[7];
  const bf16* w_up   = (const bf16*)d_in[8];
  const bf16* w_down = (const bf16*)d_in[9];
  const bf16* cvec   = (const bf16*)d_in[10];
  const bf16* w_mod  = (const bf16*)d_in[11];
  bf16* out = (bf16*)d_out;

  static PFN_encodeTiled enc = nullptr;
  static void *p_o = nullptr, *p_hm = nullptr;
  if (!enc) {
    void* fn = nullptr; cudaDriverEntryPointQueryResult qres;
    cudaGetDriverEntryPoint("cuTensorMapEncodeTiled", &fn, cudaEnableDefault, &qres);
    enc = (PFN_encodeTiled)fn;
    cudaGetSymbolAddress(&p_o, g_o);
    cudaGetSymbolAddress(&p_hm, g_scr);
    cudaFuncSetAttribute(fused_kernel, cudaFuncAttributeMaxDynamicSharedMemorySize, (int)AT_SMEM);
  }
  const CUtensorMap tm_m   = make_map_2d(enc, w_mod, 6 * T_D, T_D, 6 * T_D * 2, 64, 256);
  const CUtensorMap tm_wq  = make_map_3d(enc, wq, T_DQKV, T_D, 64, 4);
  const CUtensorMap tm_k   = make_map_2d(enc, kc, T_DH, (uint64_t)T_NH * T_SEQ, T_DH * 2, 64, 128);
  const CUtensorMap tm_v   = make_map_2d(enc, vc, T_DH, (uint64_t)T_NH * T_SEQ, T_DH * 2, 64, 128);
  const CUtensorMap tm_ost = make_map_2d(enc, p_o, T_DQKV, T_SEQ, T_DQKV * 2, 64, 64);
  const CUtensorMap tm_old = make_map_2d(enc, p_o, T_DQKV, T_SEQ, T_DQKV * 2, 64, 128);
  const CUtensorMap tm_wo  = make_map_2d(enc, wo, T_D, T_DQKV, T_D * 2, 64, 64);
  const CUtensorMap tm_x   = make_map_2d(enc, x, T_D, T_SEQ, T_D * 2, 64, 128);
  const CUtensorMap tm_out = make_map_2d(enc, out, T_D, T_SEQ, T_D * 2, 64, 128);

  fused_kernel<<<132, 384, AT_SMEM, cudaStreamPerThread>>>(x, cvec, w_mod, (Scratch*)p_hm, 0u, (const uint8_t*)wo, kc, vc, w_r, w_gate, w_up, w_down, out,
             tm_m, tm_wq, tm_k, tm_v, tm_ost, tm_old, tm_wo, tm_x, tm_out);
}
```

```cpp
#include <cuda_runtime.h>
#include <cuda_bf16.h>
#include <cuda.h>
#include <stdint.h>

namespace {

typedef __nv_bfloat16 bf16;

constexpr int T_SEQ = 2048, T_D = 1024, T_NH = 32, T_DH = 128, T_DQKV = 4096, T_F = 3584;

__device__ __align__(1024) bf16 g_o[T_SEQ * T_DQKV];
struct __align__(2048) TailMail {
  float4 part1[T_SEQ * 8];
  uint32_t key[256];
  uint4 cand[16 * 2 * 2 * 128];
  uint32_t cnt[32];
  float ypart[(T_F / 32) * 2 * T_D];
};
struct __align__(2048) Scratch {
  TailMail mail;
  float mod[2 * T_D];
  float modu[16 * 512];
  float2 stat[T_SEQ * 2];
  uint32_t gkey[160];
  uint8_t tab[132 * 4096];
  uint8_t col[8 * 1536];
  unsigned int hcnt[17 * 32];
  float scal[4];
};
__device__ Scratch g_scr;
#define g_part1 hm->mail.part1
#define g_key hm->mail.key
#define g_cand hm->mail.cand
#define CNT_Y hm->mail.cnt
#define g_ypart hm->mail.ypart
#define g_col hm->col
#define g_scal hm->scal
#define g_hcnt hm->hcnt

__device__ __forceinline__ uint32_t smem_u32(const void* p) { return (uint32_t)__cvta_generic_to_shared(p); }
__device__ __forceinline__ void mbar_init(uint32_t bar, uint32_t cnt) { asm volatile("mbarrier.init.shared::cta.b64 [%0], %1;" :: "r"(bar), "r"(cnt)); }
__device__ __forceinline__ void mbar_expect_tx(uint32_t bar, uint32_t bytes) { asm volatile("mbarrier.arrive.expect_tx.shared::cta.b64 _, [%0], %1;" :: "r"(bar), "r"(bytes) : "memory"); }
__device__ __forceinline__ void mbar_arrive(uint32_t bar) { asm volatile("mbarrier.arrive.shared::cta.b64 _, [%0];" :: "r"(bar) : "memory"); }
__device__ __forceinline__ void mbar_wait(uint32_t bar, uint32_t parity) {
  asm volatile("{\n.reg .pred p;\nLAB_WAIT:\nmbarrier.try_wait.parity.shared::cta.b64 p, [%0], %1;\n@!p bra LAB_WAIT;\n}\n" :: "r"(bar), "r"(parity) : "memory");
}
__device__ __forceinline__ bool mbar_test(uint32_t bar, uint32_t parity) {
  uint32_t r; asm volatile("{\n.reg .pred p;\nmbarrier.test_wait.parity.shared::cta.b64 p, [%1], %2;\nselp.u32 %0, 1, 0, p;\n}\n" : "=r"(r) : "r"(bar), "r"(parity) : "memory");
  return r != 0;
}
__device__ __forceinline__ void fence_mbar_init() { asm volatile("fence.mbarrier_init.release.cluster;" ::: "memory"); }
__device__ __forceinline__ uint64_t policy_evict_first() {
  uint64_t p; asm volatile("createpolicy.fractional.L2::evict_first.b64 %0, 1.0;" : "=l"(p)); return p;
}
__device__ __forceinline__ void tma_load_2d_hint(uint32_t dst, const CUtensorMap* map, int c0, int c1, uint32_t bar, uint64_t pol) {
  asm volatile("cp.async.bulk.tensor.2d.shared::cluster.global.mbarrier::complete_tx::bytes.L2::cache_hint [%0], [%1, {%3, %4}], [%2], %5;"
    :: "r"(dst), "l"(map), "r"(bar), "r"(c0), "r"(c1), "l"(pol) : "memory");
}
__device__ __forceinline__ void tma_load_3d_hint(uint32_t dst, const CUtensorMap* map, int c1, int c2, uint32_t bar, uint64_t pol) {
  asm volatile("cp.async.bulk.tensor.3d.shared::cluster.global.mbarrier::complete_tx::bytes.L2::cache_hint [%0], [%1, {%6, %3, %4}], [%2], %5;"
    :: "r"(dst), "l"(map), "r"(bar), "r"(c1), "r"(c2), "l"(pol), "r"(0) : "memory");
}
__device__ __forceinline__ void tma_store_2d(const CUtensorMap* map, uint32_t src, int c0, int c1) {
  asm volatile("cp.async.bulk.tensor.2d.global.shared::cta.bulk_group [%0, {%2, %3}], [%1];" :: "l"(map), "r"(src), "r"(c0), "r"(c1) : "memory");
}
__device__ __forceinline__ void prefetch_tmap(const CUtensorMap* map) { asm volatile("prefetch.tensormap [%0];" :: "l"(map) : "memory"); }
__device__ __forceinline__ void l2_prefetch_bulk(const void* p, uint32_t bytes) {
  asm volatile("cp.async.bulk.prefetch.L2.global [%0], %1;" :: "l"(p), "r"(bytes) : "memory");
}
__device__ __forceinline__ void bulk_commit() { asm volatile("cp.async.bulk.commit_group;" ::: "memory"); }
template<int N> __device__ __forceinline__ void bulk_wait_read() { asm volatile("cp.async.bulk.wait_group.read %0;" :: "n"(N) : "memory"); }
template<int N> __device__ __forceinline__ void bulk_wait() { asm volatile("cp.async.bulk.wait_group %0;" :: "n"(N) : "memory"); }
__device__ __forceinline__ void named_bar_sync(int id, int nthreads) { asm volatile("bar.sync %0, %1;" :: "r"(id), "r"(nthreads) : "memory"); }
__device__ __forceinline__ void named_bar_arrive(int id, int nthreads) { asm volatile("bar.arrive %0, %1;" :: "r"(id), "r"(nthreads) : "memory"); }
__device__ __forceinline__ void named_bar_arrive_if(bool c, int id, int nthreads) { asm volatile("{\n.reg .pred p;\nsetp.ne.u32 p, %2, 0;\n@p bar.arrive %0, %1;\n}" :: "r"(id), "r"(nthreads), "r"((uint32_t)c) : "memory"); }
__device__ __forceinline__ void wgmma_fence() { asm volatile("wgmma.fence.sync.aligned;" ::: "memory"); }
__device__ __forceinline__ void wgmma_commit() { asm volatile("wgmma.commit_group.sync.aligned;" ::: "memory"); }
template<int N> __device__ __forceinline__ void wgmma_wait() { asm volatile("wgmma.wait_group.sync.aligned %0;" :: "n"(N) : "memory"); }
template<int R> __device__ __forceinline__ void reg_alloc() { asm volatile("setmaxnreg.inc.sync.aligned.u32 %0;" :: "n"(R)); }
template<int R> __device__ __forceinline__ void reg_dealloc() { asm volatile("setmaxnreg.dec.sync.aligned.u32 %0;" :: "n"(R)); }
__device__ __forceinline__ bool elect_one() {
  uint32_t pred; asm volatile("{\n.reg .pred p;\nelect.sync _|p, 0xffffffff;\nselp.u32 %0, 1, 0, p;\n}\n" : "=r"(pred)); return pred != 0;
}
__device__ __forceinline__ uint32_t pack_bf16(float lo, float hi) {
  uint32_t r; asm("cvt.rn.bf16x2.f32 %0, %1, %2;" : "=r"(r) : "f"(hi), "f"(lo)); return r;
}
__device__ __forceinline__ void stmatrix_x4(uint32_t addr, uint32_t r0, uint32_t r1, uint32_t r2, uint32_t r3) {
  asm volatile("stmatrix.sync.aligned.m8n8.x4.shared.b16 [%0], {%1, %2, %3, %4};" :: "r"(addr), "r"(r0), "r"(r1), "r"(r2), "r"(r3) : "memory");
}
__device__ __forceinline__ void fence_proxy_async() { asm volatile("fence.proxy.async.shared::cta;" ::: "memory"); }
__device__ __forceinline__ float ex2_approx(float x) { float y; asm("ex2.approx.ftz.f32 %0, %1;" : "=f"(y) : "f"(x)); return y; }
template<int N> __device__ __forceinline__ void fence_regs(float (&r)[N]) {
  #pragma unroll
  for (int i = 0; i < N; i++) asm volatile("" : "+f"(r[i]) :: "memory");
}
template<int N> __device__ __forceinline__ void zero_regs(float (&r)[N]) {
  #pragma unroll
  for (int i = 0; i < N; i += 2) asm volatile("mov.b64 {%0, %1}, 0;" : "=f"(r[i]), "=f"(r[i + 1]));
}
__device__ __forceinline__ float rbf(float x) { return __uint_as_float(pack_bf16(0.f, x)); }
__device__ __forceinline__ float bflo(uint32_t v) { return __uint_as_float(v << 16); }
__device__ __forceinline__ float bfhi(uint32_t v) { return __uint_as_float(v & 0xffff0000u); }

#define TL_START(k) do {} while (0)
#define TL_END(k, cond) do {} while (0)
#define TL_CTA(i, cond) do {} while (0)
#define FS(slot, k) do {} while (0)
#define QS(idx) do {} while (0)
#define QDUMP() do {} while (0)
#define TL_MARK2(k, cond) do {} while (0)
#define TL_CLK(k, i, cond) do {} while (0)

#define HS(k) do {} while (0)
#define HSD(k, dep) do {} while (0)
#define HSDUMP() do {} while (0)
#define PS(k, cond) do {} while (0)
#define PSV(k, cond, v) do {} while (0)
#define PF(k) do {} while (0)
template <int OFFA, int OFFB>
__device__ __forceinline__ void wgmma_m64n256k16_ss_tb(float (&d)[128], uint32_t a_lo, uint32_t b_lo, int scaleD) {
  asm volatile("{\n.reg .pred p;\n.reg .b32 ta, tb;\n.reg .b64 da, db;\nsetp.ne.b32 p, %130, 0;\n"
    "add.u32 ta, %128, %131;\nadd.u32 tb, %129, %132;\n"
    "mov.b64 da, {ta, 0x40000040};\nmov.b64 db, {tb, 0x40000040};\n"
    "wgmma.mma_async.sync.aligned.m64n256k16.f32.bf16.bf16 "
    "{%0, %1, %2, %3, %4, %5, %6, %7, %8, %9, %10, %11, %12, %13, %14, %15, %16, %17, %18, %19, %20, %21, %22, %23, %24, %25, %26, %27, %28, %29, %30, %31, %32, %33, %34, %35, %36, %37, %38, %39, %40, %41, %42, %43, %44, %45, %46, %47, %48, %49, %50, %51, %52, %53, %54, %55, %56, %57, %58, %59, %60, %61, %62, %63, %64, %65, %66, %67, %68, %69, %70, %71, %72, %73, %74, %75, %76, %77, %78, %79, %80, %81, %82, %83, %84, %85, %86, %87, %88, %89, %90, %91, %92, %93, %94, %95, %96, %97, %98, %99, %100, %101, %102, %103, %104, %105, %106, %107, %108, %109, %110, %111, %112, %113, %114, %115, %116, %117, %118, %119, %120, %121, %122, %123, %124, %125, %126, %127}, "
    "da, db, p, 1, 1, 0, 1;\n}\n"
    : "+f"(d[0]), "+f"(d[1]), "+f"(d[2]), "+f"(d[3]), "+f"(d[4]), "+f"(d[5]), "+f"(d[6]), "+f"(d[7]), "+f"(d[8]), "+f"(d[9]), "+f"(d[10]), "+f"(d[11]), "+f"(d[12]), "+f"(d[13]), "+f"(d[14]), "+f"(d[15]), "+f"(d[16]), "+f"(d[17]), "+f"(d[18]), "+f"(d[19]), "+f"(d[20]), "+f"(d[21]), "+f"(d[22]), "+f"(d[23]), "+f"(d[24]), "+f"(d[25]), "+f"(d[26]), "+f"(d[27]), "+f"(d[28]), "+f"(d[29]), "+f"(d[30]), "+f"(d[31]), "+f"(d[32]), "+f"(d[33]), "+f"(d[34]), "+f"(d[35]), "+f"(d[36]), "+f"(d[37]), "+f"(d[38]), "+f"(d[39]), "+f"(d[40]), "+f"(d[41]), "+f"(d[42]), "+f"(d[43]), "+f"(d[44]), "+f"(d[45]), "+f"(d[46]), "+f"(d[47]), "+f"(d[48]), "+f"(d[49]), "+f"(d[50]), "+f"(d[51]), "+f"(d[52]), "+f"(d[53]), "+f"(d[54]), "+f"(d[55]), "+f"(d[56]), "+f"(d[57]), "+f"(d[58]), "+f"(d[59]), "+f"(d[60]), "+f"(d[61]), "+f"(d[62]), "+f"(d[63]), "+f"(d[64]), "+f"(d[65]), "+f"(d[66]), "+f"(d[67]), "+f"(d[68]), "+f"(d[69]), "+f"(d[70]), "+f"(d[71]), "+f"(d[72]), "+f"(d[73]), "+f"(d[74]), "+f"(d[75]), "+f"(d[76]), "+f"(d[77]), "+f"(d[78]), "+f"(d[79]), "+f"(d[80]), "+f"(d[81]), "+f"(d[82]), "+f"(d[83]), "+f"(d[84]), "+f"(d[85]), "+f"(d[86]), "+f"(d[87]), "+f"(d[88]), "+f"(d[89]), "+f"(d[90]), "+f"(d[91]), "+f"(d[92]), "+f"(d[93]), "+f"(d[94]), "+f"(d[95]), "+f"(d[96]), "+f"(d[97]), "+f"(d[98]), "+f"(d[99]), "+f"(d[100]), "+f"(d[101]), "+f"(d[102]), "+f"(d[103]), "+f"(d[104]), "+f"(d[105]), "+f"(d[106]), "+f"(d[107]), "+f"(d[108]), "+f"(d[109]), "+f"(d[110]), "+f"(d[111]), "+f"(d[112]), "+f"(d[113]), "+f"(d[114]), "+f"(d[115]), "+f"(d[116]), "+f"(d[117]), "+f"(d[118]), "+f"(d[119]), "+f"(d[120]), "+f"(d[121]), "+f"(d[122]), "+f"(d[123]), "+f"(d[124]), "+f"(d[125]), "+f"(d[126]), "+f"(d[127])
    : "r"(a_lo), "r"(b_lo), "r"(scaleD), "n"(OFFA), "n"(OFFB));
}

template <int OFFA, int OFFB>
__device__ __forceinline__ void wgmma_m64n128k16_ss_tb(float (&d)[64], uint32_t a_lo, uint32_t b_lo, int scaleD) {
  asm volatile("{\n.reg .pred p;\n.reg .b32 ta, tb;\n.reg .b64 da, db;\nsetp.ne.b32 p, %66, 0;\n"
    "add.u32 ta, %64, %67;\nadd.u32 tb, %65, %68;\n"
    "mov.b64 da, {ta, 0x40000040};\nmov.b64 db, {tb, 0x40000040};\n"
    "wgmma.mma_async.sync.aligned.m64n128k16.f32.bf16.bf16 "
    "{%0, %1, %2, %3, %4, %5, %6, %7, %8, %9, %10, %11, %12, %13, %14, %15, %16, %17, %18, %19, %20, %21, %22, %23, %24, %25, %26, %27, %28, %29, %30, %31, %32, %33, %34, %35, %36, %37, %38, %39, %40, %41, %42, %43, %44, %45, %46, %47, %48, %49, %50, %51, %52, %53, %54, %55, %56, %57, %58, %59, %60, %61, %62, %63}, "
    "da, db, p, 1, 1, 0, 1;\n}\n"
    : "+f"(d[0]), "+f"(d[1]), "+f"(d[2]), "+f"(d[3]), "+f"(d[4]), "+f"(d[5]), "+f"(d[6]), "+f"(d[7]), "+f"(d[8]), "+f"(d[9]), "+f"(d[10]), "+f"(d[11]), "+f"(d[12]), "+f"(d[13]), "+f"(d[14]), "+f"(d[15]), "+f"(d[16]), "+f"(d[17]), "+f"(d[18]), "+f"(d[19]), "+f"(d[20]), "+f"(d[21]), "+f"(d[22]), "+f"(d[23]), "+f"(d[24]), "+f"(d[25]), "+f"(d[26]), "+f"(d[27]), "+f"(d[28]), "+f"(d[29]), "+f"(d[30]), "+f"(d[31]), "+f"(d[32]), "+f"(d[33]), "+f"(d[34]), "+f"(d[35]), "+f"(d[36]), "+f"(d[37]), "+f"(d[38]), "+f"(d[39]), "+f"(d[40]), "+f"(d[41]), "+f"(d[42]), "+f"(d[43]), "+f"(d[44]), "+f"(d[45]), "+f"(d[46]), "+f"(d[47]), "+f"(d[48]), "+f"(d[49]), "+f"(d[50]), "+f"(d[51]), "+f"(d[52]), "+f"(d[53]), "+f"(d[54]), "+f"(d[55]), "+f"(d[56]), "+f"(d[57]), "+f"(d[58]), "+f"(d[59]), "+f"(d[60]), "+f"(d[61]), "+f"(d[62]), "+f"(d[63])
    : "r"(a_lo), "r"(b_lo), "r"(scaleD), "n"(OFFA), "n"(OFFB));
}

template <int OFFB>
__device__ __forceinline__ void wgmma_m64n256k16_rs_tb(float (&d)[128], uint32_t a0, uint32_t a1, uint32_t a2, uint32_t a3, uint32_t b_lo, int scaleD) {
  asm volatile("{\n.reg .pred p;\n.reg .b32 tb;\n.reg .b64 db;\nsetp.ne.b32 p, %133, 0;\n"
    "add.u32 tb, %132, %134;\n"
    "mov.b64 db, {tb, 0x40000040};\n"
    "wgmma.mma_async.sync.aligned.m64n256k16.f32.bf16.bf16 "
    "{%0, %1, %2, %3, %4, %5, %6, %7, %8, %9, %10, %11, %12, %13, %14, %15, %16, %17, %18, %19, %20, %21, %22, %23, %24, %25, %26, %27, %28, %29, %30, %31, %32, %33, %34, %35, %36, %37, %38, %39, %40, %41, %42, %43, %44, %45, %46, %47, %48, %49, %50, %51, %52, %53, %54, %55, %56, %57, %58, %59, %60, %61, %62, %63, %64, %65, %66, %67, %68, %69, %70, %71, %72, %73, %74, %75, %76, %77, %78, %79, %80, %81, %82, %83, %84, %85, %86, %87, %88, %89, %90, %91, %92, %93, %94, %95, %96, %97, %98, %99, %100, %101, %102, %103, %104, %105, %106, %107, %108, %109, %110, %111, %112, %113, %114, %115, %116, %117, %118, %119, %120, %121, %122, %123, %124, %125, %126, %127}, "
    "{%128, %129, %130, %131}, db, p, 1, 1, 1;\n}\n"
    : "+f"(d[0]), "+f"(d[1]), "+f"(d[2]), "+f"(d[3]), "+f"(d[4]), "+f"(d[5]), "+f"(d[6]), "+f"(d[7]), "+f"(d[8]), "+f"(d[9]), "+f"(d[10]), "+f"(d[11]), "+f"(d[12]), "+f"(d[13]), "+f"(d[14]), "+f"(d[15]), "+f"(d[16]), "+f"(d[17]), "+f"(d[18]), "+f"(d[19]), "+f"(d[20]), "+f"(d[21]), "+f"(d[22]), "+f"(d[23]), "+f"(d[24]), "+f"(d[25]), "+f"(d[26]), "+f"(d[27]), "+f"(d[28]), "+f"(d[29]), "+f"(d[30]), "+f"(d[31]), "+f"(d[32]), "+f"(d[33]), "+f"(d[34]), "+f"(d[35]), "+f"(d[36]), "+f"(d[37]), "+f"(d[38]), "+f"(d[39]), "+f"(d[40]), "+f"(d[41]), "+f"(d[42]), "+f"(d[43]), "+f"(d[44]), "+f"(d[45]), "+f"(d[46]), "+f"(d[47]), "+f"(d[48]), "+f"(d[49]), "+f"(d[50]), "+f"(d[51]), "+f"(d[52]), "+f"(d[53]), "+f"(d[54]), "+f"(d[55]), "+f"(d[56]), "+f"(d[57]), "+f"(d[58]), "+f"(d[59]), "+f"(d[60]), "+f"(d[61]), "+f"(d[62]), "+f"(d[63]), "+f"(d[64]), "+f"(d[65]), "+f"(d[66]), "+f"(d[67]), "+f"(d[68]), "+f"(d[69]), "+f"(d[70]), "+f"(d[71]), "+f"(d[72]), "+f"(d[73]), "+f"(d[74]), "+f"(d[75]), "+f"(d[76]), "+f"(d[77]), "+f"(d[78]), "+f"(d[79]), "+f"(d[80]), "+f"(d[81]), "+f"(d[82]), "+f"(d[83]), "+f"(d[84]), "+f"(d[85]), "+f"(d[86]), "+f"(d[87]), "+f"(d[88]), "+f"(d[89]), "+f"(d[90]), "+f"(d[91]), "+f"(d[92]), "+f"(d[93]), "+f"(d[94]), "+f"(d[95]), "+f"(d[96]), "+f"(d[97]), "+f"(d[98]), "+f"(d[99]), "+f"(d[100]), "+f"(d[101]), "+f"(d[102]), "+f"(d[103]), "+f"(d[104]), "+f"(d[105]), "+f"(d[106]), "+f"(d[107]), "+f"(d[108]), "+f"(d[109]), "+f"(d[110]), "+f"(d[111]), "+f"(d[112]), "+f"(d[113]), "+f"(d[114]), "+f"(d[115]), "+f"(d[116]), "+f"(d[117]), "+f"(d[118]), "+f"(d[119]), "+f"(d[120]), "+f"(d[121]), "+f"(d[122]), "+f"(d[123]), "+f"(d[124]), "+f"(d[125]), "+f"(d[126]), "+f"(d[127])
    : "r"(a0), "r"(a1), "r"(a2), "r"(a3), "r"(b_lo), "r"(scaleD), "n"(OFFB));
}

template <int OFFB>
__device__ __forceinline__ void wgmma_m64n128k16_rs_tb(float (&d)[64], uint32_t a0, uint32_t a1, uint32_t a2, uint32_t a3, uint32_t b_lo, int scaleD) {
  asm volatile("{\n.reg .pred p;\n.reg .b32 tb;\n.reg .b64 db;\nsetp.ne.b32 p, %69, 0;\n"
    "add.u32 tb, %68, %70;\n"
    "mov.b64 db, {tb, 0x40000040};\n"
    "wgmma.mma_async.sync.aligned.m64n128k16.f32.bf16.bf16 "
    "{%0, %1, %2, %3, %4, %5, %6, %7, %8, %9, %10, %11, %12, %13, %14, %15, %16, %17, %18, %19, %20, %21, %22, %23, %24, %25, %26, %27, %28, %29, %30, %31, %32, %33, %34, %35, %36, %37, %38, %39, %40, %41, %42, %43, %44, %45, %46, %47, %48, %49, %50, %51, %52, %53, %54, %55, %56, %57, %58, %59, %60, %61, %62, %63}, "
    "{%64, %65, %66, %67}, db, p, 1, 1, 1;\n}\n"
    : "+f"(d[0]), "+f"(d[1]), "+f"(d[2]), "+f"(d[3]), "+f"(d[4]), "+f"(d[5]), "+f"(d[6]), "+f"(d[7]), "+f"(d[8]), "+f"(d[9]), "+f"(d[10]), "+f"(d[11]), "+f"(d[12]), "+f"(d[13]), "+f"(d[14]), "+f"(d[15]), "+f"(d[16]), "+f"(d[17]), "+f"(d[18]), "+f"(d[19]), "+f"(d[20]), "+f"(d[21]), "+f"(d[22]), "+f"(d[23]), "+f"(d[24]), "+f"(d[25]), "+f"(d[26]), "+f"(d[27]), "+f"(d[28]), "+f"(d[29]), "+f"(d[30]), "+f"(d[31]), "+f"(d[32]), "+f"(d[33]), "+f"(d[34]), "+f"(d[35]), "+f"(d[36]), "+f"(d[37]), "+f"(d[38]), "+f"(d[39]), "+f"(d[40]), "+f"(d[41]), "+f"(d[42]), "+f"(d[43]), "+f"(d[44]), "+f"(d[45]), "+f"(d[46]), "+f"(d[47]), "+f"(d[48]), "+f"(d[49]), "+f"(d[50]), "+f"(d[51]), "+f"(d[52]), "+f"(d[53]), "+f"(d[54]), "+f"(d[55]), "+f"(d[56]), "+f"(d[57]), "+f"(d[58]), "+f"(d[59]), "+f"(d[60]), "+f"(d[61]), "+f"(d[62]), "+f"(d[63])
    : "r"(a0), "r"(a1), "r"(a2), "r"(a3), "r"(b_lo), "r"(scaleD), "n"(OFFB));
}

template <int OFFB>
__device__ __forceinline__ void wgmma_m64n128k16_rs(float (&d)[64], uint32_t a0, uint32_t a1, uint32_t a2, uint32_t a3, uint32_t b_lo, int scaleD) {
  asm volatile("{\n.reg .pred p;\n.reg .b32 tb;\n.reg .b64 db;\nsetp.ne.b32 p, %69, 0;\n"
    "add.u32 tb, %68, %70;\n"
    "mov.b64 db, {tb, 0x40000040};\n"
    "wgmma.mma_async.sync.aligned.m64n128k16.f32.bf16.bf16 "
    "{%0, %1, %2, %3, %4, %5, %6, %7, %8, %9, %10, %11, %12, %13, %14, %15, %16, %17, %18, %19, %20, %21, %22, %23, %24, %25, %26, %27, %28, %29, %30, %31, %32, %33, %34, %35, %36, %37, %38, %39, %40, %41, %42, %43, %44, %45, %46, %47, %48, %49, %50, %51, %52, %53, %54, %55, %56, %57, %58, %59, %60, %61, %62, %63}, "
    "{%64, %65, %66, %67}, db, p, 1, 1, 0;\n}\n"
    : "+f"(d[0]), "+f"(d[1]), "+f"(d[2]), "+f"(d[3]), "+f"(d[4]), "+f"(d[5]), "+f"(d[6]), "+f"(d[7]), "+f"(d[8]), "+f"(d[9]), "+f"(d[10]), "+f"(d[11]), "+f"(d[12]), "+f"(d[13]), "+f"(d[14]), "+f"(d[15]), "+f"(d[16]), "+f"(d[17]), "+f"(d[18]), "+f"(d[19]), "+f"(d[20]), "+f"(d[21]), "+f"(d[22]), "+f"(d[23]), "+f"(d[24]), "+f"(d[25]), "+f"(d[26]), "+f"(d[27]), "+f"(d[28]), "+f"(d[29]), "+f"(d[30]), "+f"(d[31]), "+f"(d[32]), "+f"(d[33]), "+f"(d[34]), "+f"(d[35]), "+f"(d[36]), "+f"(d[37]), "+f"(d[38]), "+f"(d[39]), "+f"(d[40]), "+f"(d[41]), "+f"(d[42]), "+f"(d[43]), "+f"(d[44]), "+f"(d[45]), "+f"(d[46]), "+f"(d[47]), "+f"(d[48]), "+f"(d[49]), "+f"(d[50]), "+f"(d[51]), "+f"(d[52]), "+f"(d[53]), "+f"(d[54]), "+f"(d[55]), "+f"(d[56]), "+f"(d[57]), "+f"(d[58]), "+f"(d[59]), "+f"(d[60]), "+f"(d[61]), "+f"(d[62]), "+f"(d[63])
    : "r"(a0), "r"(a1), "r"(a2), "r"(a3), "r"(b_lo), "r"(scaleD), "n"(OFFB));
}

__device__ __forceinline__ uint4 ldg_nc_v4(const void* p) {
  uint4 v;
    asm volatile("{\n.reg .b64 pol;\ncreatepolicy.fractional.L2::evict_first.b64 pol, 1.0;\n"
                 "ld.global.nc.L1::no_allocate.L2::cache_hint.v4.u32 {%0, %1, %2, %3}, [%4], pol;\n}\n" : "=r"(v.x), "=r"(v.y), "=r"(v.z), "=r"(v.w) : "l"(p));
  return v;
}
__device__ __forceinline__ uint64_t pol_normal() {
  uint64_t p; asm volatile("createpolicy.fractional.L2::evict_normal.b64 %0, 1.0;" : "=l"(p)); return p;
}
__device__ __forceinline__ float rcp_approx(float x) { float y; asm("rcp.approx.ftz.f32 %0, %1;" : "=f"(y) : "f"(x)); return y; }
__device__ __forceinline__ float sigmoid_f(float v) { return rcp_approx(1.0f + ex2_approx(v * -1.4426950408889634f)); }
__device__ __forceinline__ float silu_bf(float v) { return rbf(v * sigmoid_f(v)); }
__device__ __forceinline__ uint32_t rank_key(float r, int idx) {
  const uint32_t b = __float_as_uint(r) >> 16;
  const uint32_t u = (r != r) ? 0u : ((b & 0x8000u) ? (~b & 0xffffu) : (b | 0x8000u));
  return (u << 16) | (0xffffu - (uint32_t)idx);
}
__device__ __forceinline__ void warp_top2(uint32_t& k1, uint32_t& k2) {
  const uint32_t m1 = __reduce_max_sync(0xffffffffu, k1);
  k2 = __reduce_max_sync(0xffffffffu, k1 == m1 ? k2 : k1);
  k1 = m1;
}
__device__ __forceinline__ uint32_t bmul2(uint32_t a, uint32_t b) { uint32_t r; asm("mul.rn.bf16x2 %0, %1, %2;" : "=r"(r) : "r"(a), "r"(b)); return r; }
__device__ __forceinline__ uint32_t badd2(uint32_t a, uint32_t b) { uint32_t r; asm("add.rn.bf16x2 %0, %1, %2;" : "=r"(r) : "r"(a), "r"(b)); return r; }
__device__ __forceinline__ uint32_t bsub2(uint32_t a, uint32_t b) { uint32_t r; asm("sub.rn.bf16x2 %0, %1, %2;" : "=r"(r) : "r"(a), "r"(b)); return r; }
__device__ __forceinline__ float sqrt_approx(float x) { float y; asm("sqrt.approx.f32 %0, %1;" : "=f"(y) : "f"(x)); return y; }
__device__ __forceinline__ uint32_t ln_norm2(uint32_t x1, uint32_t mb2, float inv) {
  const uint32_t d = bsub2(x1, mb2);
  return pack_bf16(bflo(d) * inv, bfhi(d) * inv);
}
__device__ __forceinline__ uint32_t ln_mod2(uint32_t x1, uint32_t mb2, float inv, uint32_t c1, uint32_t sb) { return badd2(bmul2(ln_norm2(x1, mb2, inv), c1), sb); }
__device__ __forceinline__ void ldmatrix_x4(uint32_t addr, uint32_t& r0, uint32_t& r1, uint32_t& r2, uint32_t& r3) {
  asm volatile("ldmatrix.sync.aligned.m8n8.x4.shared.b16 {%0, %1, %2, %3}, [%4];" : "=r"(r0), "=r"(r1), "=r"(r2), "=r"(r3) : "r"(addr) : "memory");
}
__device__ __forceinline__ uint4 ldg_stream_v4(const void* p, uint64_t pol) {
  uint4 v; asm volatile("ld.global.nc.L1::no_allocate.L2::cache_hint.L2::128B.v4.u32 {%0, %1, %2, %3}, [%4], %5;" : "=r"(v.x), "=r"(v.y), "=r"(v.z), "=r"(v.w) : "l"(p), "l"(pol)); return v;
}
__device__ __forceinline__ void bulk_load_hint(uint32_t dst, const void* src, uint32_t bytes, uint32_t bar, uint64_t pol) {
  asm volatile("cp.async.bulk.shared::cluster.global.mbarrier::complete_tx::bytes.L2::cache_hint [%0], [%1], %2, [%3], %4;"
    :: "r"(dst), "l"(src), "r"(bytes), "r"(bar), "l"(pol) : "memory");
}
__device__ __forceinline__ void red_release_add(unsigned int* p, unsigned int v) { asm volatile("red.release.gpu.global.add.u32 [%0], %1;" :: "l"(p), "r"(v) : "memory"); }
__device__ __forceinline__ unsigned int ld_acquire(const unsigned int* p) { unsigned int v; asm volatile("ld.acquire.gpu.global.u32 %0, [%1];" : "=r"(v) : "l"(p) : "memory"); return v; }
__device__ __forceinline__ void spin_until(const unsigned int* p, unsigned int target) {
  #pragma unroll 1
  for (unsigned int i = 0; i < (1u << 22); i++) { if (ld_acquire(p) >= target) return; }
}
__device__ __forceinline__ float lds_f32(uint32_t a) { float v; asm volatile("ld.shared.f32 %0, [%1];" : "=f"(v) : "r"(a) : "memory"); return v; }
__device__ __forceinline__ float2 lds_f32x2(uint32_t a) { float2 v; asm volatile("ld.shared.v2.f32 {%0, %1}, [%2];" : "=f"(v.x), "=f"(v.y) : "r"(a) : "memory"); return v; }
__device__ __forceinline__ uint2 lds_u32x2(uint32_t a) { uint2 v; asm volatile("ld.shared.v2.u32 {%0, %1}, [%2];" : "=r"(v.x), "=r"(v.y) : "r"(a) : "memory"); return v; }
__device__ __forceinline__ uint32_t lds_u32(uint32_t a) { uint32_t v; asm volatile("ld.shared.u32 %0, [%1];" : "=r"(v) : "r"(a) : "memory"); return v; }
__device__ __forceinline__ void sts_u32(uint32_t a, uint32_t v) { asm volatile("st.shared.u32 [%0], %1;" :: "r"(a), "r"(v) : "memory"); }
__device__ __forceinline__ void sts_u32x2(uint32_t a, uint32_t x, uint32_t y) { asm volatile("st.shared.v2.u32 [%0], {%1, %2};" :: "r"(a), "r"(x), "r"(y) : "memory"); }
__device__ __forceinline__ void sts_f32(uint32_t a, float v) { asm volatile("st.shared.f32 [%0], %1;" :: "r"(a), "f"(v) : "memory"); }
__device__ __forceinline__ void sts_f32x4(uint32_t a, float x, float y, float z, float w) { asm volatile("st.shared.v4.f32 [%0], {%1, %2, %3, %4};" :: "r"(a), "f"(x), "f"(y), "f"(z), "f"(w) : "memory"); }

__device__ __forceinline__ uint4 lds_u32x4(uint32_t a) { uint4 v; asm volatile("ld.shared.v4.u32 {%0, %1, %2, %3}, [%4];" : "=r"(v.x), "=r"(v.y), "=r"(v.z), "=r"(v.w) : "r"(a) : "memory"); return v; }
__device__ __forceinline__ void sts_u32x4(uint32_t a, uint32_t x, uint32_t y, uint32_t z, uint32_t w) { asm volatile("st.shared.v4.u32 [%0], {%1, %2, %3, %4};" :: "r"(a), "r"(x), "r"(y), "r"(z), "r"(w) : "memory"); }
__device__ __forceinline__ void st_tagged(float* p, float v) {
  const uint32_t b = __float_as_uint(v);
  asm volatile("st.relaxed.gpu.global.u32 [%0], %1;" :: "l"(p), "r"(b == 0u ? 0x80000000u : b) : "memory");
}
__device__ __forceinline__ void st_tagged4(float* p, float x, float y, float z, float w) {
  const uint32_t a = __float_as_uint(x), b = __float_as_uint(y), c = __float_as_uint(z), d = __float_as_uint(w);
  asm volatile("st.relaxed.gpu.global.v4.u32 [%0], {%1, %2, %3, %4};" :: "l"(p), "r"(a == 0u ? 0x80000000u : a), "r"(b == 0u ? 0x80000000u : b),
               "r"(c == 0u ? 0x80000000u : c), "r"(d == 0u ? 0x80000000u : d) : "memory");
}
__device__ __forceinline__ void st_relaxed2(void* p, uint32_t a, uint32_t b) { asm volatile("st.relaxed.gpu.global.v2.u32 [%0], {%1, %2};" :: "l"(p), "r"(a), "r"(b) : "memory"); }
__device__ __forceinline__ float4 ld_tagged4(const float* p) {
  float4 v; asm volatile("ld.relaxed.gpu.global.v4.f32 {%0, %1, %2, %3}, [%4];" : "=f"(v.x), "=f"(v.y), "=f"(v.z), "=f"(v.w) : "l"(p) : "memory"); return v;
}
__device__ __forceinline__ bool tagged4(const float4& v) {
  return __float_as_uint(v.x) != 0u && __float_as_uint(v.y) != 0u && __float_as_uint(v.z) != 0u && __float_as_uint(v.w) != 0u;
}
__device__ __forceinline__ void hint_arrive(uint32_t* p) { asm volatile("red.relaxed.gpu.global.add.u32 [%0], 1;" :: "l"(p) : "memory"); }
__device__ __forceinline__ void hint_wait(const uint32_t* p, uint32_t target) {
  uint32_t v = 0u;
  #pragma unroll 1
  for (unsigned int i = 0; i < (1u << 22) && v < target; i++) asm volatile("ld.relaxed.gpu.global.u32 %0, [%1];" : "=r"(v) : "l"(p) : "memory");
}
__device__ __forceinline__ void fence_proxy_async_global() { asm volatile("fence.proxy.async.global;" ::: "memory"); }

__device__ __forceinline__ void mma_bf16(float (&d)[4], uint32_t a0, uint32_t a1, uint32_t a2, uint32_t a3, uint32_t b0, uint32_t b1) {
  asm volatile("mma.sync.aligned.m16n8k16.row.col.f32.bf16.bf16.f32 {%0, %1, %2, %3}, {%4, %5, %6, %7}, {%8, %9}, {%0, %1, %2, %3};"
               : "+f"(d[0]), "+f"(d[1]), "+f"(d[2]), "+f"(d[3]) : "r"(a0), "r"(a1), "r"(a2), "r"(a3), "r"(b0), "r"(b1));
}
__device__ __forceinline__ uint32_t bfma2(uint32_t a, uint32_t b, uint32_t c) { uint32_t r; asm("fma.rn.bf16x2 %0, %1, %2, %3;" : "=r"(r) : "r"(a), "r"(b), "r"(c)); return r; }
#define PRE_T 1000
#define WDLY 3000
#define GDLY 4000
#define GDLY2 8000
#define ST1_T 6000
#define A_T 4500
#define QT0 0
#define QTO 0
#define QTN 0
#define QARR 4
#define WCH 4
#define QORD 0
#define PACE 128
#define EREL 0
#define EA0 1
#define PINQ 1
#define PINS 0
#define SYN_G 0
#define SYN_S 2
#define GSLP 50
#define DROPN 2
#define SERP 1
#define DYN 1
#define ASLP 200
#define CPCM 1
#define ZMMA 0
#define LATEF 0
#define SGL_T 82000
#define CLR_T 70000
#define NDUM 16
#define XDLY 1000
#define SDLY 5800
#define EPOLL 1
__device__ __forceinline__ uint32_t clock_lo() { uint32_t c; asm volatile("mov.u32 %0, %%clock;" : "=r"(c) :: "memory"); return c; }
__device__ __forceinline__ void wait_clock(uint32_t t0, uint32_t n) {
  #pragma unroll 1
  while (clock_lo() - t0 < n) {}
}
__device__ __forceinline__ void sleep_until(uint32_t t0, uint32_t n) {
  #pragma unroll 1
  while (clock_lo() - t0 < n) __nanosleep(500);
}
__device__ __forceinline__ float2 ld_tagged2(const float2* p) {
  float2 v; asm volatile("ld.relaxed.gpu.global.v2.f32 {%0, %1}, [%2];" : "=f"(v.x), "=f"(v.y) : "l"(p) : "memory"); return v;
}
template <int N, int NW>
__device__ __forceinline__ float gemv64(const uint4 (&w)[N], const uint32_t (&sv)[N / 2], uint32_t scr, int t2) {
  const int lane = t2 & 31, g = lane >> 2;
  const uint32_t lo = (g & 1) ? 0x1044u : 0x4410u, hi = (g & 1) ? 0x3244u : 0x4432u;
  const uint32_t lo0 = g < 2 ? lo : 0x4444u, hi0 = g < 2 ? hi : 0x4444u, lo1 = (g & 6) == 2 ? lo : 0x4444u, hi1 = (g & 6) == 2 ? hi : 0x4444u;
  float d[2][4] = {{0.f, 0.f, 0.f, 0.f}, {0.f, 0.f, 0.f, 0.f}};
  #pragma unroll
  for (int i = 0; i < N; i++)
    mma_bf16(d[i & 1], w[i].x, w[i].y, w[i].z, w[i].w, __byte_perm(sv[i >> 1], 0u, (i & 1) ? hi0 : lo0), __byte_perm(sv[i >> 1], 0u, (i & 1) ? hi1 : lo1));
  if ((lane & 2) == 0) sts_f32x4(scr + (t2 >> 5) * 256 + g * 32 + (lane & 1) * 16, d[0][0] + d[1][0], d[0][1] + d[1][1], d[0][2] + d[1][2], d[0][3] + d[1][3]);
  named_bar_sync(NW == 8 ? 5 : 3, NW * 32);
  float sum = 0.f;
  if (t2 < 64) {
    #pragma unroll
    for (int i = 0; i < NW; i += 2) sum += lds_f32(scr + i * 256 + t2 * 4) + lds_f32(scr + i * 256 + 256 + t2 * 4);
  }
  return sum;
}
__device__ __forceinline__ uint32_t silu2(uint32_t c) { return pack_bf16(silu_bf(bflo(c)), silu_bf(bfhi(c))); }
__device__ __forceinline__ void head_first(Scratch* hm, uint32_t scr, int t2, const bf16* __restrict__ cvec, const bf16* __restrict__ w_mod) {
  const int row = (blockIdx.x >> 3) * 64 + (t2 >> 5) * 16 + (t2 & 3) * 4;
  const bf16* wp = w_mod + (size_t)row * (6 * T_D) + (blockIdx.x & 4) * 256 + (blockIdx.x & 3) * 64 + (t2 & 28) * 2;
  uint4 w[4];
  #pragma unroll
  for (int i = 0; i < 4; i++) w[i] = ldg_nc_v4(wp + i * 6 * T_D);
  const uint2 c = *reinterpret_cast<const uint2*>(cvec + row);
  const uint32_t sv[2] = {silu2(c.x), silu2(c.y)};
  const float sum = gemv64<4, 4>(w, sv, scr, t2);
  if (t2 < 64) st_tagged(hm->modu + (blockIdx.x >> 3) * 512 + (blockIdx.x & 7) * 64 + t2, sum);
  HS(1);
}
__device__ __forceinline__ void head_stats(Scratch* hm, uint32_t xs, uint32_t b_x, int tid) {
  const int lane = tid & 31, w = tid >> 5, g = lane >> 2;
  float d[4][4] = {{0.f, 0.f, 0.f, 0.f}, {0.f, 0.f, 0.f, 0.f}, {0.f, 0.f, 0.f, 0.f}, {0.f, 0.f, 0.f, 0.f}};
  const uint32_t xa = xs + ((w & 1) * 8 + g) * 2048 + (w >> 1) * 1024 + (g & 1) * 64 + (lane & 3) * 16;
  float2* dst = hm->stat + ((blockIdx.x * 2 + (w & 1)) * 2 + (w >> 1)) * 8 + g;
  mbar_wait(b_x, 0);
  #pragma unroll
  for (int j = 0; j < 16; j++) {
    const uint4 v = lds_u32x4((xa ^ ((j & 1) * 64)) + (j >> 1) * 128);
    mma_bf16(d[2 * (j & 1)], v.x, 0x3F803F80u, v.y, 0x3F803F80u, v.x, v.y);
    mma_bf16(d[2 * (j & 1) + 1], v.z, 0x3F803F80u, v.w, 0x3F803F80u, v.z, v.w);
  }
  #pragma unroll
  for (int e = 0; e < 4; e++) d[0][e] = (d[0][e] + d[1][e]) + (d[2][e] + d[3][e]);
  const uint32_t sm = __float_as_uint((g & 1) ? d[0][3] : d[0][2]), sq = __float_as_uint((g & 1) ? d[0][1] : d[0][0]);
  if ((lane & 3) == (g >> 1)) st_relaxed2(dst, sm == 0u ? 0x80000000u : sm, sq == 0u ? 0x80000000u : sq);
  HSD(3, sm);
}
__device__ __forceinline__ void put_table(uint32_t tab, int l, bool ca, const float4& v) {
  uint32_t m0 = pack_bf16(v.x, v.y), m1 = pack_bf16(v.z, v.w);
  if (ca) { m0 = badd2(m0, 0x3F803F80u); m1 = badd2(m1, 0x3F803F80u); }
  tab += (l >> 2) * 64 + (l & 1) * 32 + (l & 2) * 2 + (ca ? 0 : 8);
  sts_u32(tab, m0); sts_u32(tab + 16, m1);
}
__device__ __forceinline__ void head_gather(Scratch* hm, uint32_t tab, int tid) {
  float4 p[16];
  #pragma unroll 1
  for (unsigned int spin = 0; spin < (1u << 22); spin++) {
    uint32_t m = 0xffffffffu;
    #pragma unroll
    for (int k = 0; k < 16; k++) p[k] = ld_tagged4(hm->modu + k * 512 + tid * 4);
    #pragma unroll
    for (int k = 0; k < 16; k++) m = min(min(m, min(__float_as_uint(p[k].x), __float_as_uint(p[k].y))), min(__float_as_uint(p[k].z), __float_as_uint(p[k].w)));
    if (m != 0u) break;
  }
  #pragma unroll
  for (int o = 1; o < 16; o <<= 1)
    #pragma unroll
    for (int k = 0; k < 16; k += 2 * o) { p[k].x += p[k + o].x; p[k].y += p[k + o].y; p[k].z += p[k + o].z; p[k].w += p[k + o].w; }
  put_table(tab, tid & 63, tid >= 64, p[0]);
  fence_proxy_async();
  __syncwarp();
  HS(2);
}
__device__ __forceinline__ float mod_cols(uint32_t sbase, uint32_t sc, uint32_t bar, uint32_t par, int t2, const CUtensorMap* tm, int col) {
  fence_proxy_async();
  named_bar_sync(5, 256);
  if (t2 == 0) {
    const uint64_t pol = policy_evict_first();
    mbar_expect_tx(bar, 131072);
    #pragma unroll 1
    for (int i = 0; i < 4; i++) tma_load_2d_hint(sbase + (i == 3 ? 5 : i) * 32768, tm, col, i * 256, bar, pol);
  }
  __syncwarp();
  const int w8 = t2 >> 5, t = t2 & 3, g = (t2 >> 2) & 7;
  const uint32_t wa = sbase + (w8 >= 6 ? w8 + 4 : w8) * 16384 + t * 256;
  uint4 w[32];
  uint32_t sv[16];
  #pragma unroll
  for (int i = 0; i < 16; i++) sv[i] = lds_u32(sc + w8 * 256 + i * 16 + t * 4);
  mbar_wait(bar, par);
  #pragma unroll
  for (int i = 0; i < 32; i++) w[i] = lds_u32x4(wa + (i >> 1) * 1024 + (i & 1) * 128 + ((g ^ (t * 2 + (i & 1))) << 4));
  return gemv64<32, 8>(w, sv, sc + 2048, t2);
}
__device__ __forceinline__ uint32_t ln_stat(float sm, float sq) {
  const float mean = sm * (1.0f / T_D), var = fmaxf(fmaf(-mean, mean, sq * (1.0f / T_D)), 0.f);
  return pack_bf16(mean, sqrt_approx(rbf(rbf(var) + 1e-05f)));
}
__device__ __forceinline__ void gather_table(Scratch* hm, uint32_t t0, uint32_t tab0, uint32_t b_tab, uint32_t b_a0, int a, int lane) {
  wait_clock(t0, GDLY2);
  #pragma unroll 1
  for (int r = 2; r < 8; r++) {
    float4 v;
    #pragma unroll 1
    for (unsigned int spin = 0; spin < (1u << 22); spin++) {
      v = ld_tagged4(hm->mod + a * T_D + r * 128 + lane * 4);
      if (__all_sync(0xffffffffu, tagged4(v))) break;
      if (GSLP) __nanosleep(GSLP);
    }
    put_table(tab0 + r * 512, lane, a, v);
    if (r == 7) {
      mbar_wait(b_a0, 0);
      fence_proxy_async();
      named_bar_sync(8, 64);
      if (a == 0 && elect_one()) {
        asm volatile("cp.async.bulk.global.shared::cta.bulk_group [%0], [%1], 4096;" :: "l"(hm->tab + blockIdx.x * 4096), "r"(tab0) : "memory");
        bulk_commit();
        bulk_wait<0>();
      }
    }
    __syncwarp();
    if (lane == 0) mbar_arrive(b_tab + 8 * r);
    if (r < 6) HS(2 + r);
  }
}

__device__ __forceinline__ uint32_t assign_tile(Scratch* hm, uint32_t t0, int lane) {
  uint32_t me; asm("mov.u32 %0, %%smid;" : "=r"(me));
  me = (me & 255u) + 1u;
  if (lane == 0) asm volatile("st.relaxed.gpu.global.u32 [%0], %1;" :: "l"(hm->gkey + blockIdx.x), "r"((t0 & ~511u) | me) : "memory");
  uint32_t k[5];
  #pragma unroll 1
  for (unsigned int spin = 0; spin < (1u << 20); spin++) {
    __nanosleep(ASLP);
    #pragma unroll
    for (int m = 0; m < 5; m++) asm volatile("ld.relaxed.gpu.global.u32 %0, [%1];" : "=r"(k[m]) : "l"(hm->gkey + m * 32 + lane) : "memory");
    if (__all_sync(0xffffffffu, k[0] != 0u && k[1] != 0u && k[2] != 0u && k[3] != 0u && (k[4] != 0u || lane >= 4))) break;
  }
  uint32_t sz = 0u, g = 0u, rank = 0u, w[5];
  #pragma unroll
  for (int m = 0; m < 5; m++) w[m] = k[m] == 0u ? 0u : (k[m] & 511u) < me ? 257u : (k[m] & 511u) == me ? 65537u : 1u;
  #pragma unroll 1
  for (int i = 0; i < 16; i++) {
    const uint32_t v = __reduce_max_sync(0xffffffffu, max(max(max(k[0], k[1]), max(k[2], k[3])), k[4])), lo = (i == 15 || v < 4096u) ? 0u : v - 4096u;
    uint32_t n = 0u;
    #pragma unroll
    for (int m = 0; m < 5; m++) { const bool in = k[m] >= lo; n += in ? w[m] : 0u; w[m] = in ? 0u : w[m]; k[m] = in ? 0u : k[m]; }
    n = __reduce_add_sync(0xffffffffu, n);
    if (lane == i) sz = n & 255u;
    if (n >> 16) { g = i; rank = (n >> 8) & 255u; }
  }
  #pragma unroll 1
  for (int d = 0; d < 4; d += DROPN)
    if ((__reduce_max_sync(0xffffffffu, sz * 32u + lane) & 31u) == (uint32_t)lane) sz -= DROPN;
  const uint32_t gs = __shfl_sync(0xffffffffu, sz, g);
  const uint32_t off = __reduce_add_sync(0xffffffffu, (sz != 16u) * 32u + lane < (gs != 16u) * 32u + g ? sz : 0u);
  return rank < gs ? off + rank : 128u;
}

__device__ __forceinline__ void mod_rest(Scratch* hm, uint32_t sbase, uint32_t bar, int t2, int j, const bf16* __restrict__ cvec, const CUtensorMap* tm, const bf16* __restrict__ w_r) {
  const uint32_t scr = sbase + 4 * 32768 + 8192;
  const uint2 c4 = *reinterpret_cast<const uint2*>(cvec + t2 * 4);
  sts_u32x2(scr + t2 * 8, silu2(c4.x), silu2(c4.y));
  const int kind = j >> 1;
  float dot = 0.f;
  #pragma unroll 1
  for (int b = -3; b < 8; b++) {
    const int c0 = b < 0 ? (j & 1) * T_D + (b + 4) * 256 + (kind ^ 2) * 64 : 2 * T_D + j * 512 + b * 64;
    float v = mod_cols(sbase, scr, bar, (b & 1) ^ 1, t2, tm, c0);
    if (t2 < 64) {
      if (b < 0) st_tagged(hm->mod + c0 + t2, v);
      else {
        const int col = (c0 + t2) & 1023;
        uint8_t* dst = g_col + (col >> 7) * 1536;
        v = rbf(v);
        if (kind == 2) v = rbf(1.0f + v);
        const float vw = v * __bfloat162float(w_r[col]);
        dot += vw;
        if (kind == 2) {
          const int c = col & 127, i = (c & ~15) + ((c >> 1) & 3) * 4 + ((c >> 3) & 1) * 2 + (c & 1);
          reinterpret_cast<bf16*>(dst)[i] = __float2bfloat16_rn(vw);
          reinterpret_cast<bf16*>(dst)[128 + i] = __float2bfloat16_rn(vw - rbf(vw));
        }
        reinterpret_cast<bf16*>(dst + 512 + (kind == 0 ? 0 : kind == 2 ? 256 : kind == 1 ? 512 : 768))[col & 127] = __float2bfloat16_rn(v);
      }
    }
  }
  #pragma unroll
  for (int o = 16; o > 0; o >>= 1) dot += __shfl_xor_sync(0xffffffffu, dot, o);
  if (t2 == 32) sts_f32(scr + 4096, dot);
  fence_proxy_async();
  named_bar_sync(5, 256);
  if (t2 == 0 && (kind == 1 || kind == 2)) g_scal[(kind == 2 ? 0 : 2) + (j & 1)] = dot + lds_f32(scr + 4096);
}

constexpr int AT_NBLK = T_SEQ / 128;
constexpr float AT_HEAD = 7.0f;
constexpr int WO_LATE = 12;
#define QSTG 3
constexpr int QP_STAG = QSTG;
constexpr int AT_SPLIT = 28, AT_PIN = 8, PINB = 4;
constexpr int AT_NFULL = 124;
constexpr int AT_PREG = 40, AT_CREG = 232;
constexpr uint32_t AT_SQ = 5 * 32768;
constexpr float AT_C = 0.08838834764831845f * 1.4426950408889634f;
constexpr float AT_RAW_LO = -16.0f, AT_RAW_HI = 24.0f;
constexpr float AT_RAW_SUM = 281474976710656.0f, AT_RAW_MIN = 9.094947017729282e-13f;
constexpr uint32_t AT_SBAR = AT_SQ + 65536 + 256;
constexpr uint32_t AT_SMEM = AT_SQ + 65536 + 3072;

__device__ __forceinline__ uint32_t ring_slot(uint32_t t) { return t - 5u * ((t * 205u) >> 10); }
__device__ __forceinline__ uint32_t qp_pos(uint32_t j, uint32_t it) { return 4u * it + (j & 3u) + ((j & 3u) == 3u ? it : 0u); }
__device__ __forceinline__ uint32_t ring_par(uint32_t t) { return ((t * 205u) >> 10) & 1u; }
__device__ __forceinline__ void softmax_rowmax(const float (&s)[64], float& mx0, float& mx1) {
  float a0 = fmaxf(s[0], s[1]), a1 = fmaxf(s[4], s[5]), a2 = fmaxf(s[8], s[9]), a3 = fmaxf(s[12], s[13]);
  float b0 = fmaxf(s[2], s[3]), b1 = fmaxf(s[6], s[7]), b2 = fmaxf(s[10], s[11]), b3 = fmaxf(s[14], s[15]);
  #pragma unroll
  for (int j = 4; j < 16; j += 4) {
    a0 = fmaxf(a0, fmaxf(s[4 * j + 0], s[4 * j + 1]));  b0 = fmaxf(b0, fmaxf(s[4 * j + 2], s[4 * j + 3]));
    a1 = fmaxf(a1, fmaxf(s[4 * j + 4], s[4 * j + 5]));  b1 = fmaxf(b1, fmaxf(s[4 * j + 6], s[4 * j + 7]));
    a2 = fmaxf(a2, fmaxf(s[4 * j + 8], s[4 * j + 9]));  b2 = fmaxf(b2, fmaxf(s[4 * j + 10], s[4 * j + 11]));
    a3 = fmaxf(a3, fmaxf(s[4 * j + 12], s[4 * j + 13])); b3 = fmaxf(b3, fmaxf(s[4 * j + 14], s[4 * j + 15]));
  }
  mx0 = fmaxf(fmaxf(a0, a1), fmaxf(a2, a3));
  mx1 = fmaxf(fmaxf(b0, b1), fmaxf(b2, b3));
  mx0 = fmaxf(mx0, __shfl_xor_sync(0xffffffffu, mx0, 1));
  mx1 = fmaxf(mx1, __shfl_xor_sync(0xffffffffu, mx1, 1));
  mx0 = fmaxf(mx0, __shfl_xor_sync(0xffffffffu, mx0, 2));
  mx1 = fmaxf(mx1, __shfl_xor_sync(0xffffffffu, mx1, 2));
}
__device__ __forceinline__ void softmax_sub(float (&s)[64], float mc0, float mc1) {
  #pragma unroll
  for (int j = 0; j < 16; j++) { s[4 * j] -= mc0; s[4 * j + 1] -= mc0; s[4 * j + 2] -= mc1; s[4 * j + 3] -= mc1; }
}
template <int LO, int HI>
__device__ __forceinline__ void softmax_exp(float (&s)[64]) {
  #pragma unroll
  for (int i = LO; i < HI; i++) s[i] = ex2_approx(s[i]);
}
__device__ __forceinline__ bool softmax_mode(const float (&s)[64], float& mc0, float& mc1) {
  softmax_rowmax(s, mc0, mc1);
  const bool raw = __all_sync(0xffffffffu, mc0 >= AT_RAW_LO && mc0 <= AT_RAW_HI && mc1 >= AT_RAW_LO && mc1 <= AT_RAW_HI);
  mc0 += AT_HEAD; mc1 += AT_HEAD;
  return raw;
}
__device__ __forceinline__ void rowsum_p(const uint32_t (&p)[32], uint32_t& t0, uint32_t& t1) {
  uint32_t a[16];
  #pragma unroll
  for (int i = 0; i < 8; i++) { a[2 * i] = badd2(p[4 * i], p[4 * i + 2]); a[2 * i + 1] = badd2(p[4 * i + 1], p[4 * i + 3]); }
  #pragma unroll
  for (int i = 0; i < 4; i++) { a[2 * i] = badd2(a[4 * i], a[4 * i + 2]); a[2 * i + 1] = badd2(a[4 * i + 1], a[4 * i + 3]); }
  t0 = badd2(badd2(a[0], a[2]), badd2(a[4], a[6]));
  t1 = badd2(badd2(a[1], a[3]), badd2(a[5], a[7]));
}
__device__ __forceinline__ void add_rowsum(const uint32_t (&p)[32], float& l0, float& l1) {
  uint32_t t0, t1;
  rowsum_p(p, t0, t1);
  l0 += bflo(t0) + bfhi(t0); l1 += bflo(t1) + bfhi(t1);
}
__device__ __forceinline__ void pack_p(uint32_t (&p)[32], const float (&s)[64]) {
  #pragma unroll
  for (int i = 0; i < 32; i++) p[i] = pack_bf16(s[2 * i], s[2 * i + 1]);
}
__device__ __noinline__ void attn_rows_exact(uint32_t sq, int warp, int lane, const bf16* __restrict__ kh, const bf16* __restrict__ vh) {
  #pragma unroll 1
  for (int r = 16 * warp; r < 16 * warp + 16; r++) {
    const uint32_t ad = (lane >> 4) * 16384 + r * 128 + ((((lane & 15) >> 1) ^ (r & 7)) << 4) + (lane & 1) * 8;
    uint2 qv; asm volatile("ld.shared.v2.u32 {%0, %1}, [%2];" : "=r"(qv.x), "=r"(qv.y) : "r"(sq + ad) : "memory");
    const float q0 = bflo(qv.x), q1 = bfhi(qv.x), q2 = bflo(qv.y), q3 = bfhi(qv.y);
    float m = -INFINITY, l = 0.f, o0 = 0.f, o1 = 0.f, o2 = 0.f, o3 = 0.f;
    #pragma unroll 1
    for (int key = 0; key < T_SEQ; key++) {
      const uint2 kv = *reinterpret_cast<const uint2*>(kh + (size_t)key * T_DH + lane * 4);
      const uint2 vv = *reinterpret_cast<const uint2*>(vh + (size_t)key * T_DH + lane * 4);
      float sc = (q0 * bflo(kv.x) + q1 * bfhi(kv.x)) + (q2 * bflo(kv.y) + q3 * bfhi(kv.y));
      #pragma unroll
      for (int o = 16; o > 0; o >>= 1) sc += __shfl_xor_sync(0xffffffffu, sc, o);
      const float mn = fmaxf(m, sc);
      const float al = (m == mn) ? 1.0f : ex2_approx(m - mn), p = rbf(ex2_approx(sc - mn));
      m = mn;
      l = fmaf(l, al, p);
      o0 = fmaf(o0, al, p * bflo(vv.x)); o1 = fmaf(o1, al, p * bfhi(vv.x));
      o2 = fmaf(o2, al, p * bflo(vv.y)); o3 = fmaf(o3, al, p * bfhi(vv.y));
    }
    const float inv = rcp_approx(l);
    asm volatile("st.shared.v2.u32 [%0], {%1, %2};" :: "r"(sq + ad), "r"(pack_bf16(o0 * inv, o1 * inv)), "r"(pack_bf16(o2 * inv, o3 * inv)) : "memory");
  }
}
__device__ __forceinline__ void issue_qk(float (&s)[64], const uint32_t (&q)[32], uint32_t k_lo) {
  wgmma_fence();
  wgmma_m64n128k16_rs<0>(s, q[0], q[1], q[2], q[3], k_lo, 0);
  wgmma_m64n128k16_rs<2>(s, q[4], q[5], q[6], q[7], k_lo, 1);
  wgmma_m64n128k16_rs<4>(s, q[8], q[9], q[10], q[11], k_lo, 1);
  wgmma_m64n128k16_rs<6>(s, q[12], q[13], q[14], q[15], k_lo, 1);
  wgmma_m64n128k16_rs<1024>(s, q[16], q[17], q[18], q[19], k_lo, 1);
  wgmma_m64n128k16_rs<1026>(s, q[20], q[21], q[22], q[23], k_lo, 1);
  wgmma_m64n128k16_rs<1028>(s, q[24], q[25], q[26], q[27], k_lo, 1);
  wgmma_m64n128k16_rs<1030>(s, q[28], q[29], q[30], q[31], k_lo, 1);
  wgmma_commit();
}
__device__ __forceinline__ void issue_pv(float (&o)[64], const uint32_t (&p)[32], uint32_t v_lo, int accumulate) {
  wgmma_fence();
  wgmma_m64n128k16_rs_tb<0>(o, p[0], p[1], p[2], p[3], v_lo, accumulate);
  wgmma_m64n128k16_rs_tb<128>(o, p[4], p[5], p[6], p[7], v_lo, 1);
  wgmma_m64n128k16_rs_tb<256>(o, p[8], p[9], p[10], p[11], v_lo, 1);
  wgmma_m64n128k16_rs_tb<384>(o, p[12], p[13], p[14], p[15], v_lo, 1);
  wgmma_m64n128k16_rs_tb<512>(o, p[16], p[17], p[18], p[19], v_lo, 1);
  wgmma_m64n128k16_rs_tb<640>(o, p[20], p[21], p[22], p[23], v_lo, 1);
  wgmma_m64n128k16_rs_tb<768>(o, p[24], p[25], p[26], p[27], v_lo, 1);
  wgmma_m64n128k16_rs_tb<896>(o, p[28], p[29], p[30], p[31], v_lo, 1);
  wgmma_commit();
}
__device__ __forceinline__ void rescale_o(float (&o)[64], float al0, float al1) {
  #pragma unroll
  for (int j = 0; j < 16; j++) { o[4 * j] *= al0; o[4 * j + 1] *= al0; o[4 * j + 2] *= al1; o[4 * j + 3] *= al1; }
}

__device__ __forceinline__ void stage_o(const float (&o)[64], float i0, float i1, uint32_t dst, int lane) {
  #pragma unroll
  for (int J = 0; J < 16; J += 2)
    stmatrix_x4(dst + (J >> 3) * 16384 + ((((J & 7) + (lane >> 4)) ^ (lane & 7)) << 4),
                pack_bf16(o[4 * J + 0] * i0, o[4 * J + 1] * i0), pack_bf16(o[4 * J + 2] * i1, o[4 * J + 3] * i1),
                pack_bf16(o[4 * J + 4] * i0, o[4 * J + 5] * i0), pack_bf16(o[4 * J + 6] * i1, o[4 * J + 7] * i1));
}
__device__ __forceinline__ bool finish_l(float& l0, float& l1) {
  l0 += __shfl_xor_sync(0xffffffffu, l0, 1); l1 += __shfl_xor_sync(0xffffffffu, l1, 1);
  l0 += __shfl_xor_sync(0xffffffffu, l0, 2); l1 += __shfl_xor_sync(0xffffffffu, l1, 2);
  const bool redo = __any_sync(0xffffffffu, !(l0 <= AT_RAW_SUM && l1 <= AT_RAW_SUM && l0 >= AT_RAW_MIN && l1 >= AT_RAW_MIN));
  l0 = rcp_approx(l0); l1 = rcp_approx(l1);
  return redo;
}
__device__ __forceinline__ void stage_qregs(const uint32_t (&q)[32], uint32_t dst, int lane) {
  #pragma unroll
  for (int J = 0; J < 16; J += 2)
    stmatrix_x4(dst + (J >> 3) * 16384 + ((((J & 7) + (lane >> 4)) ^ (lane & 7)) << 4), q[2 * J], q[2 * J + 1], q[2 * J + 2], q[2 * J + 3]);
}
__device__ __forceinline__ void store_o(const CUtensorMap* tmO, uint32_t src, int head, int row) {
  tma_store_2d(tmO, src, head * T_DH, row);
  tma_store_2d(tmO, src + 16384, head * T_DH + 64, row);
  bulk_commit();
}
struct GemvSel { uint32_t lo0, hi0, lo1, hi1; };
__device__ __forceinline__ GemvSel gemv_sel(int lane) {
  const uint32_t lo = (lane & 8) ? 0x1044u : 0x4410u, hi = (lane & 8) ? 0x3244u : 0x4432u;
  GemvSel s; s.lo0 = (lane & 16) ? 0x4444u : lo; s.hi0 = (lane & 16) ? 0x4444u : hi; s.lo1 = (lane & 16) ? lo : 0x4444u; s.hi1 = (lane & 16) ? hi : 0x4444u;
  return s;
}
#define GEMV_B0(j, h, s) __byte_perm((j) < 2 ? (h).x : (h).y, 0u, ((j) & 1) ? (s).hi0 : (s).lo0)
#define GEMV_B1(j, h, s) __byte_perm((j) < 2 ? (h).x : (h).y, 0u, ((j) & 1) ? (s).hi1 : (s).lo1)
__device__ __forceinline__ float4 gemv_out(const float (&d)[4], int lane) {
  const bool tk = lane & 1;
  const float r0 = __shfl_xor_sync(0xffffffffu, tk ? d[0] : d[1], 1), r1 = __shfl_xor_sync(0xffffffffu, tk ? d[2] : d[3], 1);
  return tk ? make_float4(r0, d[1], r1, d[3]) : make_float4(d[0], r0, d[2], r1);
}
#define OG_NG 8
#define OG_GRP (64 / OG_NG)
constexpr int OG_ST = 5, OG_NKB = T_DQKV / 64, OG_MOE = T_F / 32;
constexpr int OG_POS = 8;
constexpr uint32_t OG_STAGE = 32768;
constexpr uint32_t OG_SWD = AT_SQ;
constexpr uint32_t OG_SCOL = AT_SBAR + 512;
constexpr uint32_t OG_SMISC = AT_SBAR + 2048;
constexpr uint32_t OG_XSLOT = ((OG_POS + OG_NKB) % OG_ST) * OG_STAGE;
constexpr uint32_t OG_OSLOT = ((OG_POS + OG_NKB + 1) % OG_ST) * OG_STAGE;
constexpr uint32_t OG_SH2 = ((OG_POS + OG_NKB + 2) % OG_ST) * OG_STAGE;
constexpr uint32_t OG_SRED = ((OG_POS + OG_NKB + 3) % OG_ST) * OG_STAGE;
constexpr uint32_t OG_SSTAT = OG_SRED + 16384;
constexpr uint32_t OG_SGU = OG_SRED + 8192;
constexpr uint32_t OG_SFIN = OG_SGU + 256;
#define OGM 2
#define OG_MT(b) ((((b) >> OGM) & 15) ^ (SERP && ((b) & 64) ? 15 : 0))
#define OG_NT(b) (((b) & ((1 << OGM) - 1)) + (((b) >> (4 + OGM)) << OGM))
#define TAIL_SETUP \
  const uint32_t bar_full = sbase + AT_SBAR, bar_empty = bar_full + 40; \
  const uint32_t bar_wd = bar_full + 168, bar_col = bar_full + 176, bar_out = bar_full + 184, bar_end = bar_full + 192; \
  const uint32_t bar_key = bar_full + 200, bar_h2 = bar_full + 208, bar_sel = bar_full + 216; \
  const int mt = OG_MT(bx), nt = OG_NT(bx); \
  const int m0 = mt * 128, n0 = nt * 128; \
  const bool has_moe = (int)bx < OG_MOE; \
  (void)bar_empty; (void)bar_wd; (void)bar_col; (void)bar_out; (void)bar_end; (void)bar_key; (void)bar_h2; (void)bar_sel; (void)m0; (void)n0; (void)has_moe;

__device__ __forceinline__ void tail_producer(Scratch* hm, uint32_t bx, uint32_t sbase, uint32_t ph, uint32_t obpar, uint64_t pol, const CUtensorMap* tmA, const CUtensorMap* tmB,
                                              const CUtensorMap* tmX, const bf16* __restrict__ w_down) {
  TAIL_SETUP
  const uint32_t b_q0 = bar_full + 80, b_ob = bar_full + 96, b_acq = bar_full + 264;
  uint32_t stage = OG_POS % OG_ST;
  if (has_moe) mbar_expect_tx(bar_wd, 65536);
  mbar_expect_tx(bar_col, 1536 + 16);
  #pragma unroll 1
  for (int kb = 0; kb <= OG_NKB; kb++) {
    const uint32_t fb = bar_full + 8 * stage, sa = sbase + stage * OG_STAGE, sb = sa + 16384;
    mbar_wait(bar_empty + 8 * stage, ph);
    mbar_expect_tx(fb, OG_STAGE);
    if (kb < OG_NKB) {
      tma_load_2d_hint(sb, tmB, n0, kb * 64, fb, pol);
      tma_load_2d_hint(sb + 8192, tmB, n0 + 64, kb * 64, fb, pol);
      if ((kb & 31) == 0) { mbar_wait(b_acq, kb >> 5); fence_proxy_async_global(); }
      tma_load_2d_hint(sa, tmA, kb * 64, m0, fb, pol);
    } else {
      tma_load_2d_hint(sa, tmX, n0, m0, fb, pol);
      tma_load_2d_hint(sb, tmX, n0 + 64, m0, fb, pol);
    }
    if (kb == 32) {
      bulk_load_hint(sbase + OG_SCOL, g_col + nt * 1536, 1536, bar_col, pol);
      bulk_load_hint(sbase + OG_SMISC, g_scal, 16, bar_col, pol);
    }
    if (kb == 6) { mbar_wait(b_q0, obpar); mbar_wait(b_ob, obpar); }
    if (has_moe && (kb & 7) == 6 && kb < 64)
      bulk_load_hint(sbase + OG_SWD + (kb >> 3) * 8224, (const uint8_t*)w_down + (size_t)bx * 65536 + (kb >> 3) * 8192, 8192, bar_wd, pol);
    if (++stage == OG_ST) { stage = 0; ph ^= 1; }
  }
}

__device__ __forceinline__ uint32_t out2(uint32_t x1, uint32_t mb2, uint32_t ih, uint32_t il, uint32_t c1, uint32_t sb, uint32_t gb) {
  const uint32_t d = bsub2(x1, mb2);
  const uint32_t h2 = badd2(bmul2(bfma2(d, ih, bmul2(d, il)), c1), sb);
  return badd2(x1, bmul2(gb, bfma2(h2, 0u, h2)));
}
__device__ __forceinline__ void tail_exchange(Scratch* hm, uint32_t bx, uint32_t sbase, uint32_t tx, const CUtensorMap* tmOut, bf16* __restrict__ out) {
    TAIL_SETUP
    mbar_wait(bar_end, 0);
    const int lane = tx & 31;
    TL_MARK2(22, lane == 0);
    if (tx == 96) PF(5);
    if (tx < 32) {
      uint32_t k1 = 0u, k2 = 0u;
      #pragma unroll 1
      for (unsigned int spin = 0; spin < (1u << 22) && k1 == 0u; spin++) asm volatile("ld.relaxed.gpu.global.u32 %0, [%1];" : "=r"(k1) : "l"(g_key + lane) : "memory");
      __syncwarp();
      TL_MARK2(28, lane == 0);
      warp_top2(k1, k2);
      if (lane == 0) {
        const uint32_t r1 = 0xffffu - (k1 & 0xffffu), r2 = 0xffffu - (k2 & 0xffffu);
        sts_u32x4(sbase + OG_SMISC + 64, r1, r2, (r1 >> 7) * 2, (r2 >> 7) * 2 + ((r1 >> 7) == (r2 >> 7)));
        sts_u32x2(sbase + OG_SMISC + 192, k1, k2);
        mbar_arrive(bar_sel);
      }
    } else if (tx < 96) {
          mbar_wait(bar_key, 0);
          const uint4 kk = lds_u32x4(sbase + OG_SSTAT + 1024 + lane * 16);
          uint32_t k1 = max(kk.x, kk.y), k2 = min(kk.x, kk.y);
          k2 = max(max(k2, min(kk.z, kk.w)), min(k1, max(kk.z, kk.w))); k1 = max(k1, max(kk.z, kk.w));
          warp_top2(k1, k2);
          if (tx < 64) {
            if (lane == 0 && nt == (mt & 7)) st_relaxed2(g_key + mt * 2, k1, k2);
            TL_MARK2(27, lane == 0);
          } else {
            const uint32_t r = (~((lane & 16) ? k2 : k1)) & 127u, ch = lane & 15;
            const uint2 st = lds_u32x2(sbase + OG_SSTAT + r * 8);
            const uint4 xc = lds_u32x4(sbase + OG_XSLOT + (ch >> 3) * 16384 + r * 128 + (((ch ^ r) & 7) << 4));
            const uint4 c1 = lds_u32x4(sbase + OG_SCOL + 768 + ch * 16), sh = lds_u32x4(sbase + OG_SCOL + 1024 + ch * 16);
            const float inr = __uint_as_float(st.y);
            float* dst = reinterpret_cast<float*>(g_cand + (mt * 2 + (lane >> 4)) * 256 + nt * 16 + ch);
            st_tagged4(dst + 512, __uint_as_float(ln_mod2(xc.x, st.x, inr, c1.x, sh.x)), __uint_as_float(ln_mod2(xc.y, st.x, inr, c1.y, sh.y)),
                       __uint_as_float(ln_mod2(xc.z, st.x, inr, c1.z, sh.z)), __uint_as_float(ln_mod2(xc.w, st.x, inr, c1.w, sh.w)));
            st_tagged4(dst, __uint_as_float(xc.x), __uint_as_float(xc.y), __uint_as_float(xc.z), __uint_as_float(xc.w));
          }
    }
    mbar_wait(bar_sel, 0);
    const int sel0 = (int)lds_u32(sbase + OG_SMISC + 64), sel1 = (int)lds_u32(sbase + OG_SMISC + 68);
    mbar_wait(bar_out, 0);
    if ((sel0 >> 7) == mt || (sel1 >> 7) == mt) {
      #pragma unroll 2
      for (int i = 0; i < 16; i++) {
        const int r = i * 8 + (tx >> 4), ch = tx & 15;
        if (m0 + r != sel0 && m0 + r != sel1)
          *reinterpret_cast<uint4*>(out + (size_t)(m0 + r) * T_D + n0 + ch * 8) =
              lds_u32x4(sbase + OG_OSLOT + (ch >> 3) * 16384 + r * 128 + (((ch & 7) ^ (r & 7)) << 4));
      }
    } else if (tx == 0) {
      tma_store_2d(tmOut, sbase + OG_OSLOT, n0, m0);
      tma_store_2d(tmOut, sbase + OG_OSLOT + 16384, n0 + 64, m0);
      bulk_commit();
    }
    if (bx == 0 && tx < 68) g_hcnt[32 * (tx >> 2) + (tx & 3)] = 0u;
    if (tx < 64) hm->modu[bx * 64 + tx] = 0.f;
    else if (tx < 96) hm->stat[bx * 32 + tx - 64] = make_float2(0.f, 0.f);
    else if (tx < 112) hm->mod[bx * 16 + tx - 96] = 0.f;
    else if (tx < 114 && bx < 66) hm->gkey[bx * 2 + tx - 112] = 0u;
    {
      const int tk = bx >> 6, c0 = (bx & 63) * 16;
      const uint32_t gb2 = *reinterpret_cast<const uint32_t*>(g_col + (c0 >> 7) * 1536 + 512 + 768 + ((c0 & 127) + (tx & 14)) * 2);
      const uint32_t* xp = reinterpret_cast<const uint32_t*>(g_cand + lds_u32(sbase + OG_SMISC + 72 + tk * 4) * 256) + ((c0 + (tx & 14)) >> 1);
      uint32_t x2 = 0u;
      #pragma unroll 1
      for (unsigned int spin = 0; spin < (1u << 20) && x2 == 0u; spin++) asm volatile("ld.relaxed.gpu.global.u32 %0, [%1];" : "=r"(x2) : "l"(xp) : "memory");
      const float* src = g_ypart + (size_t)((tx >> 2) * 2 + tk) * T_D + c0 + (tx & 3) * 4;
      const bool four = tx < (OG_MOE - 96) * 4;
      mbar_wait(bar_h2, 0);
      if (tx == 0) hint_wait(CNT_Y, (uint32_t)OG_MOE);
      named_bar_sync(10, 128);
      float4 p0, p1, p2, p3;
      #pragma unroll 1
      for (unsigned int spin = 0; spin < (1u << 20); spin++) {
        p0 = ld_tagged4(src); p1 = ld_tagged4(src + 64 * T_D); p2 = ld_tagged4(src + 128 * T_D); p3 = ld_tagged4(four ? src + 192 * T_D : src);
        if (tagged4(p0) && tagged4(p1) && tagged4(p2) && tagged4(p3)) break;
      }
      if (four) { p2.x += p3.x; p2.y += p3.y; p2.z += p3.z; p2.w += p3.w; }
      p0.x = (p0.x + p1.x) + p2.x; p0.y = (p0.y + p1.y) + p2.y; p0.z = (p0.z + p1.z) + p2.z; p0.w = (p0.w + p1.w) + p2.w;
      #pragma unroll
      for (int o = 4; o <= 16; o <<= 1) {
        p0.x += __shfl_xor_sync(0xffffffffu, p0.x, o); p0.y += __shfl_xor_sync(0xffffffffu, p0.y, o);
        p0.z += __shfl_xor_sync(0xffffffffu, p0.z, o); p0.w += __shfl_xor_sync(0xffffffffu, p0.w, o);
      }
      if (lane < 4) sts_f32x4(sbase + OG_SFIN + (tx >> 5) * 64 + lane * 16, p0.x, p0.y, p0.z, p0.w);
      named_bar_sync(10, 128);
      TL_MARK2(21, tx == 0);
      if (tx < 16) {
        const uint32_t ya = sbase + OG_SFIN + tx * 4, key = lds_u32(sbase + OG_SMISC + 192 + tk * 4);
        float y = (lds_f32(ya) + lds_f32(ya + 64)) + (lds_f32(ya + 128) + lds_f32(ya + 192));
        const float r = bfhi((key & 0x80000000u) ? key ^ 0x80000000u : ~key);
        const float rs = rbf(sigmoid_f(r));
        const uint32_t h2p = lds_u32(sbase + OG_SH2 + tk * 2048 + (c0 + (tx & 14)) * 2);
        const float fh = (lane & 1) ? bfhi(h2p) : bflo(h2p);
        y = rbf(y);
        y = rbf(y * rs);
        const float upd = rbf(rbf(fh * 0.0f) + y);
        out[(size_t)(tk ? sel1 : sel0) * T_D + c0 + tx] =
            __float2bfloat16_rn(((lane & 1) ? bfhi(x2) : bflo(x2)) + rbf(((lane & 1) ? bfhi(gb2) : bflo(gb2)) * rbf(fh + upd)));
      }
      if (tx == 0) bulk_wait_read<0>();
    }
    TL_END(4, tx == 0);
    PS(6, tx == 0);
}

__device__ __forceinline__ void tail_consumer(Scratch* hm, uint32_t bx, uint32_t sbase, int t2, int cwg, const bf16* __restrict__ w_gate, const bf16* __restrict__ w_up) {
    TAIL_SETUP
    const int tid = threadIdx.x & 127;
    const int warp = tid >> 5, lane = tid & 31, w8 = t2 >> 5;
    const uint32_t dbase = (sbase & 0x3FFFFu) >> 4;
    const uint32_t a_base = dbase + ((cwg * 8192) >> 4) + (1u << 16);
    const uint32_t b_base = dbase + (16384 >> 4) + (512u << 16);
    TL_MARK2(25, threadIdx.x == 128);
    const uint64_t pol = policy_evict_first();
    const bf16* pw = ((lane & 16) ? w_up : w_gate) + (size_t)(w8 * 128 + (lane & 3) * 4) * T_F + (has_moe ? bx : 0) * 32 + ((lane >> 2) & 3) * 8;
    uint4 wv[32];
    float acc[64];
    {
      uint32_t stage = OG_POS % OG_ST, phase = (OG_POS / OG_ST) & 1, prev = 0;
      #pragma unroll
      for (int g = 0; g < OG_NG; g++) {
        #pragma unroll
        for (int j = 0; j < 4; j++) wv[4 * g + j] = ldg_stream_v4(pw + (size_t)(16 * g + j) * T_F, pol);
        #pragma unroll 1
        for (int kb = g * OG_GRP; kb < (g == OG_NG - 1 ? OG_NKB : (g + 1) * OG_GRP); kb++) {
          mbar_wait(bar_full + 8 * stage, phase);
          const uint32_t a_lo = a_base + stage * (OG_STAGE >> 4), b_lo = b_base + stage * (OG_STAGE >> 4);
          wgmma_fence();
          wgmma_m64n128k16_ss_tb<0, 0>(acc, a_lo, b_lo, kb != 0);
          wgmma_m64n128k16_ss_tb<2, 128>(acc, a_lo, b_lo, 1);
          wgmma_m64n128k16_ss_tb<4, 256>(acc, a_lo, b_lo, 1);
          wgmma_m64n128k16_ss_tb<6, 384>(acc, a_lo, b_lo, 1);
          wgmma_commit();
          wgmma_wait<1>();
          if (kb > 0 && tid == 0) mbar_arrive(bar_empty + 8 * prev);
          prev = stage;
          if (++stage == OG_ST) { stage = 0; phase ^= 1; }
        }
      }
    }
    mbar_wait(bar_col, 0);
    mbar_wait(bar_full + 8 * ((OG_POS + OG_NKB) % OG_ST), ((OG_POS + OG_NKB) / OG_ST) & 1);
    wgmma_wait<0>();
    fence_regs(acc);
    if (tid == 0) mbar_arrive(bar_end);
    TL_MARK2(9, lane == 0);
    PS(5, threadIdx.x == 256);
    const int q2 = 2 * (lane & 3);
    const uint32_t frag = (64 * cwg + 16 * warp + (lane & 7) + 8 * ((lane >> 3) & 1)) * 128;
    const int fsw = lane & 7, fhi = lane >> 4;
    {
      float dl[4] = {0.f, 0.f, 0.f, 0.f}, da[4] = {0.f, 0.f, 0.f, 0.f}, db[4] = {0.f, 0.f, 0.f, 0.f};
      const uint32_t tb = sbase + OG_SCOL + (lane & 8) * 32 + (lane & 3) * 8, g = lane >> 2;
      const uint32_t msk = (g == 1 || g == 2) ? 0xffffffffu : 0u, one = g == 0 ? 0x3F803F80u : 0u;
      #pragma unroll
      for (int J = 0; J < 16; J += 2) {
        const uint32_t ad = sbase + OG_XSLOT + (J >> 3) * 16384 + frag + ((((J & 7) + fhi) ^ fsw) << 4);
        uint32_t xr[4];
        ldmatrix_x4(ad, xr[0], xr[1], xr[2], xr[3]);
        const uint2 cw = lds_u32x2(tb + J * 16);
        #pragma unroll
        for (int h = 0; h < 2; h++) {
          const uint32_t ga = lds_u32(sbase + OG_SCOL + 512 + (8 * (J + h) + q2) * 2);
          xr[2 * h] = badd2(xr[2 * h], bmul2(ga, pack_bf16(acc[4 * (J + h)], acc[4 * (J + h) + 1])));
          xr[2 * h + 1] = badd2(xr[2 * h + 1], bmul2(ga, pack_bf16(acc[4 * (J + h) + 2], acc[4 * (J + h) + 3])));
        }
        stmatrix_x4(ad, xr[0], xr[1], xr[2], xr[3]);
        mma_bf16(dl, xr[0], xr[1], xr[2], xr[3], (cw.x & msk) | one, (cw.y & msk) | one);
        mma_bf16(da, xr[0], xr[1], xr[2], xr[3], xr[0], xr[2]);
        mma_bf16(db, xr[0], xr[1], xr[2], xr[3], xr[1], xr[3]);
      }
      {
        const int dsrc = (lane & ~3) + (g >> 1);
        const float qa = __shfl_sync(0xffffffffu, (g & 1) ? da[1] : da[0], dsrc), qb = __shfl_sync(0xffffffffu, (g & 1) ? db[3] : db[2], dsrc);
        const float e0 = __shfl_xor_sync(0xffffffffu, (lane & 1) ? dl[0] : dl[2], 1), e1 = __shfl_xor_sync(0xffffffffu, dl[3], 1);
        if ((lane & 3) < 2) {
          const bool hi = lane & 1;
          st_tagged4(reinterpret_cast<float*>(g_part1 + ((mt * 8 + w8) * 8 + nt) * 16 + g + (hi ? 8 : 0)),
                     hi ? e0 : dl[0], hi ? qb : qa, hi ? e1 + dl[2] : dl[1] + e0, 1.0f);
        }
      }
    }
    TL_MARK2(10, lane == 0);
    uint4 wd[16];
    if (has_moe) mbar_wait(bar_wd, 0);
    #pragma unroll
    for (int i = 0; i < 16; i++) wd[i] = lds_u32x4(sbase + OG_SWD + (((i >> 2) & 1) * 4 + (lane & 3)) * 8224 + (i & 3) * 2048 + w8 * 256 + (i >> 3) * 128 + (lane >> 2) * 16);
    {
      const float* src = reinterpret_cast<const float*>(g_part1 + ((mt * 8 + w8) * 8 + (lane & 1) * 4) * 16 + (lane >> 1));
      float4 v, v1, v2, v3;
      #pragma unroll 1
      for (unsigned int spin = 0; spin < (1u << 22); spin++) {
        v = ld_tagged4(src); v1 = ld_tagged4(src + 64); v2 = ld_tagged4(src + 128); v3 = ld_tagged4(src + 192);
        if (tagged4(v) & tagged4(v1) & tagged4(v2) & tagged4(v3)) break;
        __nanosleep(100);
      }
      __syncwarp();
      TL_MARK2(26, lane == 0);
      v.x = (v.x + v1.x) + (v2.x + v3.x); v.y = (v.y + v1.y) + (v2.y + v3.y); v.z = (v.z + v1.z) + (v2.z + v3.z);
      v.x += __shfl_xor_sync(0xffffffffu, v.x, 1); v.y += __shfl_xor_sync(0xffffffffu, v.y, 1); v.z += __shfl_xor_sync(0xffffffffu, v.z, 1);
      const float mean = v.x * (1.0f / T_D);
      const float var = fmaxf(fmaf(-mean, mean, v.y * (1.0f / T_D)), 0.f);
      const uint32_t mb2 = pack_bf16(mean, mean);
      const float inv = rcp_approx(rbf(sqrt_approx(rbf(rbf(var) + 1e-05f))));
      {
        const float2 cwp = lds_f32x2(sbase + OG_SMISC), sbp = lds_f32x2(sbase + OG_SMISC + 8);
        const uint32_t key = rank_key(rbf(fmaf(fmaf(-bflo(mb2), cwp.x + cwp.y, v.z), inv, sbp.x + sbp.y)), m0 + 16 * w8 + (lane >> 1));
        mbar_wait(bar_end, 0);
        if (lane & 1) sts_u32(sbase + OG_SSTAT + 1024 + (16 * w8 + (lane >> 1)) * 4, key);
        else sts_u32x2(sbase + OG_SSTAT + (16 * w8 + (lane >> 1)) * 8, mb2, __float_as_uint(inv));
        __syncwarp();
        if (lane == 0) mbar_arrive(bar_key);
      }
      const uint32_t ih = pack_bf16(inv, inv), il = pack_bf16(inv - bflo(ih), inv - bflo(ih));
      const uint32_t mba = __shfl_sync(0xffffffffu, mb2, 2 * (lane >> 2)), mbb = __shfl_sync(0xffffffffu, mb2, 2 * (lane >> 2) + 16);
      const uint32_t iha = __shfl_sync(0xffffffffu, ih, 2 * (lane >> 2)), ihb = __shfl_sync(0xffffffffu, ih, 2 * (lane >> 2) + 16);
      const uint32_t ila = __shfl_sync(0xffffffffu, il, 2 * (lane >> 2)), ilb = __shfl_sync(0xffffffffu, il, 2 * (lane >> 2) + 16);
      #pragma unroll 2
      for (int J = 0; J < 16; J += 2) {
        const uint32_t off = (J >> 3) * 16384 + frag + ((((J & 7) + fhi) ^ fsw) << 4);
        uint32_t xr[4];
        ldmatrix_x4(sbase + OG_XSLOT + off, xr[0], xr[1], xr[2], xr[3]);
        #pragma unroll
        for (int h = 0; h < 2; h++) {
          const uint32_t ca = sbase + OG_SCOL + 512 + (8 * (J + h) + q2) * 2;
          const uint32_t c1 = lds_u32(ca + 256), sh = lds_u32(ca + 512), gb = lds_u32(ca + 768);
          xr[2 * h] = out2(xr[2 * h], mba, iha, ila, c1, sh, gb);
          xr[2 * h + 1] = out2(xr[2 * h + 1], mbb, ihb, ilb, c1, sh, gb);
        }
        stmatrix_x4(sbase + OG_OSLOT + off, xr[0], xr[1], xr[2], xr[3]);
      }
      fence_proxy_async();
      __syncwarp();
      if (lane == 0) mbar_arrive(bar_out);
      TL_MARK2(24, lane == 0);
    }
    {
      mbar_wait(bar_sel, 0);
      TL_MARK2(12, lane == 0);
      const float* src = reinterpret_cast<const float*>(g_cand + lds_u32(sbase + OG_SMISC + 72 + cwg * 4) * 256 + 128 + tid);
      float4 hf;
      #pragma unroll 1
      for (unsigned int spin = 0; spin < (1u << 20); spin++) { hf = ld_tagged4(src); if (tagged4(hf)) break; }
      const uint4 hv = make_uint4(__float_as_uint(hf.x), __float_as_uint(hf.y), __float_as_uint(hf.z), __float_as_uint(hf.w));
      sts_u32x4(sbase + OG_SH2 + t2 * 16, hv.x, hv.y, hv.z, hv.w);
    }
    named_bar_sync(9, 256);
    if (t2 == 0) mbar_arrive(bar_h2);
    TL_MARK2(13, lane == 0);
    if (has_moe) {
      const GemvSel sel = gemv_sel(lane);
      {
        float d[4][4];
        #pragma unroll
        for (int c = 0; c < 4; c++) { d[c][0] = 0.f; d[c][1] = 0.f; d[c][2] = 0.f; d[c][3] = 0.f; }
        #pragma unroll
        for (int st = 0; st < 8; st++) {
          const uint2 hb = lds_u32x2(sbase + OG_SH2 + ((lane >> 2) & 1) * 2048 + (w8 * 128 + st * 16 + (lane & 3) * 4) * 2);
          #pragma unroll
          for (int j = 0; j < 4; j++) mma_bf16(d[j], wv[4 * st + j].x, wv[4 * st + j].y, wv[4 * st + j].z, wv[4 * st + j].w, GEMV_B0(j, hb, sel), GEMV_B1(j, hb, sel));
        }
        #pragma unroll
        for (int e = 0; e < 4; e++) d[0][e] = (d[0][e] + d[1][e]) + (d[2][e] + d[3][e]);
        const float4 r = gemv_out(d[0], lane);
        sts_f32x4(sbase + OG_SRED + w8 * 512 + (((lane >> 4) * 2 + (lane & 1)) * 32 + ((lane >> 2) & 3) * 8 + (lane & 2) * 2) * 4, r.x, r.y, r.z, r.w);
      }
      named_bar_sync(9, 256);
      if (t2 < 64) {
        float gp[8], up[8];
        #pragma unroll
        for (int w = 0; w < 8; w++) { gp[w] = lds_f32(sbase + OG_SRED + w * 512 + t2 * 4); up[w] = lds_f32(sbase + OG_SRED + w * 512 + 256 + t2 * 4); }
        const float gs = ((gp[0] + gp[1]) + (gp[2] + gp[3])) + ((gp[4] + gp[5]) + (gp[6] + gp[7]));
        const float us = ((up[0] + up[1]) + (up[2] + up[3])) + ((up[4] + up[5]) + (up[6] + up[7]));
        asm volatile("st.shared.u16 [%0], %1;" :: "r"(sbase + OG_SGU + t2 * 2), "h"((uint16_t)pack_bf16(silu_bf(rbf(gs)) * rbf(us), 0.f)) : "memory");
      }
      named_bar_sync(9, 256);
      TL_MARK2(20, threadIdx.x == 128);
      float d[4][4];
      #pragma unroll
      for (int c = 0; c < 4; c++) { d[c][0] = 0.f; d[c][1] = 0.f; d[c][2] = 0.f; d[c][3] = 0.f; }
      #pragma unroll
      for (int st = 0; st < 2; st++) {
        const uint2 g = lds_u32x2(sbase + OG_SGU + ((lane >> 2) & 1) * 64 + st * 32 + (lane & 3) * 8);
        #pragma unroll
        for (int j = 0; j < 4; j++) {
          const uint32_t b0 = GEMV_B0(j, g, sel), b1 = GEMV_B1(j, g, sel);
          mma_bf16(d[j & 1], wd[4 * st + j].x, wd[4 * st + j].y, wd[4 * st + j].z, wd[4 * st + j].w, b0, b1);
          mma_bf16(d[2 + (j & 1)], wd[8 + 4 * st + j].x, wd[8 + 4 * st + j].y, wd[8 + 4 * st + j].z, wd[8 + 4 * st + j].w, b0, b1);
        }
      }
      #pragma unroll
      for (int e = 0; e < 4; e++) { d[0][e] += d[1][e]; d[2][e] += d[3][e]; }
      const float4 y0 = gemv_out(d[0], lane), y1 = gemv_out(d[2], lane);
      float* yp = g_ypart + (size_t)(bx * 2 + (lane & 1)) * T_D + w8 * 128 + (lane >> 2) * 8 + (lane & 2) * 2;
      st_tagged4(yp, y0.x, y0.y, y0.z, y0.w);
      st_tagged4(yp + 64, y1.x, y1.y, y1.z, y1.w);
      named_bar_sync(9, 256);
      if (t2 == 0) hint_arrive(CNT_Y);
    }
    TL_MARK2(14, threadIdx.x == 128);
    TL_CLK(4, 1, threadIdx.x == 128);
}

__device__ __noinline__ void store_warp(Scratch* hm, uint32_t sbase, const CUtensorMap* tmO, int item0, int n_items) {
  if (elect_one()) {
    const uint32_t bars = sbase + AT_SBAR, b_q0 = bars + 80, b_ob = bars + 96, b_ordy = bars + 104, b_acq = bars + 264;
    mbar_wait(bars + 232, 0);
    const uint32_t bx = lds_u32(bars + 240);
    const unsigned int* cnt = &g_hcnt[32 * (1 + OG_MT(bx)) + 2];
    #pragma unroll 1
    for (int q = 0; q < 4 * n_items; q++) {
      const int item = item0 + (q >> 2) * 128, h = (q >> 1) & 1, w = q & 1;
      const bool last = (q >> 2) == n_items - 1;
      mbar_wait(b_ordy + 8 * (q & 3), q >> 2);
      store_o(tmO, (h ? (last ? sbase + AT_SQ + 32768 : sbase + 2 * 32768) : sbase + AT_SQ) + w * 8192, (item >> 4) * 2 + h, (item & 15) * 128 + w * 64);
      if (w) {
        PF(1 + (q >> 1));
        bulk_wait_read<0>();
        mbar_arrive(h ? b_ob : b_q0);
        bulk_wait<0>();
        fence_proxy_async_global();
        red_release_add(&g_hcnt[32 * (1 + (item & 15)) + 2 + (item >> 7)], 1u);
        if (bx < 128 && q == (n_items == 2 ? 5 : 3)) { spin_until(cnt, 16u); mbar_arrive(b_acq); }
      }
    }
    if (bx < 128) { spin_until(&g_hcnt[0], 8u); spin_until(cnt + 1, 16u); mbar_arrive(b_acq); }
  }
}

__global__ void __launch_bounds__(384, 1)
fused_kernel(const bf16* __restrict__ x, const bf16* __restrict__ cvec, const bf16* __restrict__ w_mod, Scratch* hm, uint32_t zero,
            const uint8_t* __restrict__ pf_wo, const bf16* __restrict__ kc, const bf16* __restrict__ vc, const bf16* __restrict__ w_r,
            const bf16* __restrict__ w_gate, const bf16* __restrict__ w_up, const bf16* __restrict__ w_down, bf16* __restrict__ out,
            const __grid_constant__ CUtensorMap tmM, const __grid_constant__ CUtensorMap tmW, const __grid_constant__ CUtensorMap tmK,
            const __grid_constant__ CUtensorMap tmV, const __grid_constant__ CUtensorMap tmO, const __grid_constant__ CUtensorMap tmOl, const __grid_constant__ CUtensorMap tmWo,
            const __grid_constant__ CUtensorMap tmX, const __grid_constant__ CUtensorMap tmOut)
{
  extern __shared__ __align__(1024) uint8_t smem_raw[];
  const uint32_t sbase = smem_u32(smem_raw);
  const uint32_t bars = sbase + AT_SBAR;
  const uint32_t b_full = bars, b_empty = bars + 40;
  const uint32_t b_q0 = bars + 80, b_q1 = bars + 88;
  const uint32_t b_ob = bars + 96;
  const uint32_t b_ordy = bars + 104;
  const uint32_t b_pin = bars + 136;
  const uint32_t b_a0 = bars + 144;
  const uint32_t b_x = bars + 160;
  const uint32_t b_w = bars + 152, b_go = bars + 224;
  const uint32_t b_bx = bars + 232, s_bx = bars + 240;
  const uint32_t b_tab = bars + 272;
  const int wid = __shfl_sync(0xffffffffu, threadIdx.x >> 5, 0), wg = wid >> 2;
  const bool single = blockIdx.x >= AT_NFULL;
  const int item0 = __shfl_sync(0xffffffffu, blockIdx.x < 128 ? (int)blockIdx.x : (int)blockIdx.x + 124, 0), n_items = __shfl_sync(0xffffffffu, single ? 1 : 2, 0);
  const uint32_t t0 = clock_lo();
  TL_START(3);
  HS(0);
  if (threadIdx.x == 0) {
    if (sbase & 1023u) __trap();
    for (int i = 0; i < 5; i++) { mbar_init(b_full + 8 * i, 1); mbar_init(b_empty + 8 * i, 2); }
    mbar_init(b_q0, 1); mbar_init(b_q1, 8); mbar_init(b_ob, 1);
    for (int i = 0; i < 4; i++) mbar_init(b_ordy + 8 * i, 4);
    mbar_init(b_pin, 1); mbar_init(b_a0, 8); mbar_init(b_x, 1); mbar_init(b_w, 1); mbar_init(b_go, 1); mbar_init(b_bx, 1);
    for (int i = 0; i < 8; i++) mbar_init(b_tab + 8 * i, i < 2 ? 1 : 2);
    mbar_init(bars + 168, 1); mbar_init(bars + 176, 1); mbar_init(bars + 184, 8); mbar_init(bars + 192, 2);
    mbar_init(bars + 200, 8); mbar_init(bars + 208, 1); mbar_init(bars + 216, 1); mbar_init(bars + 264, 1);
    fence_mbar_init();
    if (blockIdx.x < 128) {
      HS(1);
      wait_clock(t0, XDLY);
      mbar_expect_tx(b_x, 32768);
      bulk_load_hint(sbase + 3 * 32768, x + (size_t)blockIdx.x * 16 * T_D, 32768, b_x, pol_normal());
    }
    mbar_arrive(b_tab); mbar_arrive(b_tab + 8);
  }

  if (wg == 0) {
    reg_dealloc<AT_PREG>();
    if (wid == 0) { __syncwarp(); named_bar_arrive(6, 128); named_bar_arrive(11, 160); named_bar_arrive(12, 160); }
    if (wid >= 2) {
      named_bar_sync(6, 128);
      gather_table(hm, t0, sbase + 4 * 32768, b_tab, b_a0, wid & 1, threadIdx.x & 31);
    } else if (wid == 1) {
      named_bar_sync(6, 128);
      sleep_until(t0, 26000);
      const uint32_t v = assign_tile(hm, t0, threadIdx.x & 31);
      if (threadIdx.x == 32) { sts_u32(s_bx, v); mbar_arrive(b_bx); }
      __syncwarp();
      store_warp(hm, sbase, &tmO, item0, n_items);
      __syncwarp();
    } else {
     if (elect_one()) {
      const uint64_t pol = policy_evict_first();
      prefetch_tmap(&tmW); prefetch_tmap(&tmX); prefetch_tmap(&tmWo); prefetch_tmap(&tmOl);
      if (single) { prefetch_tmap(&tmM); mbar_wait(b_go, 0); }
      uint32_t slot = 0, ph = 1;
      #pragma unroll 1
      for (int it = 0; it < n_items; it++) {
        const int item = item0 + it * 128, hp = item >> 4, qt = item & 15;
        const bool first = it == 0;
        const uint64_t polx = first ? pol_normal() : pol;
        const uint32_t ab = first ? 16384 : 16384 + 256;
        auto load_a = [&](int i, uint32_t fb) {
          tma_load_2d_hint(sbase + AT_SQ + (i & 3) * 16384, &tmX, i * 64, qt * 128, fb, polx);
          if (!first) bulk_load_hint(sbase + OG_SCOL + (i & 3) * 256, hm->tab + blockIdx.x * 4096 + i * 256, 256, fb, pol);
        };
        #pragma unroll 1
        for (int j = 0; j < T_D / 64; j++) {
          const uint32_t sl = ring_slot(qp_pos(j, it)), fb = b_full + 8 * sl;
          mbar_wait(b_empty + 8 * sl, ring_par(qp_pos(j, it)) ^ ((j >> 2) & 1) ^ 1);
          mbar_expect_tx(fb, 32768 + (j == 0 ? 2 * ab : j == T_D / 64 - 1 ? 0 : ab));
          if (j < 4 && first) {
            if (j < 2) wait_clock(t0, j ? ST1_T : PRE_T);
            if (j == 3) mbar_wait(b_a0, 0);
            HS(2 + j);
          }
          tma_load_3d_hint(sbase + sl * 32768, &tmW, j * 64, hp * 4, fb, pol);
          if (j == 0) {
            if (first) wait_clock(t0, A_T);
            else { mbar_wait(b_q0, 0); mbar_wait(b_q1, 0); }
            load_a(0, fb);
          }
          if (j == 3) mbar_wait(b_a0, it);
          if (j < T_D / 64 - 1) load_a(j + 1, fb);
        }
        #pragma unroll 1
        for (int j = 0; j < 4 * AT_NBLK; j++) {
          const bool isv = (j > 0 && !(j & 1)) || j == 4 * AT_NBLK - 1;
          const int row = hp * 2 * T_SEQ + (isv ? (j - 1) >> 1 : (j + 1) >> 1) * 128;
          const uint32_t fb = b_full + 8 * slot;
          mbar_wait(b_empty + 8 * slot, ph);
          if (!first && j == 3) mbar_wait(b_ob, 0);
          mbar_expect_tx(fb, 32768);
          tma_load_2d_hint(sbase + slot * 32768, isv ? &tmV : &tmK, 0, row, fb, pol);
          tma_load_2d_hint(sbase + slot * 32768 + 16384, isv ? &tmV : &tmK, 64, row, fb, pol);
          if (it == 1 && isv && j >= 2 * WO_LATE && j < 2 * WO_LATE + 32 && blockIdx.x < 64)
            l2_prefetch_bulk(pf_wo + (size_t)blockIdx.x * 131072 + ((j >> 1) - WO_LATE) * 8192, 8192);
          if (++slot == 5) { slot = 0; ph ^= 1; }
        }
      }
      mbar_wait(b_bx, 0);
      const uint32_t bx = lds_u32(s_bx);
      if (bx < 128) {
        if (single) mbar_wait(b_go, 1);
        tail_producer(hm, bx, sbase, 0, n_items - 1, pol, &tmOl, &tmWo, &tmX, w_down);
      }
     }
    }
    __syncwarp();
    PSV(0, threadIdx.x == 96, t0);
    mbar_wait(b_bx, 0);
    const uint32_t bx = __shfl_sync(0xffffffffu, lds_u32(s_bx), 0);
    if (bx < 128) tail_exchange(hm, bx, sbase, __shfl_sync(0xffffffffu, threadIdx.x, threadIdx.x), &tmOut, out);
  } else {
    if (wg == 1 && blockIdx.x < 128) head_first(hm, sbase + 4 * 32768 + 4096, threadIdx.x - 128, cvec, w_mod);
    named_bar_sync(10 + wg, 160);
    if (wg == 2 && blockIdx.x < 128) head_stats(hm, sbase + 3 * 32768, b_x, threadIdx.x - 256);
    if (single) {
      wait_clock(t0, WDLY);
      mod_rest(hm, sbase, b_w, threadIdx.x - 128, (int)blockIdx.x - AT_NFULL, cvec, &tmM, w_r);
      sleep_until(t0, CLR_T);
      #pragma unroll 1
      for (int i = (blockIdx.x - AT_NFULL) * 256 + threadIdx.x - 128; i < (int)(sizeof(TailMail) / 16); i += 8 * 256) reinterpret_cast<uint4*>(&hm->mail)[i] = make_uint4(0u, 0u, 0u, 0u);
      named_bar_sync(5, 256);
      if (threadIdx.x == 128) red_release_add(&g_hcnt[0], 1u);
      sleep_until(t0, SGL_T);
      if (threadIdx.x == 128) mbar_arrive(b_go);
    }
    if (wg == 1) { wait_clock(t0, GDLY); head_gather(hm, sbase + 4 * 32768, threadIdx.x - 128); }
    reg_alloc<AT_CREG>();
    const int cwg = wg - 1;
    const int tid = threadIdx.x & 127;
    const int warp = tid >> 5, lane = tid & 31;
    const uint32_t dbase = (sbase & 0x3FFFFu) >> 4;
    const uint32_t k_base = dbase + (1u << 16);
    const uint32_t v_base = dbase + (1024u << 16);
    const uint32_t w_base = dbase + (512u << 16);
    const uint32_t frag = cwg * 8192 + (16 * warp + (lane & 7) + 8 * ((lane >> 3) & 1)) * 128;
    if (cwg == 1) named_bar_arrive(1, 256);
    bool raw = false;
    uint32_t rw[16], sta = 0, stb = 0, xa = 0, xt = 0;
    uint4 tb[4];
    #pragma unroll
    for (int i = 0; i < 4; i++) { rw[4 * i] = 0; rw[4 * i + 1] = 0; rw[4 * i + 2] = 0; rw[4 * i + 3] = 0; tb[i] = make_uint4(0u, 0u, 0u, 0u); }
    auto qp_fetch = [&](int j, uint32_t tmask) {
      #pragma unroll
      for (int st = 0; st < 4; st++) {
        ldmatrix_x4((xa ^ (st * 32)) + (j & 3) * 16384, rw[4 * st], rw[4 * st + 1], rw[4 * st + 2], rw[4 * st + 3]);
        tb[st] = lds_u32x4(xt + (j & tmask) * 256 + st * 64);
      }
    };
    auto qp_first = [&](uint32_t tab) {
      uint32_t ln2; asm volatile("mov.u32 %0, %%tid.x;" : "=r"(ln2));
      xa = sbase + AT_SQ + ((ln2 - 128) >> 5) * 2048 + (ln2 & 15) * 128 + ((((ln2 >> 4) & 1) ^ (ln2 & 7)) << 4);
      xt = tab + (ln2 & 3) * 16;
      qp_fetch(0, 0);
      const uint32_t a = sbase + OG_SMISC + 256 + ((ln2 - 128) >> 5) * 64 + (ln2 & 28);
      sta = lds_u32(a); stb = lds_u32(a + 32);
    };
    #pragma unroll 1
    for (int it = 0; it < n_items; it++) {
      const int item = item0 + it * 128, hp = item >> 4;
      const bool more = it + 1 < n_items;
      constexpr int nkb = T_D / 64;
      const int ta = __shfl_sync(0xffffffffu, 4 * it, 0);
      float acc[128], c0, c1;
      {
        FS(2 * it, 0);
        uint32_t af[2][16];
        const uint32_t tmask = ta ? 3 : 15;
        zero_regs(acc);
        #pragma unroll
        for (int i = 0; i < 16; i++) af[1][i] = 0u;
        if (it == 0) {
          uint32_t ln2; asm volatile("mov.u32 %0, %%tid.x;" : "=r"(ln2));
          const float2* stp = hm->stat + (item & 15) * 256 + ((ln2 - 128) >> 5) * 32 + (ln2 & 3) * 8 + ((ln2 >> 2) & 7);
          HS(4);
          wait_clock(t0, SDLY);
          float2 sv = ld_tagged2(stp);
          named_bar_sync(5, 256);
          mbar_wait(b_full, 0);
          HS(5);
          qp_first(sbase + 4 * 32768);
          #pragma unroll 1
          for (unsigned int spin = 0; spin < (1u << 22); spin++) {
            if (__all_sync(0xffffffffu, (__float_as_uint(sv.x) != 0u) & (__float_as_uint(sv.y) != 0u))) break;
            sv = ld_tagged2(stp);
          }
          HS(6);
          if ((ln2 & 31) == 0) mbar_arrive(b_a0 + (rw[3] & rw[7] & rw[11] & rw[15] & zero));
          const uint32_t st = ln_stat(sv.x + __shfl_xor_sync(0xffffffffu, sv.x, 1), sv.y + __shfl_xor_sync(0xffffffffu, sv.y, 1)), so = __shfl_xor_sync(0xffffffffu, st, 2);
          sta = (ln2 & 2) ? so : st; stb = (ln2 & 2) ? st : so;
          sts_u32(sbase + OG_SMISC + 256 + ((ln2 - 128) >> 5) * 64 + (ln2 & 28) + (ln2 & 2) * 16, st);
        }
        const uint32_t mean_a = __byte_perm(sta, 0u, 0x1010), mean_b = __byte_perm(stb, 0u, 0x1010), sd_a = __byte_perm(sta, 0u, 0x3232), sd_b = __byte_perm(stb, 0u, 0x3232);
        c0 = AT_C * rcp_approx(bfhi(sta)); c1 = AT_C * rcp_approx(bfhi(stb));
        uint32_t prev = b_pin - 40;
        #pragma unroll 1
        for (int j2 = 0; j2 < nkb; j2 += 2) {
          #pragma unroll
          for (int u = 0; u < 2; u++) {
            const int j = j2 + u;
            const uint32_t slot = ring_slot(qp_pos(j, ta >> 2)), par = ring_par(qp_pos(j, ta >> 2)) ^ ((j >> 2) & 1), bt = b_tab + 4 * ((j + 1) & 15);
            if (u == 1) {
              #pragma unroll 1
              for (uint32_t z = 0; z < zero; z++)
                #pragma unroll
                for (int i = 0; i < 16; i += 4) sts_u32x4(xt + i * 4, af[1][i], af[1][i + 1], af[1][i + 2], af[1][i + 3]);
            }
            bool ok = mbar_test(b_full + 8 * slot, par);
            if (u == 1) ok &= mbar_test(bt, 0);
            #pragma unroll
            for (int st = 0; st < 4; st++) {
              af[u][4 * st + 0] = bfma2(bsub2(rw[4 * st + 0], mean_a), tb[st].x, bmul2(tb[st].z, sd_a));
              af[u][4 * st + 1] = bfma2(bsub2(rw[4 * st + 1], mean_b), tb[st].x, bmul2(tb[st].z, sd_b));
              af[u][4 * st + 2] = bfma2(bsub2(rw[4 * st + 2], mean_a), tb[st].y, bmul2(tb[st].w, sd_a));
              af[u][4 * st + 3] = bfma2(bsub2(rw[4 * st + 3], mean_b), tb[st].y, bmul2(tb[st].w, sd_b));
            }
            if (!ok) { mbar_wait(b_full + 8 * slot, par); if (u == 1) mbar_wait(bt, 0); }
            qp_fetch(j + 1, tmask);
            if (QP_STAG > 0 && cwg == 1 && j == nkb - QP_STAG) {
              named_bar_sync(7, 256);
            }
            const bool turn = QTN > 0 && (uint32_t)(j - QT0) <= (uint32_t)(QTN - 1);
            if (turn) named_bar_sync(1 + cwg, 256);
            const uint32_t b_lo = w_base + slot * 2048;
            wgmma_fence();
            wgmma_m64n256k16_rs_tb<0>(acc, af[u][0], af[u][1], af[u][2], af[u][3], b_lo, 1);
            wgmma_m64n256k16_rs_tb<128>(acc, af[u][4], af[u][5], af[u][6], af[u][7], b_lo, 1);
            wgmma_m64n256k16_rs_tb<256>(acc, af[u][8], af[u][9], af[u][10], af[u][11], b_lo, 1);
            if (QARR == 3) named_bar_arrive_if(turn, 1 + (cwg ^ 1), 256);
            wgmma_m64n256k16_rs_tb<384>(acc, af[u][12], af[u][13], af[u][14], af[u][15], b_lo, 1);
            wgmma_commit();
            if (QARR == 4) named_bar_arrive_if(turn, 1 + (cwg ^ 1), 256);
            if (QP_STAG > 0 && cwg == 0 && j == nkb - 1) named_bar_arrive(7, 256);
            if (LATEF && j == 0 && it != 0) {
              fence_proxy_async();
              __syncwarp();
              if (lane == 0) mbar_arrive(b_ordy + 16 + 8 * cwg);
            }
            if (j == 0 && it == 0) HS(7);
            wgmma_wait<1>();
            if (tid == 0) mbar_arrive(prev + 40);
            prev = b_full + 8 * slot;
          }
        }
        wgmma_wait<0>();
        fence_regs(acc);
        FS(2 * it, 1);
        TL_MARK2(29, threadIdx.x == 256 && it == 0);
        PS(1 + 2 * it, threadIdx.x == 256);
        if (tid == 0) mbar_arrive(b_empty + 24);
      }
      float o[64], s[64];
      uint32_t p[32], q[32];
      #pragma unroll
      for (int i = 0; i < 32; i++) q[i] = pack_bf16(acc[2 * i] * ((i & 1) ? c1 : c0), acc[2 * i + 1] * ((i & 1) ? c1 : c0));
      zero_regs(s);
      const uint32_t sq = sbase + AT_SQ + cwg * 8192;
      const bool last_wg1 = cwg == 1 && !more;
      float mc0, mc1, al0 = 1.0f, al1 = 1.0f, l0 = 0.f, l1 = 0.f, lp0 = 0.f, lp1 = 0.f;
      bool redo0 = false;
      FS(2 * it, 2);
      {
        uint32_t dep = zero;
        #pragma unroll
        for (int i = 0; i < 32; i += PINQ) dep &= q[i];
        mbar_wait(b_full + 8 * ring_slot(ta) + dep, ring_par(ta));
      }
      named_bar_sync(1 + cwg, 256);
      FS(2 * it, 3);
      issue_qk(s, q, k_base + ring_slot(ta) * 2048);
      named_bar_arrive(1 + (cwg ^ 1), 256);
      const uint32_t rdy = (uint32_t)mbar_test(b_full + 8 * ring_slot(ta + 1), ring_par(ta + 1));
      bool ready = rdy & mbar_test(b_full + 8 * ring_slot(ta + 2), ring_par(ta + 2));
      stage_o(*reinterpret_cast<const float (*)[64]>(&acc[64]), c0, c1, sbase + AT_SQ + 32768 + frag, lane);
      wgmma_wait<0>();
      fence_regs(s);
      if (tid == 0) mbar_arrive(b_empty + 8 * ring_slot(ta));
      mc0 = 0.f; mc1 = 0.f;
      if (!raw) {
        raw = softmax_mode(s, mc0, mc1);
        if (__builtin_expect(!raw, 0)) softmax_sub(s, mc0, mc1);
      }
      softmax_exp<0, 64>(s);
      stage_qregs(q, sbase + AT_SQ + frag, lane);
      pack_p(p, s);
      zero_regs(o);
      FS(2 * it, 4);
      uint32_t ks = ring_slot(ta + 1), vs = ring_slot(ta + 2), kp = ring_par(ta + 1), vp = ring_par(ta + 2);
      auto finish_head = [&]() {
        FS(2 * it, 5);
        redo0 = finish_l(lp0, lp1);
        if (!redo0) {
          stage_o(o, lp0, lp1, sbase + AT_SQ + frag, lane);
          fence_proxy_async();
          __syncwarp();
          if (lane == 0) mbar_arrive(b_ordy + 8 * cwg);
        }
        FS(2 * it + 1, 4);
      };
      if (!ready) { mbar_wait(b_full + 8 * ks, kp); mbar_wait(b_full + 8 * vs, vp); }
      #pragma unroll 1
      for (int n = 1; n < 2 * AT_NBLK; n++) {
        named_bar_sync(1 + cwg, 256);
        issue_qk(s, q, k_base + ks * 2048);
        if (n == AT_NBLK + 1) finish_head();
        issue_pv(o, p, v_base + vs * 2048, (n & 15) != 1);
        if (!(last_wg1 && n == 2 * AT_NBLK - 1)) named_bar_arrive(1 + (cwg ^ 1), 256);
        wgmma_wait<1>();
        fence_regs(s);
        if (tid == 0) mbar_arrive(b_empty + 8 * ks);
        if (__builtin_expect(!raw || (n + 1) >> 1 == AT_NBLK / 2, 0)) {
          if (n == AT_NBLK - 1) {
            #pragma unroll
            for (int J = 0; J < 16; J += 2)
              ldmatrix_x4(sbase + AT_SQ + 32768 + frag + (J >> 3) * 16384 + ((((J & 7) + (lane >> 4)) ^ (lane & 7)) << 4), q[2 * J], q[2 * J + 1], q[2 * J + 2], q[2 * J + 3]);
          }
          if (n == AT_NBLK && lane == 0) mbar_arrive(b_q1);
          if (!raw) {
            const float m0 = mc0, m1 = mc1;
            const bool ok = softmax_mode(s, mc0, mc1);
            if (n == AT_NBLK) raw = ok;
            else {
              mc0 = mc0 - AT_HEAD > m0 ? mc0 : m0; mc1 = mc1 - AT_HEAD > m1 ? mc1 : m1;
              al0 = ex2_approx(m0 - mc0); al1 = ex2_approx(m1 - mc1);
            }
            if (!raw) softmax_sub(s, mc0, mc1);
          }
        }
        softmax_exp<0, AT_SPLIT>(s);
        add_rowsum(p, l0, l1);
        if (tid == 0) {
          uint32_t dep = zero & __float_as_uint(l0) & __float_as_uint(l1);
          #pragma unroll
          for (int i = AT_SPLIT - AT_PIN - PINB; i < AT_SPLIT - PINB; i += 2) dep &= __float_as_uint(s[i]) & __float_as_uint(s[i + 1]);
          mbar_arrive(b_pin + dep);
        }
        wgmma_wait<0>();
        fence_regs(o);
        if (tid == 0) mbar_arrive(b_empty + 8 * vs);
        ks += 2; if (ks >= 5) { ks -= 5; kp ^= 1; }
        vs += 2; if (vs >= 5) { vs -= 5; vp ^= 1; }
        ready = mbar_test(b_full + 8 * ks, kp) & mbar_test(b_full + 8 * vs, vp);
        softmax_exp<AT_SPLIT, 64>(s);
        pack_p(p, s);
        if (n == AT_NBLK) { lp0 = l0; lp1 = l1; l0 = 0.f; l1 = 0.f; }
        if (__builtin_expect(!raw || !ready, 0)) {
        if (!raw && __any_sync(0xffffffffu, al0 != 1.0f || al1 != 1.0f)) {
          rescale_o(o, al0, al1);
          l0 *= al0; l1 *= al1;
          al0 = 1.0f; al1 = 1.0f;
        }
        if (!ready && n < 2 * AT_NBLK - 1) {
          mbar_wait(b_full + 8 * ks, kp);
          mbar_wait(b_full + 8 * vs, vp);
        }
        }
      }
      FS(2 * it + 1, 5);
      const uint32_t vl = ring_slot(ta + 63);
      vs = ring_slot(ta + 62);
      const uint32_t ob = more ? sbase + vs * 32768 : sbase + AT_SQ + 32768;
      mbar_wait(b_full + 8 * vl, ring_par(ta + 63));
      issue_pv(o, p, v_base + vl * 2048, 1);
      add_rowsum(p, l0, l1);
      const bool overflow = finish_l(l0, l1);
      if (more && !redo0) mbar_wait(b_full + 32, 0);
      mbar_wait(b_empty + 8 * vs, ring_par(ta + 62));
      wgmma_wait<0>();
      fence_regs(o);
      qp_first(sbase + OG_SCOL);
      if (tid == 0) mbar_arrive(b_empty + 8 * vl);
      FS(2 * it + 1, 6);
      if (overflow) stage_qregs(q, ob + frag, lane);
      else stage_o(o, l0, l1, ob + frag, lane);
      if (__builtin_expect(overflow || redo0, 0)) {
        __syncwarp();
        #pragma unroll 1
        for (int h = redo0 ? 0 : 1; h < (overflow ? 2 : 1); h++)
          attn_rows_exact(h ? ob + cwg * 8192 : sq, warp, lane, kc + (size_t)(hp * 2 + h) * T_SEQ * T_DH, vc + (size_t)(hp * 2 + h) * T_SEQ * T_DH);
        fence_proxy_async();
        __syncwarp();
        if (lane == 0 && redo0) mbar_arrive(b_ordy + 8 * cwg);
        if (more) mbar_wait(b_full + 32, 0);
        qp_first(sbase + OG_SCOL);
        raw = false;
      }
      if (!LATEF || !more) {
        fence_proxy_async();
        __syncwarp();
        if (lane == 0) mbar_arrive(b_ordy + 16 + 8 * cwg);
      }
      if (lane == 0) {
        mbar_arrive(b_a0 + (rw[3] & rw[7] & rw[11] & rw[15] & zero));
      }
      named_bar_sync(3 + cwg, 128);
      FS(2 * it + 1, 7);
      PS(2 + 2 * it, threadIdx.x == 256);
    }
    if (single) {
      named_bar_sync(5, 256);
      if (threadIdx.x == 128) {
        #pragma unroll 1
        for (int i = 4; i < 8; i++) {
          mbar_arrive(b_full + 8 * ring_slot(i));
          mbar_arrive(b_empty + 8 * ring_slot(i)); mbar_arrive(b_empty + 8 * ring_slot(i));
        }
        mbar_arrive(b_go);
      }
      named_bar_sync(5, 256);
    }
    TL_CLK(3, 1, threadIdx.x == 128);
    TL_CTA(1, threadIdx.x == 256);
    TL_END(3, tid == 0);
    __syncwarp();
    QDUMP();
    TL_MARK2(19, tid == 0 && !single);
    mbar_wait(b_bx, 0);
    const uint32_t bx = __shfl_sync(0xffffffffu, lds_u32(s_bx), 0);
    if (bx < 128) {
      tail_consumer(hm, bx, sbase, (int)threadIdx.x - 128, cwg, w_gate, w_up);
    }
  }
}

typedef CUresult (*PFN_encodeTiled)(CUtensorMap*, CUtensorMapDataType, cuuint32_t, void*, const cuuint64_t*, const cuuint64_t*,
                                    const cuuint32_t*, const cuuint32_t*, CUtensorMapInterleave, CUtensorMapSwizzle,
                                    CUtensorMapL2promotion, CUtensorMapFloatOOBfill);

CUtensorMap make_map_2d(PFN_encodeTiled enc, const void* ptr, uint64_t inner, uint64_t outer, uint64_t stride_bytes, uint32_t box_inner, uint32_t box_outer) {
  CUtensorMap m;
  cuuint64_t gd[2] = {inner, outer}; cuuint64_t gs[1] = {stride_bytes};
  cuuint32_t bx[2] = {box_inner, box_outer}; cuuint32_t es[2] = {1, 1};
  enc(&m, CU_TENSOR_MAP_DATA_TYPE_BFLOAT16, 2, const_cast<void*>(ptr), gd, gs, bx, es, CU_TENSOR_MAP_INTERLEAVE_NONE,
      CU_TENSOR_MAP_SWIZZLE_128B, CU_TENSOR_MAP_L2_PROMOTION_L2_128B, CU_TENSOR_MAP_FLOAT_OOB_FILL_NONE);
  return m;
}

CUtensorMap make_map_3d(PFN_encodeTiled enc, const void* ptr, uint64_t cols, uint64_t rows, uint32_t box_rows, uint32_t chunks) {
  CUtensorMap m;
  cuuint64_t gd[3] = {64, rows, cols / 64}; cuuint64_t gs[2] = {cols * 2, 128};
  cuuint32_t bx[3] = {64, box_rows, chunks}; cuuint32_t es[3] = {1, 1, 1};
  enc(&m, CU_TENSOR_MAP_DATA_TYPE_BFLOAT16, 3, const_cast<void*>(ptr), gd, gs, bx, es, CU_TENSOR_MAP_INTERLEAVE_NONE,
      CU_TENSOR_MAP_SWIZZLE_128B, CU_TENSOR_MAP_L2_PROMOTION_L2_128B, CU_TENSOR_MAP_FLOAT_OOB_FILL_NONE);
  return m;
}

}

extern "C" void kernel_launch(void* const* d_in, const int* in_sizes, int n_in, void* d_out, int out_size) {
  const bf16* x      = (const bf16*)d_in[0];
  const bf16* kc     = (const bf16*)d_in[1];
  const bf16* vc     = (const bf16*)d_in[2];
  const bf16* wq     = (const bf16*)d_in[3];
  const bf16* wo     = (const bf16*)d_in[4];
  const bf16* w_r    = (const bf16*)d_in[6];
  const bf16* w_gate = (const bf16*)d_in[7];
  const bf16* w_up   = (const bf16*)d_in[8];
  const bf16* w_down = (const bf16*)d_in[9];
  const bf16* cvec   = (const bf16*)d_in[10];
  const bf16* w_mod  = (const bf16*)d_in[11];
  bf16* out = (bf16*)d_out;

  static PFN_encodeTiled enc = nullptr;
  static void *p_o = nullptr, *p_hm = nullptr;
  if (!enc) {
    void* fn = nullptr; cudaDriverEntryPointQueryResult qres;
    cudaGetDriverEntryPoint("cuTensorMapEncodeTiled", &fn, cudaEnableDefault, &qres);
    enc = (PFN_encodeTiled)fn;
    cudaGetSymbolAddress(&p_o, g_o);
    cudaGetSymbolAddress(&p_hm, g_scr);
    cudaFuncSetAttribute(fused_kernel, cudaFuncAttributeMaxDynamicSharedMemorySize, (int)AT_SMEM);
  }
  const CUtensorMap tm_m   = make_map_2d(enc, w_mod, 6 * T_D, T_D, 6 * T_D * 2, 64, 256);
  const CUtensorMap tm_wq  = make_map_3d(enc, wq, T_DQKV, T_D, 64, 4);
  const CUtensorMap tm_k   = make_map_2d(enc, kc, T_DH, (uint64_t)T_NH * T_SEQ, T_DH * 2, 64, 128);
  const CUtensorMap tm_v   = make_map_2d(enc, vc, T_DH, (uint64_t)T_NH * T_SEQ, T_DH * 2, 64, 128);
  const CUtensorMap tm_ost = make_map_2d(enc, p_o, T_DQKV, T_SEQ, T_DQKV * 2, 64, 64);
  const CUtensorMap tm_old = make_map_2d(enc, p_o, T_DQKV, T_SEQ, T_DQKV * 2, 64, 128);
  const CUtensorMap tm_wo  = make_map_2d(enc, wo, T_D, T_DQKV, T_D * 2, 64, 64);
  const CUtensorMap tm_x   = make_map_2d(enc, x, T_D, T_SEQ, T_D * 2, 64, 128);
  const CUtensorMap tm_out = make_map_2d(enc, out, T_D, T_SEQ, T_D * 2, 64, 128);

  fused_kernel<<<132, 384, AT_SMEM, cudaStreamPerThread>>>(x, cvec, w_mod, (Scratch*)p_hm, 0u, (const uint8_t*)wo, kc, vc, w_r, w_gate, w_up, w_down, out,
             tm_m, tm_wq, tm_k, tm_v, tm_ost, tm_old, tm_wo, tm_x, tm_out);
}
```

```cpp
#include <cuda_runtime.h>
#include <cuda_bf16.h>
#include <cuda.h>
#include <stdint.h>

namespace {

typedef __nv_bfloat16 bf16;

constexpr int T_SEQ = 2048, T_D = 1024, T_NH = 32, T_DH = 128, T_DQKV = 4096, T_F = 3584;

struct __align__(2048) TailMail {
  float4 part1[T_SEQ * 8];
  uint32_t key[256];
  uint4 cand[16 * 2 * 2 * 128];
  uint32_t cnt[32];
  float ypart[(T_F / 32) * 2 * T_D];
};
#define OLD 5120
constexpr int O_LD = OLD, O_H = T_DQKV;
struct __align__(2048) Scratch {
  TailMail mail;
  float mod[2 * T_D];
  float modu[16 * 512];
  float2 stat[T_SEQ * 2];
  uint32_t gkey[160];
  uint8_t col[8 * 1536];
  unsigned int hcnt[17 * 32];
  float scal[4];
  __align__(1024) bf16 o[T_SEQ * O_LD];
};
__device__ Scratch g_scr;
#define g_part1 hm->mail.part1
#define g_key hm->mail.key
#define g_cand hm->mail.cand
#define CNT_Y hm->mail.cnt
#define g_ypart hm->mail.ypart
#define g_col hm->col
#define g_scal hm->scal
#define g_hcnt hm->hcnt

__device__ __forceinline__ uint32_t smem_u32(const void* p) { return (uint32_t)__cvta_generic_to_shared(p); }
__device__ __forceinline__ void mbar_init(uint32_t bar, uint32_t cnt) { asm volatile("mbarrier.init.shared::cta.b64 [%0], %1;" :: "r"(bar), "r"(cnt)); }
__device__ __forceinline__ void mbar_expect_tx(uint32_t bar, uint32_t bytes) { asm volatile("mbarrier.arrive.expect_tx.shared::cta.b64 _, [%0], %1;" :: "r"(bar), "r"(bytes) : "memory"); }
__device__ __forceinline__ void mbar_arrive(uint32_t bar) { asm volatile("mbarrier.arrive.shared::cta.b64 _, [%0];" :: "r"(bar) : "memory"); }
__device__ __forceinline__ void mbar_wait(uint32_t bar, uint32_t parity) {
  asm volatile("{\n.reg .pred p;\nLAB_WAIT:\nmbarrier.try_wait.parity.shared::cta.b64 p, [%0], %1;\n@!p bra LAB_WAIT;\n}\n" :: "r"(bar), "r"(parity) : "memory");
}
__device__ __forceinline__ bool mbar_test(uint32_t bar, uint32_t parity) {
  uint32_t r; asm volatile("{\n.reg .pred p;\nmbarrier.test_wait.parity.shared::cta.b64 p, [%1], %2;\nselp.u32 %0, 1, 0, p;\n}\n" : "=r"(r) : "r"(bar), "r"(parity) : "memory");
  return r != 0;
}
__device__ __forceinline__ void fence_mbar_init() { asm volatile("fence.mbarrier_init.release.cluster;" ::: "memory"); }
__device__ __forceinline__ uint64_t policy_evict_first() {
  uint64_t p; asm volatile("createpolicy.fractional.L2::evict_first.b64 %0, 1.0;" : "=l"(p)); return p;
}
__device__ __forceinline__ void tma_load_2d_hint(uint32_t dst, const CUtensorMap* map, int c0, int c1, uint32_t bar, uint64_t pol) {
  asm volatile("cp.async.bulk.tensor.2d.shared::cluster.global.mbarrier::complete_tx::bytes.L2::cache_hint [%0], [%1, {%3, %4}], [%2], %5;"
    :: "r"(dst), "l"(map), "r"(bar), "r"(c0), "r"(c1), "l"(pol) : "memory");
}
__device__ __forceinline__ void tma_load_3d_hint(uint32_t dst, const CUtensorMap* map, int c1, int c2, uint32_t bar, uint64_t pol) {
  asm volatile("cp.async.bulk.tensor.3d.shared::cluster.global.mbarrier::complete_tx::bytes.L2::cache_hint [%0], [%1, {%6, %3, %4}], [%2], %5;"
    :: "r"(dst), "l"(map), "r"(bar), "r"(c1), "r"(c2), "l"(pol), "r"(0) : "memory");
}
__device__ __forceinline__ void tma_store_2d(const CUtensorMap* map, uint32_t src, int c0, int c1) {
  asm volatile("cp.async.bulk.tensor.2d.global.shared::cta.bulk_group [%0, {%2, %3}], [%1];" :: "l"(map), "r"(src), "r"(c0), "r"(c1) : "memory");
}
__device__ __forceinline__ void prefetch_tmap(const CUtensorMap* map) { asm volatile("prefetch.tensormap [%0];" :: "l"(map) : "memory"); }
__device__ __forceinline__ void l2_prefetch_bulk(const void* p, uint32_t bytes) {
  asm volatile("cp.async.bulk.prefetch.L2.global [%0], %1;" :: "l"(p), "r"(bytes) : "memory");
}
__device__ __forceinline__ void bulk_commit() { asm volatile("cp.async.bulk.commit_group;" ::: "memory"); }
template<int N> __device__ __forceinline__ void bulk_wait_read() { asm volatile("cp.async.bulk.wait_group.read %0;" :: "n"(N) : "memory"); }
template<int N> __device__ __forceinline__ void bulk_wait() { asm volatile("cp.async.bulk.wait_group %0;" :: "n"(N) : "memory"); }
__device__ __forceinline__ void named_bar_sync(int id, int nthreads) { asm volatile("bar.sync %0, %1;" :: "r"(id), "r"(nthreads) : "memory"); }
__device__ __forceinline__ void named_bar_arrive(int id, int nthreads) { asm volatile("bar.arrive %0, %1;" :: "r"(id), "r"(nthreads) : "memory"); }
__device__ __forceinline__ void wgmma_fence() { asm volatile("wgmma.fence.sync.aligned;" ::: "memory"); }
__device__ __forceinline__ void wgmma_commit() { asm volatile("wgmma.commit_group.sync.aligned;" ::: "memory"); }
template<int N> __device__ __forceinline__ void wgmma_wait() { asm volatile("wgmma.wait_group.sync.aligned %0;" :: "n"(N) : "memory"); }
template<int R> __device__ __forceinline__ void reg_alloc() { asm volatile("setmaxnreg.inc.sync.aligned.u32 %0;" :: "n"(R)); }
template<int R> __device__ __forceinline__ void reg_dealloc() { asm volatile("setmaxnreg.dec.sync.aligned.u32 %0;" :: "n"(R)); }
__device__ __forceinline__ bool elect_one() {
  uint32_t pred; asm volatile("{\n.reg .pred p;\nelect.sync _|p, 0xffffffff;\nselp.u32 %0, 1, 0, p;\n}\n" : "=r"(pred)); return pred != 0;
}
__device__ __forceinline__ uint32_t pack_bf16(float lo, float hi) {
  uint32_t r; asm("cvt.rn.bf16x2.f32 %0, %1, %2;" : "=r"(r) : "f"(hi), "f"(lo)); return r;
}
__device__ __forceinline__ void stmatrix_x4(uint32_t addr, uint32_t r0, uint32_t r1, uint32_t r2, uint32_t r3) {
  asm volatile("stmatrix.sync.aligned.m8n8.x4.shared.b16 [%0], {%1, %2, %3, %4};" :: "r"(addr), "r"(r0), "r"(r1), "r"(r2), "r"(r3) : "memory");
}
__device__ __forceinline__ void fence_proxy_async() { asm volatile("fence.proxy.async.shared::cta;" ::: "memory"); }
__device__ __forceinline__ float ex2_approx(float x) { float y; asm("ex2.approx.ftz.f32 %0, %1;" : "=f"(y) : "f"(x)); return y; }
template<int N> __device__ __forceinline__ void fence_regs(float (&r)[N]) {
  #pragma unroll
  for (int i = 0; i < N; i++) asm volatile("" : "+f"(r[i]) :: "memory");
}
template<int N> __device__ __forceinline__ void zero_regs(float (&r)[N]) {
  #pragma unroll
  for (int i = 0; i < N; i += 2) asm volatile("mov.b64 {%0, %1}, 0;" : "=f"(r[i]), "=f"(r[i + 1]));
}
__device__ __forceinline__ float rbf(float x) { return __uint_as_float(pack_bf16(0.f, x)); }
__device__ __forceinline__ float bflo(uint32_t v) { return __uint_as_float(v << 16); }
__device__ __forceinline__ float bfhi(uint32_t v) { return __uint_as_float(v & 0xffff0000u); }

#define TL_START(k) do {} while (0)
#define TL_END(k, cond) do {} while (0)
#define TL_CTA(i, cond) do {} while (0)
#define FS(slot, k) do {} while (0)
#define QS(idx) do {} while (0)
#define QDUMP() do {} while (0)
#define TL_MARK2(k, cond) do {} while (0)
#define TL_CLK(k, i, cond) do {} while (0)

#define HS(k) do {} while (0)
#define HSD(k, dep) do {} while (0)
#define HSDUMP() do {} while (0)
#define PS(k, cond) do {} while (0)
#define PSV(k, cond, v) do {} while (0)
#define PF(k) do {} while (0)
#define TS(k, cond) do {} while (0)
template <int OFFA, int OFFB>
__device__ __forceinline__ void wgmma_m64n256k16_ss_tb(float (&d)[128], uint32_t a_lo, uint32_t b_lo, int scaleD) {
  asm volatile("{\n.reg .pred p;\n.reg .b32 ta, tb;\n.reg .b64 da, db;\nsetp.ne.b32 p, %130, 0;\n"
    "add.u32 ta, %128, %131;\nadd.u32 tb, %129, %132;\n"
    "mov.b64 da, {ta, 0x40000040};\nmov.b64 db, {tb, 0x40000040};\n"
    "wgmma.mma_async.sync.aligned.m64n256k16.f32.bf16.bf16 "
    "{%0, %1, %2, %3, %4, %5, %6, %7, %8, %9, %10, %11, %12, %13, %14, %15, %16, %17, %18, %19, %20, %21, %22, %23, %24, %25, %26, %27, %28, %29, %30, %31, %32, %33, %34, %35, %36, %37, %38, %39, %40, %41, %42, %43, %44, %45, %46, %47, %48, %49, %50, %51, %52, %53, %54, %55, %56, %57, %58, %59, %60, %61, %62, %63, %64, %65, %66, %67, %68, %69, %70, %71, %72, %73, %74, %75, %76, %77, %78, %79, %80, %81, %82, %83, %84, %85, %86, %87, %88, %89, %90, %91, %92, %93, %94, %95, %96, %97, %98, %99, %100, %101, %102, %103, %104, %105, %106, %107, %108, %109, %110, %111, %112, %113, %114, %115, %116, %117, %118, %119, %120, %121, %122, %123, %124, %125, %126, %127}, "
    "da, db, p, 1, 1, 0, 1;\n}\n"
    : "+f"(d[0]), "+f"(d[1]), "+f"(d[2]), "+f"(d[3]), "+f"(d[4]), "+f"(d[5]), "+f"(d[6]), "+f"(d[7]), "+f"(d[8]), "+f"(d[9]), "+f"(d[10]), "+f"(d[11]), "+f"(d[12]), "+f"(d[13]), "+f"(d[14]), "+f"(d[15]), "+f"(d[16]), "+f"(d[17]), "+f"(d[18]), "+f"(d[19]), "+f"(d[20]), "+f"(d[21]), "+f"(d[22]), "+f"(d[23]), "+f"(d[24]), "+f"(d[25]), "+f"(d[26]), "+f"(d[27]), "+f"(d[28]), "+f"(d[29]), "+f"(d[30]), "+f"(d[31]), "+f"(d[32]), "+f"(d[33]), "+f"(d[34]), "+f"(d[35]), "+f"(d[36]), "+f"(d[37]), "+f"(d[38]), "+f"(d[39]), "+f"(d[40]), "+f"(d[41]), "+f"(d[42]), "+f"(d[43]), "+f"(d[44]), "+f"(d[45]), "+f"(d[46]), "+f"(d[47]), "+f"(d[48]), "+f"(d[49]), "+f"(d[50]), "+f"(d[51]), "+f"(d[52]), "+f"(d[53]), "+f"(d[54]), "+f"(d[55]), "+f"(d[56]), "+f"(d[57]), "+f"(d[58]), "+f"(d[59]), "+f"(d[60]), "+f"(d[61]), "+f"(d[62]), "+f"(d[63]), "+f"(d[64]), "+f"(d[65]), "+f"(d[66]), "+f"(d[67]), "+f"(d[68]), "+f"(d[69]), "+f"(d[70]), "+f"(d[71]), "+f"(d[72]), "+f"(d[73]), "+f"(d[74]), "+f"(d[75]), "+f"(d[76]), "+f"(d[77]), "+f"(d[78]), "+f"(d[79]), "+f"(d[80]), "+f"(d[81]), "+f"(d[82]), "+f"(d[83]), "+f"(d[84]), "+f"(d[85]), "+f"(d[86]), "+f"(d[87]), "+f"(d[88]), "+f"(d[89]), "+f"(d[90]), "+f"(d[91]), "+f"(d[92]), "+f"(d[93]), "+f"(d[94]), "+f"(d[95]), "+f"(d[96]), "+f"(d[97]), "+f"(d[98]), "+f"(d[99]), "+f"(d[100]), "+f"(d[101]), "+f"(d[102]), "+f"(d[103]), "+f"(d[104]), "+f"(d[105]), "+f"(d[106]), "+f"(d[107]), "+f"(d[108]), "+f"(d[109]), "+f"(d[110]), "+f"(d[111]), "+f"(d[112]), "+f"(d[113]), "+f"(d[114]), "+f"(d[115]), "+f"(d[116]), "+f"(d[117]), "+f"(d[118]), "+f"(d[119]), "+f"(d[120]), "+f"(d[121]), "+f"(d[122]), "+f"(d[123]), "+f"(d[124]), "+f"(d[125]), "+f"(d[126]), "+f"(d[127])
    : "r"(a_lo), "r"(b_lo), "r"(scaleD), "n"(OFFA), "n"(OFFB));
}

template <int OFFA, int OFFB>
__device__ __forceinline__ void wgmma_m64n128k16_ss_tb(float (&d)[64], uint32_t a_lo, uint32_t b_lo, int scaleD) {
  asm volatile("{\n.reg .pred p;\n.reg .b32 ta, tb;\n.reg .b64 da, db;\nsetp.ne.b32 p, %66, 0;\n"
    "add.u32 ta, %64, %67;\nadd.u32 tb, %65, %68;\n"
    "mov.b64 da, {ta, 0x40000040};\nmov.b64 db, {tb, 0x40000040};\n"
    "wgmma.mma_async.sync.aligned.m64n128k16.f32.bf16.bf16 "
    "{%0, %1, %2, %3, %4, %5, %6, %7, %8, %9, %10, %11, %12, %13, %14, %15, %16, %17, %18, %19, %20, %21, %22, %23, %24, %25, %26, %27, %28, %29, %30, %31, %32, %33, %34, %35, %36, %37, %38, %39, %40, %41, %42, %43, %44, %45, %46, %47, %48, %49, %50, %51, %52, %53, %54, %55, %56, %57, %58, %59, %60, %61, %62, %63}, "
    "da, db, p, 1, 1, 0, 1;\n}\n"
    : "+f"(d[0]), "+f"(d[1]), "+f"(d[2]), "+f"(d[3]), "+f"(d[4]), "+f"(d[5]), "+f"(d[6]), "+f"(d[7]), "+f"(d[8]), "+f"(d[9]), "+f"(d[10]), "+f"(d[11]), "+f"(d[12]), "+f"(d[13]), "+f"(d[14]), "+f"(d[15]), "+f"(d[16]), "+f"(d[17]), "+f"(d[18]), "+f"(d[19]), "+f"(d[20]), "+f"(d[21]), "+f"(d[22]), "+f"(d[23]), "+f"(d[24]), "+f"(d[25]), "+f"(d[26]), "+f"(d[27]), "+f"(d[28]), "+f"(d[29]), "+f"(d[30]), "+f"(d[31]), "+f"(d[32]), "+f"(d[33]), "+f"(d[34]), "+f"(d[35]), "+f"(d[36]), "+f"(d[37]), "+f"(d[38]), "+f"(d[39]), "+f"(d[40]), "+f"(d[41]), "+f"(d[42]), "+f"(d[43]), "+f"(d[44]), "+f"(d[45]), "+f"(d[46]), "+f"(d[47]), "+f"(d[48]), "+f"(d[49]), "+f"(d[50]), "+f"(d[51]), "+f"(d[52]), "+f"(d[53]), "+f"(d[54]), "+f"(d[55]), "+f"(d[56]), "+f"(d[57]), "+f"(d[58]), "+f"(d[59]), "+f"(d[60]), "+f"(d[61]), "+f"(d[62]), "+f"(d[63])
    : "r"(a_lo), "r"(b_lo), "r"(scaleD), "n"(OFFA), "n"(OFFB));
}

template <int OFFB>
__device__ __forceinline__ void wgmma_m64n256k16_rs_tb(float (&d)[128], uint32_t a0, uint32_t a1, uint32_t a2, uint32_t a3, uint32_t b_lo, int scaleD) {
  asm volatile("{\n.reg .pred p;\n.reg .b32 tb;\n.reg .b64 db;\nsetp.ne.b32 p, %133, 0;\n"
    "add.u32 tb, %132, %134;\n"
    "mov.b64 db, {tb, 0x40000040};\n"
    "wgmma.mma_async.sync.aligned.m64n256k16.f32.bf16.bf16 "
    "{%0, %1, %2, %3, %4, %5, %6, %7, %8, %9, %10, %11, %12, %13, %14, %15, %16, %17, %18, %19, %20, %21, %22, %23, %24, %25, %26, %27, %28, %29, %30, %31, %32, %33, %34, %35, %36, %37, %38, %39, %40, %41, %42, %43, %44, %45, %46, %47, %48, %49, %50, %51, %52, %53, %54, %55, %56, %57, %58, %59, %60, %61, %62, %63, %64, %65, %66, %67, %68, %69, %70, %71, %72, %73, %74, %75, %76, %77, %78, %79, %80, %81, %82, %83, %84, %85, %86, %87, %88, %89, %90, %91, %92, %93, %94, %95, %96, %97, %98, %99, %100, %101, %102, %103, %104, %105, %106, %107, %108, %109, %110, %111, %112, %113, %114, %115, %116, %117, %118, %119, %120, %121, %122, %123, %124, %125, %126, %127}, "
    "{%128, %129, %130, %131}, db, p, 1, 1, 1;\n}\n"
    : "+f"(d[0]), "+f"(d[1]), "+f"(d[2]), "+f"(d[3]), "+f"(d[4]), "+f"(d[5]), "+f"(d[6]), "+f"(d[7]), "+f"(d[8]), "+f"(d[9]), "+f"(d[10]), "+f"(d[11]), "+f"(d[12]), "+f"(d[13]), "+f"(d[14]), "+f"(d[15]), "+f"(d[16]), "+f"(d[17]), "+f"(d[18]), "+f"(d[19]), "+f"(d[20]), "+f"(d[21]), "+f"(d[22]), "+f"(d[23]), "+f"(d[24]), "+f"(d[25]), "+f"(d[26]), "+f"(d[27]), "+f"(d[28]), "+f"(d[29]), "+f"(d[30]), "+f"(d[31]), "+f"(d[32]), "+f"(d[33]), "+f"(d[34]), "+f"(d[35]), "+f"(d[36]), "+f"(d[37]), "+f"(d[38]), "+f"(d[39]), "+f"(d[40]), "+f"(d[41]), "+f"(d[42]), "+f"(d[43]), "+f"(d[44]), "+f"(d[45]), "+f"(d[46]), "+f"(d[47]), "+f"(d[48]), "+f"(d[49]), "+f"(d[50]), "+f"(d[51]), "+f"(d[52]), "+f"(d[53]), "+f"(d[54]), "+f"(d[55]), "+f"(d[56]), "+f"(d[57]), "+f"(d[58]), "+f"(d[59]), "+f"(d[60]), "+f"(d[61]), "+f"(d[62]), "+f"(d[63]), "+f"(d[64]), "+f"(d[65]), "+f"(d[66]), "+f"(d[67]), "+f"(d[68]), "+f"(d[69]), "+f"(d[70]), "+f"(d[71]), "+f"(d[72]), "+f"(d[73]), "+f"(d[74]), "+f"(d[75]), "+f"(d[76]), "+f"(d[77]), "+f"(d[78]), "+f"(d[79]), "+f"(d[80]), "+f"(d[81]), "+f"(d[82]), "+f"(d[83]), "+f"(d[84]), "+f"(d[85]), "+f"(d[86]), "+f"(d[87]), "+f"(d[88]), "+f"(d[89]), "+f"(d[90]), "+f"(d[91]), "+f"(d[92]), "+f"(d[93]), "+f"(d[94]), "+f"(d[95]), "+f"(d[96]), "+f"(d[97]), "+f"(d[98]), "+f"(d[99]), "+f"(d[100]), "+f"(d[101]), "+f"(d[102]), "+f"(d[103]), "+f"(d[104]), "+f"(d[105]), "+f"(d[106]), "+f"(d[107]), "+f"(d[108]), "+f"(d[109]), "+f"(d[110]), "+f"(d[111]), "+f"(d[112]), "+f"(d[113]), "+f"(d[114]), "+f"(d[115]), "+f"(d[116]), "+f"(d[117]), "+f"(d[118]), "+f"(d[119]), "+f"(d[120]), "+f"(d[121]), "+f"(d[122]), "+f"(d[123]), "+f"(d[124]), "+f"(d[125]), "+f"(d[126]), "+f"(d[127])
    : "r"(a0), "r"(a1), "r"(a2), "r"(a3), "r"(b_lo), "r"(scaleD), "n"(OFFB));
}

template <int OFFB>
__device__ __forceinline__ void wgmma_m64n128k16_rs_tb(float (&d)[64], uint32_t a0, uint32_t a1, uint32_t a2, uint32_t a3, uint32_t b_lo, int scaleD) {
  asm volatile("{\n.reg .pred p;\n.reg .b32 tb;\n.reg .b64 db;\nsetp.ne.b32 p, %69, 0;\n"
    "add.u32 tb, %68, %70;\n"
    "mov.b64 db, {tb, 0x40000040};\n"
    "wgmma.mma_async.sync.aligned.m64n128k16.f32.bf16.bf16 "
    "{%0, %1, %2, %3, %4, %5, %6, %7, %8, %9, %10, %11, %12, %13, %14, %15, %16, %17, %18, %19, %20, %21, %22, %23, %24, %25, %26, %27, %28, %29, %30, %31, %32, %33, %34, %35, %36, %37, %38, %39, %40, %41, %42, %43, %44, %45, %46, %47, %48, %49, %50, %51, %52, %53, %54, %55, %56, %57, %58, %59, %60, %61, %62, %63}, "
    "{%64, %65, %66, %67}, db, p, 1, 1, 1;\n}\n"
    : "+f"(d[0]), "+f"(d[1]), "+f"(d[2]), "+f"(d[3]), "+f"(d[4]), "+f"(d[5]), "+f"(d[6]), "+f"(d[7]), "+f"(d[8]), "+f"(d[9]), "+f"(d[10]), "+f"(d[11]), "+f"(d[12]), "+f"(d[13]), "+f"(d[14]), "+f"(d[15]), "+f"(d[16]), "+f"(d[17]), "+f"(d[18]), "+f"(d[19]), "+f"(d[20]), "+f"(d[21]), "+f"(d[22]), "+f"(d[23]), "+f"(d[24]), "+f"(d[25]), "+f"(d[26]), "+f"(d[27]), "+f"(d[28]), "+f"(d[29]), "+f"(d[30]), "+f"(d[31]), "+f"(d[32]), "+f"(d[33]), "+f"(d[34]), "+f"(d[35]), "+f"(d[36]), "+f"(d[37]), "+f"(d[38]), "+f"(d[39]), "+f"(d[40]), "+f"(d[41]), "+f"(d[42]), "+f"(d[43]), "+f"(d[44]), "+f"(d[45]), "+f"(d[46]), "+f"(d[47]), "+f"(d[48]), "+f"(d[49]), "+f"(d[50]), "+f"(d[51]), "+f"(d[52]), "+f"(d[53]), "+f"(d[54]), "+f"(d[55]), "+f"(d[56]), "+f"(d[57]), "+f"(d[58]), "+f"(d[59]), "+f"(d[60]), "+f"(d[61]), "+f"(d[62]), "+f"(d[63])
    : "r"(a0), "r"(a1), "r"(a2), "r"(a3), "r"(b_lo), "r"(scaleD), "n"(OFFB));
}

template <int OFFB>
__device__ __forceinline__ void wgmma_m64n128k16_rs(float (&d)[64], uint32_t a0, uint32_t a1, uint32_t a2, uint32_t a3, uint32_t b_lo, int scaleD) {
  asm volatile("{\n.reg .pred p;\n.reg .b32 tb;\n.reg .b64 db;\nsetp.ne.b32 p, %69, 0;\n"
    "add.u32 tb, %68, %70;\n"
    "mov.b64 db, {tb, 0x40000040};\n"
    "wgmma.mma_async.sync.aligned.m64n128k16.f32.bf16.bf16 "
    "{%0, %1, %2, %3, %4, %5, %6, %7, %8, %9, %10, %11, %12, %13, %14, %15, %16, %17, %18, %19, %20, %21, %22, %23, %24, %25, %26, %27, %28, %29, %30, %31, %32, %33, %34, %35, %36, %37, %38, %39, %40, %41, %42, %43, %44, %45, %46, %47, %48, %49, %50, %51, %52, %53, %54, %55, %56, %57, %58, %59, %60, %61, %62, %63}, "
    "{%64, %65, %66, %67}, db, p, 1, 1, 0;\n}\n"
    : "+f"(d[0]), "+f"(d[1]), "+f"(d[2]), "+f"(d[3]), "+f"(d[4]), "+f"(d[5]), "+f"(d[6]), "+f"(d[7]), "+f"(d[8]), "+f"(d[9]), "+f"(d[10]), "+f"(d[11]), "+f"(d[12]), "+f"(d[13]), "+f"(d[14]), "+f"(d[15]), "+f"(d[16]), "+f"(d[17]), "+f"(d[18]), "+f"(d[19]), "+f"(d[20]), "+f"(d[21]), "+f"(d[22]), "+f"(d[23]), "+f"(d[24]), "+f"(d[25]), "+f"(d[26]), "+f"(d[27]), "+f"(d[28]), "+f"(d[29]), "+f"(d[30]), "+f"(d[31]), "+f"(d[32]), "+f"(d[33]), "+f"(d[34]), "+f"(d[35]), "+f"(d[36]), "+f"(d[37]), "+f"(d[38]), "+f"(d[39]), "+f"(d[40]), "+f"(d[41]), "+f"(d[42]), "+f"(d[43]), "+f"(d[44]), "+f"(d[45]), "+f"(d[46]), "+f"(d[47]), "+f"(d[48]), "+f"(d[49]), "+f"(d[50]), "+f"(d[51]), "+f"(d[52]), "+f"(d[53]), "+f"(d[54]), "+f"(d[55]), "+f"(d[56]), "+f"(d[57]), "+f"(d[58]), "+f"(d[59]), "+f"(d[60]), "+f"(d[61]), "+f"(d[62]), "+f"(d[63])
    : "r"(a0), "r"(a1), "r"(a2), "r"(a3), "r"(b_lo), "r"(scaleD), "n"(OFFB));
}

__device__ __forceinline__ uint4 ldg_nc_v4(const void* p) {
  uint4 v;
    asm volatile("{\n.reg .b64 pol;\ncreatepolicy.fractional.L2::evict_first.b64 pol, 1.0;\n"
                 "ld.global.nc.L1::no_allocate.L2::cache_hint.v4.u32 {%0, %1, %2, %3}, [%4], pol;\n}\n" : "=r"(v.x), "=r"(v.y), "=r"(v.z), "=r"(v.w) : "l"(p));
  return v;
}
__device__ __forceinline__ uint64_t pol_normal() {
  uint64_t p; asm volatile("createpolicy.fractional.L2::evict_normal.b64 %0, 1.0;" : "=l"(p)); return p;
}
__device__ __forceinline__ float rcp_approx(float x) { float y; asm("rcp.approx.ftz.f32 %0, %1;" : "=f"(y) : "f"(x)); return y; }
__device__ __forceinline__ float sigmoid_f(float v) { return rcp_approx(1.0f + ex2_approx(v * -1.4426950408889634f)); }
__device__ __forceinline__ float silu_bf(float v) { return rbf(v * sigmoid_f(v)); }
__device__ __forceinline__ uint32_t rank_key(float r, int idx) {
  const uint32_t b = __float_as_uint(r) >> 16;
  const uint32_t u = (r != r) ? 0u : ((b & 0x8000u) ? (~b & 0xffffu) : (b | 0x8000u));
  return (u << 16) | (0xffffu - (uint32_t)idx);
}
__device__ __forceinline__ void warp_top2(uint32_t& k1, uint32_t& k2) {
  const uint32_t m1 = __reduce_max_sync(0xffffffffu, k1);
  k2 = __reduce_max_sync(0xffffffffu, k1 == m1 ? k2 : k1);
  k1 = m1;
}
__device__ __forceinline__ uint32_t bmul2(uint32_t a, uint32_t b) { uint32_t r; asm("mul.rn.bf16x2 %0, %1, %2;" : "=r"(r) : "r"(a), "r"(b)); return r; }
__device__ __forceinline__ uint32_t badd2(uint32_t a, uint32_t b) { uint32_t r; asm("add.rn.bf16x2 %0, %1, %2;" : "=r"(r) : "r"(a), "r"(b)); return r; }
__device__ __forceinline__ uint32_t bsub2(uint32_t a, uint32_t b) { uint32_t r; asm("sub.rn.bf16x2 %0, %1, %2;" : "=r"(r) : "r"(a), "r"(b)); return r; }
__device__ __forceinline__ float sqrt_approx(float x) { float y; asm("sqrt.approx.f32 %0, %1;" : "=f"(y) : "f"(x)); return y; }
__device__ __forceinline__ uint32_t ln_norm2(uint32_t x1, uint32_t mb2, float inv) {
  const uint32_t d = bsub2(x1, mb2);
  return pack_bf16(bflo(d) * inv, bfhi(d) * inv);
}
__device__ __forceinline__ uint32_t ln_mod2(uint32_t x1, uint32_t mb2, float inv, uint32_t c1, uint32_t sb) { return badd2(bmul2(ln_norm2(x1, mb2, inv), c1), sb); }
__device__ __forceinline__ void ldmatrix_x4(uint32_t addr, uint32_t& r0, uint32_t& r1, uint32_t& r2, uint32_t& r3) {
  asm volatile("ldmatrix.sync.aligned.m8n8.x4.shared.b16 {%0, %1, %2, %3}, [%4];" : "=r"(r0), "=r"(r1), "=r"(r2), "=r"(r3) : "r"(addr) : "memory");
}
__device__ __forceinline__ uint4 ldg_stream_v4(const void* p, uint64_t pol) {
  uint4 v; asm volatile("ld.global.nc.L1::no_allocate.L2::cache_hint.L2::128B.v4.u32 {%0, %1, %2, %3}, [%4], %5;" : "=r"(v.x), "=r"(v.y), "=r"(v.z), "=r"(v.w) : "l"(p), "l"(pol)); return v;
}
__device__ __forceinline__ void bulk_load_hint(uint32_t dst, const void* src, uint32_t bytes, uint32_t bar, uint64_t pol) {
  asm volatile("cp.async.bulk.shared::cluster.global.mbarrier::complete_tx::bytes.L2::cache_hint [%0], [%1], %2, [%3], %4;"
    :: "r"(dst), "l"(src), "r"(bytes), "r"(bar), "l"(pol) : "memory");
}
__device__ __forceinline__ void red_release_add(unsigned int* p, unsigned int v) { asm volatile("red.release.gpu.global.add.u32 [%0], %1;" :: "l"(p), "r"(v) : "memory"); }
__device__ __forceinline__ unsigned int ld_acquire(const unsigned int* p) { unsigned int v; asm volatile("ld.acquire.gpu.global.u32 %0, [%1];" : "=r"(v) : "l"(p) : "memory"); return v; }
__device__ __forceinline__ void spin_until(const unsigned int* p, unsigned int target) {
  #pragma unroll 1
  for (unsigned int i = 0; i < (1u << 22); i++) { if (ld_acquire(p) >= target) return; }
}
__device__ __forceinline__ float lds_f32(uint32_t a) { float v; asm volatile("ld.shared.f32 %0, [%1];" : "=f"(v) : "r"(a) : "memory"); return v; }
__device__ __forceinline__ uint2 lds_u32x2(uint32_t a) { uint2 v; asm volatile("ld.shared.v2.u32 {%0, %1}, [%2];" : "=r"(v.x), "=r"(v.y) : "r"(a) : "memory"); return v; }
__device__ __forceinline__ uint32_t lds_u32(uint32_t a) { uint32_t v; asm volatile("ld.shared.u32 %0, [%1];" : "=r"(v) : "r"(a) : "memory"); return v; }
__device__ __forceinline__ void sts_u32(uint32_t a, uint32_t v) { asm volatile("st.shared.u32 [%0], %1;" :: "r"(a), "r"(v) : "memory"); }
__device__ __forceinline__ void sts_u32x2(uint32_t a, uint32_t x, uint32_t y) { asm volatile("st.shared.v2.u32 [%0], {%1, %2};" :: "r"(a), "r"(x), "r"(y) : "memory"); }
__device__ __forceinline__ void sts_f32(uint32_t a, float v) { asm volatile("st.shared.f32 [%0], %1;" :: "r"(a), "f"(v) : "memory"); }
__device__ __forceinline__ void sts_f32x4(uint32_t a, float x, float y, float z, float w) { asm volatile("st.shared.v4.f32 [%0], {%1, %2, %3, %4};" :: "r"(a), "f"(x), "f"(y), "f"(z), "f"(w) : "memory"); }

__device__ __forceinline__ uint4 lds_u32x4(uint32_t a) { uint4 v; asm volatile("ld.shared.v4.u32 {%0, %1, %2, %3}, [%4];" : "=r"(v.x), "=r"(v.y), "=r"(v.z), "=r"(v.w) : "r"(a) : "memory"); return v; }
__device__ __forceinline__ void sts_u32x4(uint32_t a, uint32_t x, uint32_t y, uint32_t z, uint32_t w) { asm volatile("st.shared.v4.u32 [%0], {%1, %2, %3, %4};" :: "r"(a), "r"(x), "r"(y), "r"(z), "r"(w) : "memory"); }
__device__ __forceinline__ void st_tagged(float* p, float v) {
  const uint32_t b = __float_as_uint(v);
  asm volatile("st.relaxed.gpu.global.u32 [%0], %1;" :: "l"(p), "r"(b == 0u ? 0x80000000u : b) : "memory");
}
__device__ __forceinline__ void st_tagged4(float* p, float x, float y, float z, float w) {
  const uint32_t a = __float_as_uint(x), b = __float_as_uint(y), c = __float_as_uint(z), d = __float_as_uint(w);
  asm volatile("st.relaxed.gpu.global.v4.u32 [%0], {%1, %2, %3, %4};" :: "l"(p), "r"(a == 0u ? 0x80000000u : a), "r"(b == 0u ? 0x80000000u : b),
               "r"(c == 0u ? 0x80000000u : c), "r"(d == 0u ? 0x80000000u : d) : "memory");
}
__device__ __forceinline__ void st_relaxed2(void* p, uint32_t a, uint32_t b) { asm volatile("st.relaxed.gpu.global.v2.u32 [%0], {%1, %2};" :: "l"(p), "r"(a), "r"(b) : "memory"); }
__device__ __forceinline__ float4 ld_tagged4(const float* p) {
  float4 v; asm volatile("ld.relaxed.gpu.global.v4.f32 {%0, %1, %2, %3}, [%4];" : "=f"(v.x), "=f"(v.y), "=f"(v.z), "=f"(v.w) : "l"(p) : "memory"); return v;
}
__device__ __forceinline__ bool tagged4(const float4& v) {
  return __float_as_uint(v.x) != 0u && __float_as_uint(v.y) != 0u && __float_as_uint(v.z) != 0u && __float_as_uint(v.w) != 0u;
}
__device__ __forceinline__ void hint_arrive(uint32_t* p) { asm volatile("red.relaxed.gpu.global.add.u32 [%0], 1;" :: "l"(p) : "memory"); }
__device__ __forceinline__ void hint_wait(const uint32_t* p, uint32_t target) {
  uint32_t v = 0u;
  #pragma unroll 1
  for (unsigned int i = 0; i < (1u << 22) && v < target; i++) asm volatile("ld.relaxed.gpu.global.u32 %0, [%1];" : "=r"(v) : "l"(p) : "memory");
}
__device__ __forceinline__ void fence_proxy_async_global() { asm volatile("fence.proxy.async.global;" ::: "memory"); }

__device__ __forceinline__ void mma_bf16(float (&d)[4], uint32_t a0, uint32_t a1, uint32_t a2, uint32_t a3, uint32_t b0, uint32_t b1) {
  asm volatile("mma.sync.aligned.m16n8k16.row.col.f32.bf16.bf16.f32 {%0, %1, %2, %3}, {%4, %5, %6, %7}, {%8, %9}, {%0, %1, %2, %3};"
               : "+f"(d[0]), "+f"(d[1]), "+f"(d[2]), "+f"(d[3]) : "r"(a0), "r"(a1), "r"(a2), "r"(a3), "r"(b0), "r"(b1));
}
__device__ __forceinline__ uint32_t bfma2(uint32_t a, uint32_t b, uint32_t c) { uint32_t r; asm("fma.rn.bf16x2 %0, %1, %2, %3;" : "=r"(r) : "r"(a), "r"(b), "r"(c)); return r; }
#define PRE_T 1000
#define WDLY 3800
#define GDLY 4150
#define GDLY2 8000
#define ST1_T 6000
#define A_T 4800
#define QT0 0
#define QTO 0
#define QTN 0
#define QARR 4
#define WCH 4
#define QORD 0
#define PACE 128
#define EREL 0
#define EA0 1
#define PINQ 1
#define PINS 0
#define SYN_G 0
#define SYN_S 2
#define GSLP 50
#define DROPN 2
#define SERP 1
#define DYN 1
#define ASLP 200
#define CPCM 1
#define ZMMA 0
#define LATEF 0
#define CLR_T 70000
#define H_T 30000
#ifndef M_T
#define M_T 93000
#endif
#ifndef M_SLP
#define M_SLP 0
#endif
#define SGL_T 82000
#define XPOL 1
#define HST 1
#define TPRE 2
#define SGL_INL __noinline__
#define STW_INL __forceinline__
#define W_GAP 300
#define W_LATE 27000
#define HB 0
#define RSO 0
#define W_OFF 2000
#define W_RND 3600
#define NDUM 16
#define XDLY 1000
#define SDLY 5800
#define EPOLL 1
__device__ __forceinline__ uint32_t clock_lo() { uint32_t c; asm volatile("mov.u32 %0, %%clock;" : "=r"(c) :: "memory"); return c; }
__device__ __forceinline__ void wait_clock(uint32_t t0, uint32_t n) {
  #pragma unroll 1
  while (clock_lo() - t0 < n) {}
}
__device__ __forceinline__ void sleep_until(uint32_t t0, uint32_t n) {
  #pragma unroll 1
  while (clock_lo() - t0 < n) __nanosleep(500);
}
__device__ __forceinline__ float2 ld_tagged2(const float2* p) {
  float2 v; asm volatile("ld.relaxed.gpu.global.v2.f32 {%0, %1}, [%2];" : "=f"(v.x), "=f"(v.y) : "l"(p) : "memory"); return v;
}
template <int N>
__device__ __forceinline__ void gemv64(float (&d)[2][4], const uint4 (&w)[N], const uint32_t (&sv)[N / 2], int lane) {
  const int g = lane >> 2;
  const uint32_t lo = (g & 1) ? 0x1044u : 0x4410u, hi = (g & 1) ? 0x3244u : 0x4432u;
  const uint32_t lo0 = g < 2 ? lo : 0x4444u, hi0 = g < 2 ? hi : 0x4444u, lo1 = (g & 6) == 2 ? lo : 0x4444u, hi1 = (g & 6) == 2 ? hi : 0x4444u;
  #pragma unroll
  for (int i = 0; i < N; i++)
    mma_bf16(d[i & 1], w[i].x, w[i].y, w[i].z, w[i].w, __byte_perm(sv[i >> 1], 0u, (i & 1) ? hi0 : lo0), __byte_perm(sv[i >> 1], 0u, (i & 1) ? hi1 : lo1));
}
template <int NW>
__device__ __forceinline__ float gemv64_sum(const float (&d)[2][4], uint32_t scr, int t2) {
  if ((t2 & 2) == 0) sts_f32x4(scr + (t2 >> 2) * 32 + (t2 & 1) * 16, d[0][0] + d[1][0], d[0][1] + d[1][1], d[0][2] + d[1][2], d[0][3] + d[1][3]);
  named_bar_sync(NW == 8 ? 5 : 3, NW * 32);
  float sum = 0.f;
  #pragma unroll
  for (int i = 0; i < NW; i += 2) sum += lds_f32(scr + i * 256 + (t2 & 63) * 4) + lds_f32(scr + i * 256 + 256 + (t2 & 63) * 4);
  return sum;
}
__device__ __forceinline__ uint32_t silu2(uint32_t c) { return pack_bf16(silu_bf(bflo(c)), silu_bf(bfhi(c))); }
__device__ __forceinline__ void head_first(Scratch* hm, uint32_t scr, int t2, const bf16* __restrict__ cvec, const bf16* __restrict__ w_mod) {
  const int row = (blockIdx.x >> 3) * 64 + (t2 >> 5) * 16 + (t2 & 3) * 4;
  const bf16* wp = w_mod + (size_t)row * (6 * T_D) + (blockIdx.x & 4) * 256 + (blockIdx.x & 3) * 64 + (t2 & 28) * 2;
  uint4 w[4];
  #pragma unroll
  for (int i = 0; i < 4; i++) w[i] = ldg_nc_v4(wp + i * 6 * T_D);
  const uint2 c = *reinterpret_cast<const uint2*>(cvec + row);
  const uint32_t sv[2] = {silu2(c.x), silu2(c.y)};
  float d[2][4] = {{0.f, 0.f, 0.f, 0.f}, {0.f, 0.f, 0.f, 0.f}};
  gemv64<4>(d, w, sv, t2 & 31);
  const float sum = gemv64_sum<4>(d, scr, t2);
  if (t2 < 64) st_tagged(hm->modu + (blockIdx.x >> 3) * 512 + (blockIdx.x & 7) * 64 + t2, sum);
  HS(1);
}
__device__ __forceinline__ void head_stats(Scratch* hm, uint32_t xs, uint32_t b_x, int tid) {
  const int lane = tid & 31, w = tid >> 5, g = lane >> 2;
  float d[4][4] = {{0.f, 0.f, 0.f, 0.f}, {0.f, 0.f, 0.f, 0.f}, {0.f, 0.f, 0.f, 0.f}, {0.f, 0.f, 0.f, 0.f}};
  const uint32_t xa = xs + ((w & 1) * 8 + g) * 2048 + (w >> 1) * 1024 + (g & 1) * 64 + (lane & 3) * 16;
  float2* dst = hm->stat + ((blockIdx.x * 2 + (w & 1)) * 2 + (w >> 1)) * 8 + g;
  mbar_wait(b_x, 0);
  #pragma unroll
  for (int j = 0; j < 16; j++) {
    const uint4 v = lds_u32x4((xa ^ ((j & 1) * 64)) + (j >> 1) * 128);
    mma_bf16(d[2 * (j & 1)], v.x, 0x3F803F80u, v.y, 0x3F803F80u, v.x, v.y);
    mma_bf16(d[2 * (j & 1) + 1], v.z, 0x3F803F80u, v.w, 0x3F803F80u, v.z, v.w);
  }
  #pragma unroll
  for (int e = 0; e < 4; e++) d[0][e] = (d[0][e] + d[1][e]) + (d[2][e] + d[3][e]);
  const uint32_t sm = __float_as_uint((g & 1) ? d[0][3] : d[0][2]), sq = __float_as_uint((g & 1) ? d[0][1] : d[0][0]);
  if ((lane & 3) == (g >> 1)) st_relaxed2(dst, sm == 0u ? 0x80000000u : sm, sq == 0u ? 0x80000000u : sq);
  HSD(3, sm);
}
__device__ __forceinline__ void put_table(uint32_t tab, int l, bool ca, const float4& v) {
  uint32_t m0 = pack_bf16(v.x, v.y), m1 = pack_bf16(v.z, v.w);
  if (ca) { m0 = badd2(m0, 0x3F803F80u); m1 = badd2(m1, 0x3F803F80u); }
  tab += (l >> 2) * 64 + (l & 1) * 32 + (l & 2) * 2 + (ca ? 0 : 8);
  sts_u32(tab, m0); sts_u32(tab + 16, m1);
}
__device__ __forceinline__ void head_gather(Scratch* hm, uint32_t tab, int tid) {
  float4 p[16];
  #pragma unroll 1
  for (unsigned int spin = 0; spin < (1u << 22); spin++) {
    uint32_t m = 0xffffffffu;
    #pragma unroll
    for (int k = 0; k < 16; k++) p[k] = ld_tagged4(hm->modu + k * 512 + tid * 4);
    #pragma unroll
    for (int k = 0; k < 16; k++) m = min(min(m, min(__float_as_uint(p[k].x), __float_as_uint(p[k].y))), min(__float_as_uint(p[k].z), __float_as_uint(p[k].w)));
    if (m != 0u) break;
  }
  #pragma unroll
  for (int o = 1; o < 16; o <<= 1)
    #pragma unroll
    for (int k = 0; k < 16; k += 2 * o) { p[k].x += p[k + o].x; p[k].y += p[k + o].y; p[k].z += p[k + o].z; p[k].w += p[k + o].w; }
  put_table(tab, tid & 63, tid >= 64, p[0]);
  __syncwarp();
  HS(2);
}
__device__ __forceinline__ uint32_t ln_stat(float sm, float sq) {
  const float mean = sm * (1.0f / T_D), var = fmaxf(fmaf(-mean, mean, sq * (1.0f / T_D)), 0.f);
  return pack_bf16(mean, sqrt_approx(rbf(rbf(var) + 1e-05f)));
}
__device__ __forceinline__ void gather_table(Scratch* hm, uint32_t tab0, uint32_t b_tab, int a, int lane) {
  #pragma unroll 1
  for (int r = 2; r < 8; r++) {
    float4 v;
    #pragma unroll 1
    for (unsigned int spin = 0; spin < (1u << 22); spin++) {
      v = ld_tagged4(hm->mod + a * T_D + r * 128 + lane * 4);
      if (__all_sync(0xffffffffu, tagged4(v))) break;
      if (GSLP) __nanosleep(GSLP);
    }
    put_table(tab0 + r * 512, lane, a, v);
    __syncwarp();
    if (lane == 0) mbar_arrive(b_tab + 8 * r);
    if (r < 6) HS(2 + r);
  }
}

__device__ __forceinline__ uint32_t assign_tile(Scratch* hm, uint32_t t0, int lane) {
  uint32_t me; asm("mov.u32 %0, %%smid;" : "=r"(me));
  me = (me & 255u) + 1u;
  if (lane == 0) asm volatile("st.relaxed.gpu.global.u32 [%0], %1;" :: "l"(hm->gkey + blockIdx.x), "r"((t0 & ~511u) | me) : "memory");
  uint32_t k[5];
  #pragma unroll 1
  for (unsigned int spin = 0; spin < (1u << 20); spin++) {
    __nanosleep(ASLP);
    #pragma unroll
    for (int m = 0; m < 5; m++) asm volatile("ld.relaxed.gpu.global.u32 %0, [%1];" : "=r"(k[m]) : "l"(hm->gkey + m * 32 + lane) : "memory");
    if (__all_sync(0xffffffffu, k[0] != 0u && k[1] != 0u && k[2] != 0u && k[3] != 0u && (k[4] != 0u || lane >= 4))) break;
  }
  uint32_t sz = 0u, g = 0u, rank = 0u, w[5];
  #pragma unroll
  for (int m = 0; m < 5; m++) w[m] = k[m] == 0u ? 0u : (k[m] & 511u) < me ? 257u : (k[m] & 511u) == me ? 65537u : 1u;
  #pragma unroll 1
  for (int i = 0; i < 16; i++) {
    const uint32_t v = __reduce_max_sync(0xffffffffu, max(max(max(k[0], k[1]), max(k[2], k[3])), k[4])), lo = (i == 15 || v < 4096u) ? 0u : v - 4096u;
    uint32_t n = 0u;
    #pragma unroll
    for (int m = 0; m < 5; m++) { const bool in = k[m] >= lo; n += in ? w[m] : 0u; w[m] = in ? 0u : w[m]; k[m] = in ? 0u : k[m]; }
    n = __reduce_add_sync(0xffffffffu, n);
    if (lane == i) sz = n & 255u;
    if (n >> 16) { g = i; rank = (n >> 8) & 255u; }
  }
  #pragma unroll 1
  for (int d = 0; d < 4; d += DROPN)
    if ((__reduce_max_sync(0xffffffffu, sz * 32u + lane) & 31u) == (uint32_t)lane) sz -= DROPN;
  const uint32_t gs = __shfl_sync(0xffffffffu, sz, g);
  const uint32_t off = __reduce_add_sync(0xffffffffu, (sz != 16u) * 32u + lane < (gs != 16u) * 32u + g ? sz : 0u);
  return rank < gs ? off + rank : 128u;
}

__device__ __forceinline__ int col_pos(int c) { return (c & ~31) + ((c >> 1) & 3) * 8 + ((c >> 3) & 3) * 2 + (c & 1); }
__device__ __forceinline__ int mod_col0(int j, int b) { return b < 0 ? (j & 1) * T_D + (b + 4) * 256 + ((j >> 1) ^ 2) * 64 : 2 * T_D + j * 512 + b * 64; }
__device__ SGL_INL void mod_rest(Scratch* hm, uint32_t t0, uint32_t sbase, uint32_t bar, int t2, int j, const bf16* __restrict__ cvec, const bf16* __restrict__ w_r) {
  const uint32_t scr = sbase + 4 * 32768 + 8192;
  const int kind = j >> 1;
  const uint2 c4 = *reinterpret_cast<const uint2*>(cvec + t2 * 4);
  sts_u32x2(scr + t2 * 8, silu2(c4.x), silu2(c4.y));
  const int w8 = t2 >> 5, t = t2 & 3, g = (t2 >> 2) & 7;
  float dot = 0.f;
  uint32_t buf = 0, par = 0;
  named_bar_sync(5, 256);
  #pragma unroll 1
  for (int b = -3; b < 8; b++) {
    float d[2][4] = {{0.f, 0.f, 0.f, 0.f}, {0.f, 0.f, 0.f, 0.f}};
    #pragma unroll 1
    for (int k = 0; k < 4; k++) {
      const uint32_t wa = sbase + (buf + (buf > 2 ? 2 : 0)) * 32768 + w8 * 4096 + t * 256;
      uint4 w[8];
      uint32_t sv[4];
      #pragma unroll
      for (int i = 0; i < 4; i++) sv[i] = lds_u32(scr + k * 512 + w8 * 64 + i * 16 + t * 4);
      mbar_wait(bar + buf * 8, par);
      #pragma unroll
      for (int i = 0; i < 8; i++) w[i] = lds_u32x4(wa + (i >> 1) * 1024 + (i & 1) * 128 + ((g ^ (t * 2 + (i & 1))) << 4));
      gemv64<8>(d, w, sv, t2 & 31);
      named_bar_sync(5, 256);
      if (t2 == 0) sts_u32(bar + 40, b * 4 + k + 18);
      if (++buf == 5) { buf = 0; par ^= 1; }
    }
    const int c0 = mod_col0(j, b);
    float v = gemv64_sum<8>(d, scr + 2048, t2);
    if (t2 < 64) {
      if (b < 0) st_tagged(hm->mod + c0 + t2, v);
      else {
        const int col = (c0 + t2) & 1023;
        uint8_t* dst = g_col + (col >> 7) * 1536;
        v = rbf(v);
        if (kind == 2) v = rbf(1.0f + v);
        const float vw = v * __bfloat162float(w_r[col]);
        dot += vw;
        if (kind == 2) {
          reinterpret_cast<bf16*>(dst)[col_pos(col & 127)] = __float2bfloat16_rn(vw);
          reinterpret_cast<bf16*>(dst)[128 + col_pos(col & 127)] = __float2bfloat16_rn(vw - rbf(vw));
        }
        reinterpret_cast<bf16*>(dst + 512 + (kind == 0 ? 0 : kind == 2 ? 256 : kind == 1 ? 512 : 768))[col_pos(col & 127)] = __float2bfloat16_rn(v);
      }
    }
  }
  #pragma unroll
  for (int o = 16; o > 0; o >>= 1) dot += __shfl_xor_sync(0xffffffffu, dot, o);
  if (t2 == 32) sts_f32(scr + 4096, dot);
  fence_proxy_async();
  named_bar_sync(5, 256);
  if (t2 == 0 && (kind == 1 || kind == 2)) g_scal[(kind == 2 ? 0 : 2) + (j & 1)] = dot + lds_f32(scr + 4096);
  sleep_until(t0, CLR_T);
  #pragma unroll 1
  for (int i = j * 256 + t2; i < (int)(sizeof(TailMail) / 16); i += 8 * 256) reinterpret_cast<uint4*>(&hm->mail)[i] = make_uint4(0u, 0u, 0u, 0u);
  named_bar_sync(5, 256);
  if (t2 == 0) red_release_add(&g_hcnt[0], 1u);
  sleep_until(t0, SGL_T);
}

constexpr int AT_NBLK = T_SEQ / 128;
constexpr float AT_HEAD = 7.0f;
constexpr int WO_LATE = 12;
#define QSTG 3
constexpr int QP_STAG = QSTG;
constexpr int AT_SPLIT = 28, AT_PIN = 8, PINB = 4;
constexpr int AT_NFULL = 124;
constexpr int AT_PREG = 40, AT_CREG = 232;
constexpr uint32_t AT_SQ = 5 * 32768;
constexpr float AT_C = 0.08838834764831845f * 1.4426950408889634f;
constexpr float AT_RAW_LO = -16.0f, AT_RAW_HI = 24.0f;
constexpr float AT_RAW_SUM = 281474976710656.0f, AT_RAW_MIN = 9.094947017729282e-13f;
constexpr uint32_t AT_SBAR = AT_SQ + 65536 + 256;
constexpr uint32_t AT_SMEM = AT_SQ + 65536 + 3072;

__device__ __forceinline__ uint32_t ring_slot(uint32_t t) { return t - 5u * ((t * 205u) >> 10); }
__device__ __forceinline__ uint32_t qp_pos(uint32_t j, uint32_t it) { return 4u * it + (j & 3u) + ((j & 3u) == 3u ? it : 0u); }
__device__ __forceinline__ uint32_t ring_par(uint32_t t) { return ((t * 205u) >> 10) & 1u; }
__device__ __forceinline__ void softmax_rowmax(const float (&s)[64], float& mx0, float& mx1) {
  float a0 = fmaxf(s[0], s[1]), a1 = fmaxf(s[4], s[5]), a2 = fmaxf(s[8], s[9]), a3 = fmaxf(s[12], s[13]);
  float b0 = fmaxf(s[2], s[3]), b1 = fmaxf(s[6], s[7]), b2 = fmaxf(s[10], s[11]), b3 = fmaxf(s[14], s[15]);
  #pragma unroll
  for (int j = 4; j < 16; j += 4) {
    a0 = fmaxf(a0, fmaxf(s[4 * j + 0], s[4 * j + 1]));  b0 = fmaxf(b0, fmaxf(s[4 * j + 2], s[4 * j + 3]));
    a1 = fmaxf(a1, fmaxf(s[4 * j + 4], s[4 * j + 5]));  b1 = fmaxf(b1, fmaxf(s[4 * j + 6], s[4 * j + 7]));
    a2 = fmaxf(a2, fmaxf(s[4 * j + 8], s[4 * j + 9]));  b2 = fmaxf(b2, fmaxf(s[4 * j + 10], s[4 * j + 11]));
    a3 = fmaxf(a3, fmaxf(s[4 * j + 12], s[4 * j + 13])); b3 = fmaxf(b3, fmaxf(s[4 * j + 14], s[4 * j + 15]));
  }
  mx0 = fmaxf(fmaxf(a0, a1), fmaxf(a2, a3));
  mx1 = fmaxf(fmaxf(b0, b1), fmaxf(b2, b3));
  mx0 = fmaxf(mx0, __shfl_xor_sync(0xffffffffu, mx0, 1));
  mx1 = fmaxf(mx1, __shfl_xor_sync(0xffffffffu, mx1, 1));
  mx0 = fmaxf(mx0, __shfl_xor_sync(0xffffffffu, mx0, 2));
  mx1 = fmaxf(mx1, __shfl_xor_sync(0xffffffffu, mx1, 2));
}
__device__ __forceinline__ void softmax_sub(float (&s)[64], float mc0, float mc1) {
  #pragma unroll
  for (int j = 0; j < 16; j++) { s[4 * j] -= mc0; s[4 * j + 1] -= mc0; s[4 * j + 2] -= mc1; s[4 * j + 3] -= mc1; }
}
template <int LO, int HI>
__device__ __forceinline__ void softmax_exp(float (&s)[64]) {
  #pragma unroll
  for (int i = LO; i < HI; i++) s[i] = ex2_approx(s[i]);
}
__device__ __forceinline__ bool softmax_mode(const float (&s)[64], float& mc0, float& mc1) {
  softmax_rowmax(s, mc0, mc1);
  const bool raw = __all_sync(0xffffffffu, mc0 >= AT_RAW_LO && mc0 <= AT_RAW_HI && mc1 >= AT_RAW_LO && mc1 <= AT_RAW_HI);
  mc0 += AT_HEAD; mc1 += AT_HEAD;
  return raw;
}
__device__ __forceinline__ void rowsum_p(const uint32_t (&p)[32], uint32_t& t0, uint32_t& t1) {
  uint32_t a[16];
  #pragma unroll
  for (int i = 0; i < 8; i++) { a[2 * i] = badd2(p[4 * i], p[4 * i + 2]); a[2 * i + 1] = badd2(p[4 * i + 1], p[4 * i + 3]); }
  #pragma unroll
  for (int i = 0; i < 4; i++) { a[2 * i] = badd2(a[4 * i], a[4 * i + 2]); a[2 * i + 1] = badd2(a[4 * i + 1], a[4 * i + 3]); }
  t0 = badd2(badd2(a[0], a[2]), badd2(a[4], a[6]));
  t1 = badd2(badd2(a[1], a[3]), badd2(a[5], a[7]));
}
__device__ __forceinline__ void add_rowsum(const uint32_t (&p)[32], float& l0, float& l1) {
  uint32_t t0, t1;
  rowsum_p(p, t0, t1);
  l0 += bflo(t0) + bfhi(t0); l1 += bflo(t1) + bfhi(t1);
}
__device__ __forceinline__ void pack_p(uint32_t (&p)[32], const float (&s)[64]) {
  #pragma unroll
  for (int i = 0; i < 32; i++) p[i] = pack_bf16(s[2 * i], s[2 * i + 1]);
}
__device__ __noinline__ void attn_rows_exact(uint32_t sq, int warp, int lane, const bf16* __restrict__ kh, const bf16* __restrict__ vh) {
  #pragma unroll 1
  for (int r = 16 * warp; r < 16 * warp + 16; r++) {
    const uint32_t ad = (lane >> 4) * 16384 + r * 128 + ((((lane & 15) >> 1) ^ (r & 7)) << 4) + (lane & 1) * 8;
    uint2 qv; asm volatile("ld.shared.v2.u32 {%0, %1}, [%2];" : "=r"(qv.x), "=r"(qv.y) : "r"(sq + ad) : "memory");
    const float q0 = bflo(qv.x), q1 = bfhi(qv.x), q2 = bflo(qv.y), q3 = bfhi(qv.y);
    float m = -INFINITY, l = 0.f, o0 = 0.f, o1 = 0.f, o2 = 0.f, o3 = 0.f;
    #pragma unroll 1
    for (int key = 0; key < T_SEQ; key++) {
      const uint2 kv = *reinterpret_cast<const uint2*>(kh + (size_t)key * T_DH + lane * 4);
      const uint2 vv = *reinterpret_cast<const uint2*>(vh + (size_t)key * T_DH + lane * 4);
      float sc = (q0 * bflo(kv.x) + q1 * bfhi(kv.x)) + (q2 * bflo(kv.y) + q3 * bfhi(kv.y));
      #pragma unroll
      for (int o = 16; o > 0; o >>= 1) sc += __shfl_xor_sync(0xffffffffu, sc, o);
      const float mn = fmaxf(m, sc);
      const float al = (m == mn) ? 1.0f : ex2_approx(m - mn), p = rbf(ex2_approx(sc - mn));
      m = mn;
      l = fmaf(l, al, p);
      o0 = fmaf(o0, al, p * bflo(vv.x)); o1 = fmaf(o1, al, p * bfhi(vv.x));
      o2 = fmaf(o2, al, p * bflo(vv.y)); o3 = fmaf(o3, al, p * bfhi(vv.y));
    }
    const float inv = rcp_approx(l);
    asm volatile("st.shared.v2.u32 [%0], {%1, %2};" :: "r"(sq + ad), "r"(pack_bf16(o0 * inv, o1 * inv)), "r"(pack_bf16(o2 * inv, o3 * inv)) : "memory");
  }
}
__device__ __forceinline__ void issue_qk(float (&s)[64], const uint32_t (&q)[32], uint32_t k_lo) {
  wgmma_fence();
  wgmma_m64n128k16_rs<0>(s, q[0], q[1], q[2], q[3], k_lo, 0);
  wgmma_m64n128k16_rs<2>(s, q[4], q[5], q[6], q[7], k_lo, 1);
  wgmma_m64n128k16_rs<4>(s, q[8], q[9], q[10], q[11], k_lo, 1);
  wgmma_m64n128k16_rs<6>(s, q[12], q[13], q[14], q[15], k_lo, 1);
  wgmma_m64n128k16_rs<1024>(s, q[16], q[17], q[18], q[19], k_lo, 1);
  wgmma_m64n128k16_rs<1026>(s, q[20], q[21], q[22], q[23], k_lo, 1);
  wgmma_m64n128k16_rs<1028>(s, q[24], q[25], q[26], q[27], k_lo, 1);
  wgmma_m64n128k16_rs<1030>(s, q[28], q[29], q[30], q[31], k_lo, 1);
  wgmma_commit();
}
__device__ __forceinline__ void issue_pv(float (&o)[64], const uint32_t (&p)[32], uint32_t v_lo, int accumulate) {
  wgmma_fence();
  wgmma_m64n128k16_rs_tb<0>(o, p[0], p[1], p[2], p[3], v_lo, accumulate);
  wgmma_m64n128k16_rs_tb<128>(o, p[4], p[5], p[6], p[7], v_lo, 1);
  wgmma_m64n128k16_rs_tb<256>(o, p[8], p[9], p[10], p[11], v_lo, 1);
  wgmma_m64n128k16_rs_tb<384>(o, p[12], p[13], p[14], p[15], v_lo, 1);
  wgmma_m64n128k16_rs_tb<512>(o, p[16], p[17], p[18], p[19], v_lo, 1);
  wgmma_m64n128k16_rs_tb<640>(o, p[20], p[21], p[22], p[23], v_lo, 1);
  wgmma_m64n128k16_rs_tb<768>(o, p[24], p[25], p[26], p[27], v_lo, 1);
  wgmma_m64n128k16_rs_tb<896>(o, p[28], p[29], p[30], p[31], v_lo, 1);
  wgmma_commit();
}
__device__ __forceinline__ void rescale_o(float (&o)[64], float al0, float al1) {
  #pragma unroll
  for (int j = 0; j < 16; j++) { o[4 * j] *= al0; o[4 * j + 1] *= al0; o[4 * j + 2] *= al1; o[4 * j + 3] *= al1; }
}

__device__ __forceinline__ void stage_o(const float (&o)[64], float i0, float i1, uint32_t dst, int lane) {
  #pragma unroll
  for (int J = 0; J < 16; J += 2)
    stmatrix_x4(dst + (J >> 3) * 16384 + ((((J & 7) + (lane >> 4)) ^ (lane & 7)) << 4),
                pack_bf16(o[4 * J + 0] * i0, o[4 * J + 1] * i0), pack_bf16(o[4 * J + 2] * i1, o[4 * J + 3] * i1),
                pack_bf16(o[4 * J + 4] * i0, o[4 * J + 5] * i0), pack_bf16(o[4 * J + 6] * i1, o[4 * J + 7] * i1));
}
__device__ __forceinline__ bool finish_l(float& l0, float& l1) {
  l0 += __shfl_xor_sync(0xffffffffu, l0, 1); l1 += __shfl_xor_sync(0xffffffffu, l1, 1);
  l0 += __shfl_xor_sync(0xffffffffu, l0, 2); l1 += __shfl_xor_sync(0xffffffffu, l1, 2);
  const bool redo = __any_sync(0xffffffffu, !(l0 <= AT_RAW_SUM && l1 <= AT_RAW_SUM && l0 >= AT_RAW_MIN && l1 >= AT_RAW_MIN));
  l0 = rcp_approx(l0); l1 = rcp_approx(l1);
  return redo;
}
__device__ __forceinline__ void stage_qregs(const uint32_t (&q)[32], uint32_t dst, int lane) {
  #pragma unroll
  for (int J = 0; J < 16; J += 2)
    stmatrix_x4(dst + (J >> 3) * 16384 + ((((J & 7) + (lane >> 4)) ^ (lane & 7)) << 4), q[2 * J], q[2 * J + 1], q[2 * J + 2], q[2 * J + 3]);
}
__device__ __forceinline__ void store_o(const CUtensorMap* tmO, uint32_t src, int head, int row) {
  tma_store_2d(tmO, src, head * T_DH, row);
  tma_store_2d(tmO, src + 16384, head * T_DH + 64, row);
  bulk_commit();
}
struct GemvSel { uint32_t lo0, hi0, lo1, hi1; };
__device__ __forceinline__ GemvSel gemv_sel(int lane) {
  const uint32_t lo = (lane & 8) ? 0x1044u : 0x4410u, hi = (lane & 8) ? 0x3244u : 0x4432u;
  GemvSel s; s.lo0 = (lane & 16) ? 0x4444u : lo; s.hi0 = (lane & 16) ? 0x4444u : hi; s.lo1 = (lane & 16) ? lo : 0x4444u; s.hi1 = (lane & 16) ? hi : 0x4444u;
  return s;
}
#define GEMV_B0(j, h, s) __byte_perm((j) < 2 ? (h).x : (h).y, 0u, ((j) & 1) ? (s).hi0 : (s).lo0)
#define GEMV_B1(j, h, s) __byte_perm((j) < 2 ? (h).x : (h).y, 0u, ((j) & 1) ? (s).hi1 : (s).lo1)
__device__ __forceinline__ float4 gemv_out(const float (&d)[4], int lane) {
  const bool tk = lane & 1;
  const float r0 = __shfl_xor_sync(0xffffffffu, tk ? d[0] : d[1], 1), r1 = __shfl_xor_sync(0xffffffffu, tk ? d[2] : d[3], 1);
  return tk ? make_float4(r0, d[1], r1, d[3]) : make_float4(d[0], r0, d[2], r1);
}
#define OG_NG 8
#define OG_GRP (64 / OG_NG)
constexpr int OG_ST = 5, OG_NKB = T_DQKV / 64, OG_MOE = T_F / 32;
constexpr int OG_POS = 8;
constexpr uint32_t OG_STAGE = 32768;
constexpr uint32_t OG_SWD = AT_SQ;
constexpr uint32_t OG_SCOL = AT_SBAR + 512;
constexpr uint32_t OG_SMISC = AT_SBAR + 2048;
constexpr uint32_t OG_XSLOT = ((OG_POS + OG_NKB) % OG_ST) * OG_STAGE;
constexpr uint32_t OG_OSLOT = ((OG_POS + OG_NKB + 1) % OG_ST) * OG_STAGE;
constexpr uint32_t OG_SH2 = ((OG_POS + OG_NKB + 2) % OG_ST) * OG_STAGE;
constexpr uint32_t OG_SRED = ((OG_POS + OG_NKB + 3) % OG_ST) * OG_STAGE;
constexpr uint32_t OG_SSTAT = OG_SRED + 16384;
constexpr uint32_t OG_SGU = OG_SRED + 8192;
constexpr uint32_t OG_SFIN = OG_SGU + 256;
#define OGM 2
#define OG_MT(b) ((((b) >> OGM) & 15) ^ (SERP && ((b) & 64) ? 15 : 0))
#define OG_NT(b) (((b) & ((1 << OGM) - 1)) + (((b) >> (4 + OGM)) << OGM))
#define TAIL_SETUP \
  const uint32_t bar_full = sbase + AT_SBAR, bar_empty = bar_full + 40; \
  const uint32_t bar_wd = bar_full + 168, bar_col = bar_full + 176, bar_out = bar_full + 184, bar_end = bar_full + 192; \
  const uint32_t bar_key = bar_full + 200, bar_h2 = bar_full + 208, bar_sel = bar_full + 216; \
  const int mt = OG_MT(bx), nt = OG_NT(bx); \
  const int m0 = mt * 128, n0 = nt * 128; \
  const bool has_moe = (int)bx < OG_MOE; \
  (void)bar_empty; (void)bar_wd; (void)bar_col; (void)bar_out; (void)bar_end; (void)bar_key; (void)bar_h2; (void)bar_sel; (void)m0; (void)n0; (void)has_moe;

__device__ __forceinline__ void tail_producer(Scratch* hm, uint32_t bx, uint32_t sbase, uint32_t ph, uint32_t obpar, uint64_t pol, const CUtensorMap* tmA, const CUtensorMap* tmB,
                                              const CUtensorMap* tmX, const bf16* __restrict__ w_down) {
  TAIL_SETUP
  const uint32_t b_q0 = bar_full + 80, b_ob = bar_full + 96, b_acq = bar_full + 264;
  uint32_t stage = OG_POS % OG_ST;
  if (has_moe) mbar_expect_tx(bar_wd, 65536);
  mbar_expect_tx(bar_col, 1536 + 16);
  #pragma unroll 1
  for (int kb = 0; kb <= OG_NKB; kb++) {
    const uint32_t fb = bar_full + 8 * stage, sa = sbase + stage * OG_STAGE, sb = sa + 16384;
    mbar_wait(bar_empty + 8 * stage, ph);
    mbar_expect_tx(fb, OG_STAGE);
    if (kb < OG_NKB) {
      tma_load_2d_hint(sb, tmB, n0, kb * 64, fb, pol);
      tma_load_2d_hint(sb + 8192, tmB, n0 + 64, kb * 64, fb, pol);
      if ((kb & 31) == 0) { mbar_wait(b_acq, kb >> 5); fence_proxy_async_global(); }
      tma_load_2d_hint(sa, tmA, kb * 64, m0, fb, pol);
    } else {
      tma_load_2d_hint(sa, tmX, n0, m0, fb, pol);
      tma_load_2d_hint(sb, tmX, n0 + 64, m0, fb, pol);
    }
    if (kb == 32) {
      bulk_load_hint(sbase + OG_SCOL, g_col + nt * 1536, 1536, bar_col, pol);
      bulk_load_hint(sbase + OG_SMISC, g_scal, 16, bar_col, pol);
    }
    if (kb == 6) { mbar_wait(b_q0, obpar); mbar_wait(b_ob, obpar); }
    if (has_moe && (kb & 7) == 6 && kb < 64)
      bulk_load_hint(sbase + OG_SWD + (kb >> 3) * 8224, (const uint8_t*)w_down + (size_t)bx * 65536 + (kb >> 3) * 8192, 8192, bar_wd, pol);
    if (++stage == OG_ST) { stage = 0; ph ^= 1; }
  }
}

__device__ __forceinline__ uint32_t out2(uint32_t x1, uint32_t mb2, uint32_t ih, uint32_t il, uint32_t c1, uint32_t sb, uint32_t gb) {
  const uint32_t d = bsub2(x1, mb2);
  return bfma2(gb, bfma2(bfma2(d, ih, bmul2(d, il)), c1, sb), x1);
}
__device__ __forceinline__ void tail_exchange(Scratch* hm, uint32_t bx, uint32_t sbase, uint32_t tx, const CUtensorMap* tmOut, bf16* __restrict__ out) {
    TAIL_SETUP
    mbar_wait(bar_end, 0);
    const int lane = tx & 31;
    TL_MARK2(22, lane == 0);
    if (tx == 96) PF(5);
    if (tx < 32) {
      uint32_t k1 = 0u, k2 = 0u;
      #pragma unroll 1
      for (unsigned int spin = 0; spin < (1u << 22) && k1 == 0u; spin++) asm volatile("ld.relaxed.gpu.global.u32 %0, [%1];" : "=r"(k1) : "l"(g_key + lane) : "memory");
      __syncwarp();
      TL_MARK2(28, lane == 0);
    TS(6, lane == 0);
      warp_top2(k1, k2);
      if (lane == 0) {
        const uint32_t r1 = 0xffffu - (k1 & 0xffffu), r2 = 0xffffu - (k2 & 0xffffu);
        sts_u32x4(sbase + OG_SMISC + 64, r1, r2, (r1 >> 7) * 2, (r2 >> 7) * 2 + ((r1 >> 7) == (r2 >> 7)));
        sts_u32x2(sbase + OG_SMISC + 192, k1, k2);
        mbar_arrive(bar_sel);
      }
    } else if (tx < 96) {
          mbar_wait(bar_key, 0);
          const uint4 kk = lds_u32x4(sbase + OG_SSTAT + 1024 + lane * 16);
          uint32_t k1 = max(kk.x, kk.y), k2 = min(kk.x, kk.y);
          k2 = max(max(k2, min(kk.z, kk.w)), min(k1, max(kk.z, kk.w))); k1 = max(k1, max(kk.z, kk.w));
          warp_top2(k1, k2);
          if (tx < 64) {
            if (lane == 0 && nt == (mt & 7)) st_relaxed2(g_key + mt * 2, k1, k2);
            TL_MARK2(27, lane == 0);
    TS(4, lane == 0);
          } else {
            const uint32_t r = (~((lane & 16) ? k2 : k1)) & 127u, ch = lane & 15;
            const uint2 st = lds_u32x2(sbase + OG_SSTAT + r * 8);
            const uint4 xc = lds_u32x4(sbase + OG_XSLOT + (ch >> 3) * 16384 + r * 128 + (((ch ^ r) & 7) << 4));
            const uint32_t ca = sbase + OG_SCOL + 768 + (ch >> 2) * 64 + (ch & 3) * 4;
            const uint4 c1 = make_uint4(lds_u32(ca), lds_u32(ca + 16), lds_u32(ca + 32), lds_u32(ca + 48)), sh = make_uint4(lds_u32(ca + 256), lds_u32(ca + 272), lds_u32(ca + 288), lds_u32(ca + 304));
            const float inr = __uint_as_float(st.y);
            float* dst = reinterpret_cast<float*>(g_cand + (mt * 2 + (lane >> 4)) * 256 + nt * 16 + ch);
            st_tagged4(dst + 512, __uint_as_float(ln_mod2(xc.x, st.x, inr, c1.x, sh.x)), __uint_as_float(ln_mod2(xc.y, st.x, inr, c1.y, sh.y)),
                       __uint_as_float(ln_mod2(xc.z, st.x, inr, c1.z, sh.z)), __uint_as_float(ln_mod2(xc.w, st.x, inr, c1.w, sh.w)));
            st_tagged4(dst, __uint_as_float(xc.x), __uint_as_float(xc.y), __uint_as_float(xc.z), __uint_as_float(xc.w));
          }
    }
    mbar_wait(bar_sel, 0);
    const int sel0 = (int)lds_u32(sbase + OG_SMISC + 64), sel1 = (int)lds_u32(sbase + OG_SMISC + 68);
    mbar_wait(bar_out, 0);
    if ((sel0 >> 7) == mt || (sel1 >> 7) == mt) {
      #pragma unroll 2
      for (int i = 0; i < 16; i++) {
        const int r = i * 8 + (tx >> 4), ch = tx & 15;
        if (m0 + r != sel0 && m0 + r != sel1)
          *reinterpret_cast<uint4*>(out + (size_t)(m0 + r) * T_D + n0 + ch * 8) =
              lds_u32x4(sbase + OG_OSLOT + (ch >> 3) * 16384 + r * 128 + (((ch & 7) ^ (r & 7)) << 4));
      }
    } else if (tx == 0) {
      tma_store_2d(tmOut, sbase + OG_OSLOT, n0, m0);
      tma_store_2d(tmOut, sbase + OG_OSLOT + 16384, n0 + 64, m0);
      bulk_commit();
    }
    if (bx == 0 && tx < 68) g_hcnt[32 * (tx >> 2) + (tx & 3)] = 0u;
    if (tx < 64) hm->modu[bx * 64 + tx] = 0.f;
    else if (tx < 96) hm->stat[bx * 32 + tx - 64] = make_float2(0.f, 0.f);
    else if (tx < 112) hm->mod[bx * 16 + tx - 96] = 0.f;
    else if (tx < 114 && bx < 66) hm->gkey[bx * 2 + tx - 112] = 0u;
    {
      const int tk = bx >> 6, c0 = (bx & 63) * 16;
      const uint32_t gb2 = *reinterpret_cast<const uint32_t*>(g_col + (c0 >> 7) * 1536 + 512 + 768 + col_pos((c0 & 127) + (tx & 14)) * 2);
      const uint32_t* xp = reinterpret_cast<const uint32_t*>(g_cand + lds_u32(sbase + OG_SMISC + 72 + tk * 4) * 256) + ((c0 + (tx & 14)) >> 1);
      uint32_t x2 = 0u;
      #pragma unroll 1
      for (unsigned int spin = 0; spin < (1u << 20) && x2 == 0u; spin++) asm volatile("ld.relaxed.gpu.global.u32 %0, [%1];" : "=r"(x2) : "l"(xp) : "memory");
      const float* src = g_ypart + (size_t)((tx >> 2) * 2 + tk) * T_D + c0 + (tx & 3) * 4;
      const bool four = tx < (OG_MOE - 96) * 4;
      mbar_wait(bar_h2, 0);
      if (tx == 0) hint_wait(CNT_Y, (uint32_t)OG_MOE);
      named_bar_sync(10, 128);
      TS(11, lane == 0);
      float4 p0, p1, p2, p3;
      #pragma unroll 1
      for (unsigned int spin = 0; spin < (1u << 20); spin++) {
        p0 = ld_tagged4(src); p1 = ld_tagged4(src + 64 * T_D); p2 = ld_tagged4(src + 128 * T_D); p3 = ld_tagged4(four ? src + 192 * T_D : src);
        if (tagged4(p0) && tagged4(p1) && tagged4(p2) && tagged4(p3)) break;
      }
      if (four) { p2.x += p3.x; p2.y += p3.y; p2.z += p3.z; p2.w += p3.w; }
      p0.x = (p0.x + p1.x) + p2.x; p0.y = (p0.y + p1.y) + p2.y; p0.z = (p0.z + p1.z) + p2.z; p0.w = (p0.w + p1.w) + p2.w;
      #pragma unroll
      for (int o = 4; o <= 16; o <<= 1) {
        p0.x += __shfl_xor_sync(0xffffffffu, p0.x, o); p0.y += __shfl_xor_sync(0xffffffffu, p0.y, o);
        p0.z += __shfl_xor_sync(0xffffffffu, p0.z, o); p0.w += __shfl_xor_sync(0xffffffffu, p0.w, o);
      }
      if (lane < 4) sts_f32x4(sbase + OG_SFIN + (tx >> 5) * 64 + lane * 16, p0.x, p0.y, p0.z, p0.w);
      named_bar_sync(10, 128);
      TS(12, lane == 0);
      if (tx < 16) {
        const uint32_t ya = sbase + OG_SFIN + tx * 4, key = lds_u32(sbase + OG_SMISC + 192 + tk * 4);
        float y = (lds_f32(ya) + lds_f32(ya + 64)) + (lds_f32(ya + 128) + lds_f32(ya + 192));
        const float r = bfhi((key & 0x80000000u) ? key ^ 0x80000000u : ~key);
        const float rs = rbf(sigmoid_f(r));
        const uint32_t h2p = lds_u32(sbase + OG_SH2 + tk * 2048 + (c0 + (tx & 14)) * 2);
        const float fh = (lane & 1) ? bfhi(h2p) : bflo(h2p);
        y = rbf(y);
        y = rbf(y * rs);
        const float upd = rbf(rbf(fh * 0.0f) + y);
        out[(size_t)(tk ? sel1 : sel0) * T_D + c0 + tx] =
            __float2bfloat16_rn(((lane & 1) ? bfhi(x2) : bflo(x2)) + rbf(((lane & 1) ? bfhi(gb2) : bflo(gb2)) * rbf(fh + upd)));
      }
      if (tx == 0) bulk_wait_read<0>();
    }
    TL_END(4, tx == 0);
    PS(6, tx == 0);
    TS(13, tx == 0);
}

__device__ __forceinline__ void tail_consumer(Scratch* hm, uint32_t bx, uint32_t sbase, int tid, int w8, const bf16* __restrict__ w_gate, const bf16* __restrict__ w_up) {
    TAIL_SETUP
    const int warp = w8 & 3, lane = tid & 31, cwg = w8 >> 2, t2 = cwg * 128 + tid;
    const uint32_t dbase = (sbase & 0x3FFFFu) >> 4;
    const uint32_t a_base = dbase + ((cwg * 8192) >> 4) + (1u << 16);
    const uint32_t b_base = dbase + (16384 >> 4) + (512u << 16);
    TL_MARK2(25, threadIdx.x == 128);
    const uint64_t pol = policy_evict_first();
    const bf16* pw = ((lane & 16) ? w_up : w_gate) + (size_t)(w8 * 128 + (lane & 3) * 4) * T_F + (has_moe ? bx : 0) * 32 + ((lane >> 2) & 3) * 8;
    uint4 wv[32];
    float acc[64];
    {
      uint32_t stage = OG_POS % OG_ST, phase = (OG_POS / OG_ST) & 1, prev = 0;
      #pragma unroll
      for (int g = 0; g < OG_NG; g++) {
        #pragma unroll
        for (int j = 0; j < 4; j++) wv[4 * g + j] = ldg_stream_v4(pw + (size_t)(16 * g + j) * T_F, pol);
        #pragma unroll 1
        for (int kb = g * OG_GRP; kb < (g == OG_NG - 1 ? OG_NKB : (g + 1) * OG_GRP); kb++) {
          mbar_wait(bar_full + 8 * stage, phase);
          const uint32_t a_lo = a_base + stage * (OG_STAGE >> 4), b_lo = b_base + stage * (OG_STAGE >> 4);
          wgmma_fence();
          wgmma_m64n128k16_ss_tb<0, 0>(acc, a_lo, b_lo, kb != 0);
          wgmma_m64n128k16_ss_tb<2, 128>(acc, a_lo, b_lo, 1);
          wgmma_m64n128k16_ss_tb<4, 256>(acc, a_lo, b_lo, 1);
          wgmma_m64n128k16_ss_tb<6, 384>(acc, a_lo, b_lo, 1);
          wgmma_commit();
          wgmma_wait<1>();
          if (kb > 0 && tid == 0) mbar_arrive(bar_empty + 8 * prev);
          prev = stage;
          if (++stage == OG_ST) { stage = 0; phase ^= 1; }
        }
      }
    }
    const uint32_t frag = (64 * cwg + 16 * warp + (lane & 15)) * 128 + (((lane >> 4) ^ (lane & 7)) << 4);
    const uint32_t tcol = sbase + OG_SCOL + (lane & 3) * 16, g = lane >> 2;
    float* sdst = reinterpret_cast<float*>(g_part1 + ((mt * 8 + w8) * 8 + nt) * 16 + g + (lane & 1) * 8);
    uint32_t xr[32];
    uint4 ga[4], cw[4];
    auto ld_quarter = [&](int q, uint32_t dep) {
      #pragma unroll
      for (int i = 2 * q; i < 2 * q + 2; i++) ldmatrix_x4(sbase + OG_XSLOT + (i >> 2) * 16384 + (frag ^ ((i & 3) * 32)) + dep, xr[4 * i], xr[4 * i + 1], xr[4 * i + 2], xr[4 * i + 3]);
      ga[q] = lds_u32x4(tcol + 512 + q * 64 + dep);
      cw[q] = lds_u32x4((g ? tcol + (lane & 8) * 32 + q * 64 : sbase + OG_SMISC + 32) + dep);
    };
    mbar_wait(bar_col, 0);
    mbar_wait(bar_full + 8 * ((OG_POS + OG_NKB) % OG_ST), ((OG_POS + OG_NKB) / OG_ST) & 1);
    ld_quarter(0, 0);
    wgmma_wait<0>();
    fence_regs(acc);
    if (tid == 0) mbar_arrive(bar_end);
    TL_MARK2(9, lane == 0);
    TS(0, lane == 0);
    PS(5, threadIdx.x == 256);
    {
      float dl[4] = {0.f, 0.f, 0.f, 0.f}, da[4] = {0.f, 0.f, 0.f, 0.f}, db[4] = {0.f, 0.f, 0.f, 0.f};
      #pragma unroll
      for (int q = 0; q < 4; q++) {
        uint32_t pk[8];
        #pragma unroll
        for (int i = 0; i < 8; i++) pk[i] = pack_bf16(acc[16 * q + 2 * i], acc[16 * q + 2 * i + 1]);
        if (q < 3) ld_quarter(q + 1, 0u);
        #pragma unroll
        for (int i = 2 * q; i < 2 * q + 2; i++) {
          #pragma unroll
          for (int k = 0; k < 4; k++) xr[4 * i + k] = badd2(xr[4 * i + k], bmul2((i & 1) ? (k < 2 ? ga[q].z : ga[q].w) : (k < 2 ? ga[q].x : ga[q].y), pk[4 * (i & 1) + k]));
          mma_bf16(dl, xr[4 * i], xr[4 * i + 1], xr[4 * i + 2], xr[4 * i + 3], (i & 1) ? cw[q].z : cw[q].x, (i & 1) ? cw[q].w : cw[q].y);
          mma_bf16(da, xr[4 * i], xr[4 * i + 1], xr[4 * i + 2], xr[4 * i + 3], xr[4 * i], xr[4 * i + 2]);
          mma_bf16(db, xr[4 * i], xr[4 * i + 1], xr[4 * i + 2], xr[4 * i + 3], xr[4 * i + 1], xr[4 * i + 3]);
        }
      }
      {
        const int dsrc = (lane & ~3) + (g >> 1);
        const float qa = __shfl_sync(0xffffffffu, (g & 1) ? da[1] : da[0], dsrc), qb = __shfl_sync(0xffffffffu, (g & 1) ? db[3] : db[2], dsrc);
        const float e0 = __shfl_xor_sync(0xffffffffu, (lane & 1) ? dl[0] : dl[2], 1), e1 = __shfl_xor_sync(0xffffffffu, dl[3], 1);
        const bool hi = lane & 1;
        if ((lane & 3) < 2) st_tagged4(sdst, hi ? e0 : dl[0], hi ? qb : qa, hi ? e1 + dl[2] : dl[1] + e0, 1.0f);
      }
    }
    TL_MARK2(10, lane == 0);
    TS(1, lane == 0);
    uint4 tc[4], ts[4], tg[4];
    #pragma unroll
    for (int i = 0; i < 8; i++) stmatrix_x4(sbase + OG_XSLOT + (i >> 2) * 16384 + (frag ^ ((i & 3) * 32)), xr[4 * i], xr[4 * i + 1], xr[4 * i + 2], xr[4 * i + 3]);
    #pragma unroll
    for (int i = 0; i < 8; i++) ldmatrix_x4(sbase + OG_XSLOT + (i >> 2) * 16384 + (frag ^ ((i & 3) * 32)), xr[4 * i], xr[4 * i + 1], xr[4 * i + 2], xr[4 * i + 3]);
    #pragma unroll
    for (int i = 0; i < TPRE; i++) { tc[i] = lds_u32x4(tcol + 768 + i * 64); ts[i] = lds_u32x4(tcol + 1024 + i * 64); tg[i] = lds_u32x4(tcol + 1280 + i * 64); }
    {
      const float* src = reinterpret_cast<const float*>(g_part1 + ((mt * 8 + w8) * 8 + (lane & 1) * 4) * 16 + (lane >> 1));
      float4 v, v1, v2, v3;
      #pragma unroll 1
      for (unsigned int spin = 0; spin < (1u << 22); spin++) {
        v = ld_tagged4(src); v1 = ld_tagged4(src + 64); v2 = ld_tagged4(src + 128); v3 = ld_tagged4(src + 192);
        if (tagged4(v) & tagged4(v1) & tagged4(v2) & tagged4(v3)) break;
        __nanosleep(100);
      }
      __syncwarp();
      TL_MARK2(26, lane == 0);
    TS(2, lane == 0);
      v.x = (v.x + v1.x) + (v2.x + v3.x); v.y = (v.y + v1.y) + (v2.y + v3.y); v.z = (v.z + v1.z) + (v2.z + v3.z);
      v.x += __shfl_xor_sync(0xffffffffu, v.x, 1); v.y += __shfl_xor_sync(0xffffffffu, v.y, 1); v.z += __shfl_xor_sync(0xffffffffu, v.z, 1);
      const float mean = v.x * (1.0f / T_D);
      const float var = fmaxf(fmaf(-mean, mean, v.y * (1.0f / T_D)), 0.f);
      const uint32_t mb2 = pack_bf16(mean, mean);
      const float inv = rcp_approx(rbf(sqrt_approx(rbf(rbf(var) + 1e-05f))));
      {
        const uint4 sc = lds_u32x4(sbase + OG_SMISC);
        const uint32_t key = rank_key(rbf(fmaf(fmaf(-bflo(mb2), __uint_as_float(sc.x) + __uint_as_float(sc.y), v.z), inv, __uint_as_float(sc.z) + __uint_as_float(sc.w))), m0 + 16 * w8 + (lane >> 1));
        mbar_wait(bar_end, 0);
        if (lane & 1) sts_u32(sbase + OG_SSTAT + 1024 + (16 * w8 + (lane >> 1)) * 4, key);
        else sts_u32x2(sbase + OG_SSTAT + (16 * w8 + (lane >> 1)) * 8, mb2, __float_as_uint(inv));
        __syncwarp();
        TS(3, lane == 0);
        if (lane == 0) mbar_arrive(bar_key);
      }
      const uint32_t ih = pack_bf16(inv, inv), il = pack_bf16(inv - bflo(ih), inv - bflo(ih));
      const uint32_t mba = __shfl_sync(0xffffffffu, mb2, 2 * (lane >> 2)), mbb = __shfl_sync(0xffffffffu, mb2, 2 * (lane >> 2) + 16);
      const uint32_t iha = __shfl_sync(0xffffffffu, ih, 2 * (lane >> 2)), ihb = __shfl_sync(0xffffffffu, ih, 2 * (lane >> 2) + 16);
      const uint32_t ila = __shfl_sync(0xffffffffu, il, 2 * (lane >> 2)), ilb = __shfl_sync(0xffffffffu, il, 2 * (lane >> 2) + 16);
      #pragma unroll
      for (int i = TPRE; i < 4; i++) { tc[i] = lds_u32x4(tcol + 768 + i * 64); ts[i] = lds_u32x4(tcol + 1024 + i * 64); tg[i] = lds_u32x4(tcol + 1280 + i * 64); }
      #pragma unroll
      for (int i = 0; i < 8; i++) {
        const uint4 &c = tc[i >> 1], &s = ts[i >> 1], &b = tg[i >> 1];
        const bool u = i & 1;
        stmatrix_x4(sbase + OG_OSLOT + (i >> 2) * 16384 + (frag ^ ((i & 3) * 32)),
                    out2(xr[4 * i], mba, iha, ila, u ? c.z : c.x, u ? s.z : s.x, u ? b.z : b.x), out2(xr[4 * i + 1], mbb, ihb, ilb, u ? c.z : c.x, u ? s.z : s.x, u ? b.z : b.x),
                    out2(xr[4 * i + 2], mba, iha, ila, u ? c.w : c.y, u ? s.w : s.y, u ? b.w : b.y), out2(xr[4 * i + 3], mbb, ihb, ilb, u ? c.w : c.y, u ? s.w : s.y, u ? b.w : b.y));
      }
      fence_proxy_async();
      __syncwarp();
      if (lane == 0) mbar_arrive(bar_out);
      TL_MARK2(24, lane == 0);
    TS(5, lane == 0);
    }
    uint4 wd[16];
    {
      mbar_wait(bar_sel, 0);
      TL_MARK2(12, lane == 0);
    TS(7, lane == 0);
      const float* src = reinterpret_cast<const float*>(g_cand + lds_u32(sbase + OG_SMISC + 72 + cwg * 4) * 256 + 128 + tid);
      float4 hf = ld_tagged4(src);
      if (has_moe) mbar_wait(bar_wd, 0);
      #pragma unroll
      for (int i = 0; i < 16; i++) wd[i] = lds_u32x4(sbase + OG_SWD + (((i >> 2) & 1) * 4 + (lane & 3)) * 8224 + (i & 3) * 2048 + w8 * 256 + (i >> 3) * 128 + (lane >> 2) * 16);
      #pragma unroll 1
      for (unsigned int spin = 0; spin < (1u << 20) && !tagged4(hf); spin++) hf = ld_tagged4(src);
      const uint4 hv = make_uint4(__float_as_uint(hf.x), __float_as_uint(hf.y), __float_as_uint(hf.z), __float_as_uint(hf.w));
      sts_u32x4(sbase + OG_SH2 + t2 * 16, hv.x, hv.y, hv.z, hv.w);
    }
    named_bar_sync(9, 256);
    if (t2 == 0) mbar_arrive(bar_h2);
    TL_MARK2(13, lane == 0);
    TS(8, lane == 0);
    if (has_moe) {
      const GemvSel sel = gemv_sel(lane);
      {
        float d[4][4];
        #pragma unroll
        for (int c = 0; c < 4; c++) { d[c][0] = 0.f; d[c][1] = 0.f; d[c][2] = 0.f; d[c][3] = 0.f; }
        #pragma unroll
        for (int st = 0; st < 8; st++) {
          const uint2 hb = lds_u32x2(sbase + OG_SH2 + ((lane >> 2) & 1) * 2048 + (w8 * 128 + st * 16 + (lane & 3) * 4) * 2);
          #pragma unroll
          for (int j = 0; j < 4; j++) mma_bf16(d[j], wv[4 * st + j].x, wv[4 * st + j].y, wv[4 * st + j].z, wv[4 * st + j].w, GEMV_B0(j, hb, sel), GEMV_B1(j, hb, sel));
        }
        #pragma unroll
        for (int e = 0; e < 4; e++) d[0][e] = (d[0][e] + d[1][e]) + (d[2][e] + d[3][e]);
        const float4 r = gemv_out(d[0], lane);
        sts_f32x4(sbase + OG_SRED + w8 * 512 + (((lane >> 4) * 2 + (lane & 1)) * 32 + ((lane >> 2) & 3) * 8 + (lane & 2) * 2) * 4, r.x, r.y, r.z, r.w);
      }
      named_bar_sync(9, 256);
      if (t2 < 64) {
        float gp[8], up[8];
        #pragma unroll
        for (int w = 0; w < 8; w++) { gp[w] = lds_f32(sbase + OG_SRED + w * 512 + t2 * 4); up[w] = lds_f32(sbase + OG_SRED + w * 512 + 256 + t2 * 4); }
        const float gs = ((gp[0] + gp[1]) + (gp[2] + gp[3])) + ((gp[4] + gp[5]) + (gp[6] + gp[7]));
        const float us = ((up[0] + up[1]) + (up[2] + up[3])) + ((up[4] + up[5]) + (up[6] + up[7]));
        asm volatile("st.shared.u16 [%0], %1;" :: "r"(sbase + OG_SGU + t2 * 2), "h"((uint16_t)pack_bf16(silu_bf(rbf(gs)) * rbf(us), 0.f)) : "memory");
      }
      named_bar_sync(9, 256);
      TS(9, lane == 0);
      float d[4][4];
      #pragma unroll
      for (int c = 0; c < 4; c++) { d[c][0] = 0.f; d[c][1] = 0.f; d[c][2] = 0.f; d[c][3] = 0.f; }
      #pragma unroll
      for (int st = 0; st < 2; st++) {
        const uint2 g = lds_u32x2(sbase + OG_SGU + ((lane >> 2) & 1) * 64 + st * 32 + (lane & 3) * 8);
        #pragma unroll
        for (int j = 0; j < 4; j++) {
          const uint32_t b0 = GEMV_B0(j, g, sel), b1 = GEMV_B1(j, g, sel);
          mma_bf16(d[j & 1], wd[4 * st + j].x, wd[4 * st + j].y, wd[4 * st + j].z, wd[4 * st + j].w, b0, b1);
          mma_bf16(d[2 + (j & 1)], wd[8 + 4 * st + j].x, wd[8 + 4 * st + j].y, wd[8 + 4 * st + j].z, wd[8 + 4 * st + j].w, b0, b1);
        }
      }
      #pragma unroll
      for (int e = 0; e < 4; e++) { d[0][e] += d[1][e]; d[2][e] += d[3][e]; }
      const float4 y0 = gemv_out(d[0], lane), y1 = gemv_out(d[2], lane);
      float* yp = g_ypart + (size_t)(bx * 2 + (lane & 1)) * T_D + w8 * 128 + (lane >> 2) * 8 + (lane & 2) * 2;
      st_tagged4(yp, y0.x, y0.y, y0.z, y0.w);
      st_tagged4(yp + 64, y1.x, y1.y, y1.z, y1.w);
      named_bar_sync(9, 256);
      if (t2 == 0) hint_arrive(CNT_Y);
    }
    TS(10, lane == 0);
    TL_CLK(4, 1, threadIdx.x == 128);
}

__device__ STW_INL void store_warp(Scratch* hm, uint32_t sbase, const CUtensorMap* tmO, int item0, int n_items) {
  if (elect_one()) {
    const uint32_t bars = sbase + AT_SBAR, b_q0 = bars + 80, b_ob = bars + 96, b_ordy = bars + 104, b_acq = bars + 264;
    mbar_wait(bars + 232, 0);
    const uint32_t bx = lds_u32(bars + 240);
    const unsigned int* cnt = &g_hcnt[32 * (1 + OG_MT(bx)) + 2];
    #pragma unroll 1
    for (int q = 0; q < 4 * n_items; q++) {
      const int item = item0 + (q >> 2) * 128, h = (q >> 1) & 1, w = q & 1;
      const bool last = (q >> 2) == n_items - 1;
      mbar_wait(b_ordy + 8 * (q & 3), q >> 2);
      store_o(tmO, (h ? (last ? sbase + AT_SQ + 32768 : sbase + 2 * 32768) : sbase + AT_SQ) + w * 8192, (item >> 4) * 2 + h, (item & 15) * 128 + w * 64);
      if (w) {
        PF(1 + (q >> 1));
        bulk_wait_read<0>();
        mbar_arrive(h ? b_ob : b_q0);
        bulk_wait<0>();
        fence_proxy_async_global();
        red_release_add(&g_hcnt[32 * (1 + (item & 15)) + 2 + (item >> 7)], 1u);
        if (bx < 128 && q == (n_items == 2 ? 5 : 3)) { spin_until(cnt, 16u); mbar_arrive(b_acq); }
      }
    }
    if (bx < 128) { spin_until(&g_hcnt[0], 8u); spin_until(cnt + 1, 16u); mbar_arrive(b_acq); }
  }
}

#define TUNE_PARAM
__device__ __forceinline__ int h_first(int item, int c) { const int j = (item >> 4) + 3 * c; return j >= 7 ? j - 7 : j; }
__device__ __forceinline__ int item_of(int b) {
  const int B = b >> 4, r = b & 15;
  return (((B >> HB) << HB) + (r >> (4 - HB))) * 16 + ((B & ((1 << HB) - 1)) << (4 - HB)) + (r & ((16 >> HB) - 1));
}
__global__ void __launch_bounds__(384, 1)
fused_kernel(const bf16* __restrict__ x, const bf16* __restrict__ cvec, const bf16* __restrict__ w_mod, Scratch* hm, uint32_t zero, TUNE_PARAM
            const uint8_t* __restrict__ pf_wo, const bf16* __restrict__ kc, const bf16* __restrict__ vc, const bf16* __restrict__ w_r,
            const bf16* __restrict__ w_gate, const bf16* __restrict__ w_up, const bf16* __restrict__ w_down, bf16* __restrict__ out,
            const __grid_constant__ CUtensorMap tmM, const __grid_constant__ CUtensorMap tmW, const __grid_constant__ CUtensorMap tmK,
            const __grid_constant__ CUtensorMap tmV, const __grid_constant__ CUtensorMap tmO, const __grid_constant__ CUtensorMap tmOl, const __grid_constant__ CUtensorMap tmWo,
            const __grid_constant__ CUtensorMap tmX, const __grid_constant__ CUtensorMap tmOut)
{
  extern __shared__ __align__(1024) uint8_t smem_raw[];
  const uint32_t sbase = smem_u32(smem_raw);
  const uint32_t bars = sbase + AT_SBAR;
  const uint32_t b_full = bars, b_empty = bars + 40;
  const uint32_t b_q0 = bars + 80, b_q1 = bars + 88;
  const uint32_t b_ob = bars + 96;
  const uint32_t b_ordy = bars + 104;
  const uint32_t b_pin = bars + 136;
  const uint32_t b_a0 = bars + 144;
  const uint32_t b_x = bars + 160;
  const uint32_t b_w = bars + 152, b_go = bars + 224;
  const uint32_t b_bx = bars + 232, s_bx = bars + 240;
  const uint32_t b_hs = bars + 464;
  const uint32_t b_tab = bars + 272;
  const int wid = __shfl_sync(0xffffffffu, threadIdx.x >> 5, 0), wg = wid >> 2;
  const bool single = blockIdx.x >= AT_NFULL;
  const int item0 = __shfl_sync(0xffffffffu, blockIdx.x < 128 ? item_of(blockIdx.x) : item_of(blockIdx.x - 4) + 128, 0), n_items = __shfl_sync(0xffffffffu, single ? 1 : 2, 0);
  const uint32_t t0 = clock_lo();
  TL_START(3);
  HS(0);
  if (threadIdx.x == 0) {
    if (sbase & 1023u) __trap();
    for (int i = 0; i < 5; i++) { mbar_init(b_full + 8 * i, 1); mbar_init(b_empty + 8 * i, 2); mbar_init(b_hs + 8 * i, i < 2 && !single ? 4 : 1); }
    sts_u32(bars + 504, 5u);
    mbar_init(b_q0, 1); mbar_init(b_q1, 8); mbar_init(b_ob, 1);
    for (int i = 0; i < 4; i++) mbar_init(b_ordy + 8 * i, 4);
    mbar_init(b_pin, 1); mbar_init(b_a0, 8); mbar_init(b_x, 1); mbar_init(b_w, 1); mbar_init(b_go, 1); mbar_init(b_bx, 1);
    for (int i = 0; i < 8; i++) mbar_init(b_tab + 8 * i, i < 2 ? 1 : 2);
    mbar_init(bars + 168, 1); mbar_init(bars + 176, 1); mbar_init(bars + 184, 8); mbar_init(bars + 192, 2);
    mbar_init(bars + 200, 8); mbar_init(bars + 208, 1); mbar_init(bars + 216, 1); mbar_init(bars + 264, 1);
    sts_u32x4(sbase + OG_SMISC + 32, 0x3F803F80u, 0x3F803F80u, 0x3F803F80u, 0x3F803F80u);
    fence_mbar_init();
    if (blockIdx.x < 128) {
      HS(1);
      wait_clock(t0, XDLY);
      mbar_expect_tx(b_x, 32768);
      bulk_load_hint(sbase + 3 * 32768, x + (size_t)blockIdx.x * 16 * T_D, 32768, b_x, pol_normal());
    }
    mbar_arrive(b_tab); mbar_arrive(b_tab + 8);
  }

  if (wg == 0) {
    reg_dealloc<AT_PREG>();
    if (wid == 0) { __syncwarp(); named_bar_arrive(6, 128); named_bar_arrive(11, 160); named_bar_arrive(12, 160); }
    if (wid >= 2) {
      named_bar_sync(6, 128);
      wait_clock(t0, GDLY2);
      gather_table(hm, sbase + 4 * 32768, b_tab, wid & 1, threadIdx.x & 31);
      if (threadIdx.x == 64) PF(0);
      if (threadIdx.x == 96 && !single) { sleep_until(t0, 40000); spin_until(&g_hcnt[32 * (1 + (item0 & 15))], 7u); mbar_arrive(b_w); }
    } else if (wid == 1) {
      named_bar_sync(6, 128);
      if (item0 < 112) {
        const int lane = threadIdx.x & 31;
        #pragma unroll 1
        for (int j0 = h_first(item0, 0), j1 = h_first(item0, 1); j0 < 16 || j1 < 16;) {
          const int c = j1 < j0, j = c ? j1 : j0;
          bf16* hg = hm->o + (size_t)((item0 & 15) * 128 + c * 64 + (lane >> 3)) * O_LD + O_H + (lane & 7) * 8 + j * 64;
          uint32_t src = sbase + AT_SQ - 16384 + c * 8192 + (lane >> 3) * 128 + (((lane ^ (lane >> 3)) & 7) << 4);
          mbar_wait(b_hs + 8 * c, j >= 7 && j < 14);
          #pragma unroll 1
          for (int i = 0; i < 4; i++, hg += 16 * O_LD, src += 2048) {
            uint4 v[4];
            #pragma unroll
            for (int k = 0; k < 4; k++) v[k] = lds_u32x4((src ^ ((k & 1) * 64)) + k * 512);
            #pragma unroll
            for (int k = 0; k < 4; k++) *reinterpret_cast<uint4*>(hg + k * 4 * O_LD) = v[k];
          }
          __syncwarp();
          if (lane == 0) mbar_arrive(b_hs + 16 + 8 * c);
          if (c) j1 += 7; else j0 += 7;
        }
        if (lane == 0) mbar_arrive(b_go);
        if (lane == 0) red_release_add(&g_hcnt[32 * (1 + (item0 & 15))], 1u);
      }
      sleep_until(t0, 26000);
      const uint32_t v = assign_tile(hm, t0, threadIdx.x & 31);
      if (threadIdx.x == 32) { sts_u32(s_bx, v); mbar_arrive(b_bx); }
      __syncwarp();
      store_warp(hm, sbase, &tmO, item0, n_items);
      __syncwarp();
    } else {
     if (elect_one()) {
      const uint64_t pol = policy_evict_first();
      prefetch_tmap(&tmW); prefetch_tmap(&tmX); prefetch_tmap(&tmWo); prefetch_tmap(&tmOl);
      if (single) {
        prefetch_tmap(&tmM);
        #pragma unroll 1
        for (uint32_t i = 0, buf = 0; i < 44; i++) {
          wait_clock(t0, i < 12 ? (blockIdx.x < 128 ? WDLY + W_OFF : WDLY) + (i & 3) * W_GAP + (i >> 2) * W_RND : W_LATE);
          #pragma unroll 1
          for (uint32_t spin = 0, n = 0; spin < (1u << 24) && n <= i; spin++) asm volatile("ld.volatile.shared.u32 %0, [%1];" : "=r"(n) : "r"(bars + 504) : "memory");
          mbar_expect_tx(bars + 464 + buf * 8, 32768);
          tma_load_2d_hint(sbase + (buf + (buf > 2 ? 2 : 0)) * 32768, &tmM, mod_col0(blockIdx.x - AT_NFULL, (int)(i >> 2) - 3), (i & 3) * 256, bars + 464 + buf * 8, pol);
          if (++buf == 5) buf = 0;
        }
        mbar_wait(b_go, 0);
      }
      {
        const uint64_t polx = XPOL ? pol : pol_normal();
        #pragma unroll 1
        for (int j = 0; j < T_D / 64; j++) {
          const uint32_t fb = b_full + 8 * (j & 3);
          mbar_wait(b_empty + 8 * (j & 3), ((j >> 2) & 1) ^ 1);
          mbar_expect_tx(fb, j == 0 ? 65536 : j == T_D / 64 - 1 ? 32768 : 49152);
          if (j < 2) wait_clock(t0, j ? ST1_T : PRE_T);
          if (j == 3) mbar_wait(b_a0, 0);
          if (j < 4) HS(2 + j);
          tma_load_3d_hint(sbase + (j & 3) * 32768, &tmW, j * 64, (item0 >> 4) * 4, fb, pol);
          if (j == 0) { wait_clock(t0, A_T); tma_load_2d_hint(sbase + AT_SQ, &tmX, 0, (item0 & 15) * 128, fb, polx); }
          if (j < T_D / 64 - 1) tma_load_2d_hint(sbase + AT_SQ + ((j + 1) & 3) * 16384, &tmX, (j + 1) * 64, (item0 & 15) * 128, fb, polx);
        }
      }
      uint32_t slot = 0, ph = 1;
      #pragma unroll 1
      for (int it = 0; it < n_items; it++) {
        const int item = item0 + it * 128, hp = item >> 4, qt = item & 15;
        const bool first = it == 0;
        if (!first) {
          #pragma unroll 1
          for (int j = 0; j < T_D / 64; j++) {
            const uint32_t sl = ring_slot(qp_pos(j, 1)), fb = b_full + 8 * sl;
            mbar_wait(b_empty + 8 * sl, ring_par(qp_pos(j, 1)) ^ ((j >> 2) & 1) ^ 1);
            mbar_expect_tx(fb, 49152);
            tma_load_3d_hint(sbase + sl * 32768, &tmW, j * 64, hp * 4, fb, pol);
            if (j == 0) { mbar_wait(b_q0, 0); mbar_wait(b_q1, 0); mbar_wait(b_w, 0); fence_proxy_async_global(); }
            tma_load_2d_hint(sbase + AT_SQ + (j & 3) * 16384, &tmOl, O_H + j * 64, qt * 128, fb, pol);
          }
        }
        #pragma unroll 1
        for (int j = 0; j < 4 * AT_NBLK; j++) {
          const bool isv = (j > 0 && !(j & 1)) || j == 4 * AT_NBLK - 1;
          const int row = hp * 2 * T_SEQ + (isv ? (j - 1) >> 1 : (j + 1) >> 1) * 128;
          const uint32_t fb = b_full + 8 * slot;
          mbar_wait(b_empty + 8 * slot, ph);
          if (!first && j == 3) mbar_wait(b_ob, 0);
          if (first && j == 4 && item0 < 112) mbar_wait(b_go, 0);
          mbar_expect_tx(fb, 32768);
          tma_load_2d_hint(sbase + slot * 32768, isv ? &tmV : &tmK, 0, row, fb, pol);
          tma_load_2d_hint(sbase + slot * 32768 + 16384, isv ? &tmV : &tmK, 64, row, fb, pol);
          if (it == 1 && isv && j >= 2 * WO_LATE && j < 2 * WO_LATE + 32 && blockIdx.x < 64)
            l2_prefetch_bulk(pf_wo + (size_t)blockIdx.x * 131072 + ((j >> 1) - WO_LATE) * 8192, 8192);
          if (++slot == 5) { slot = 0; ph ^= 1; }
        }
      }
      mbar_wait(b_bx, 0);
      const uint32_t bx = lds_u32(s_bx);
      if (bx < 128) {
        if (single) mbar_wait(b_go, 1);
        tail_producer(hm, bx, sbase, 0, n_items - 1, pol, &tmOl, &tmWo, &tmX, w_down);
      }
     }
    }
    __syncwarp();
    PSV(0, threadIdx.x == 96, t0);
    mbar_wait(b_bx, 0);
    const uint32_t bx = __shfl_sync(0xffffffffu, lds_u32(s_bx), 0);
    if (bx < 128) tail_exchange(hm, bx, sbase, __shfl_sync(0xffffffffu, threadIdx.x, threadIdx.x), &tmOut, out);
  } else {
    if (wg == 1 && blockIdx.x < 128) head_first(hm, sbase + 4 * 32768 + 4096, threadIdx.x - 128, cvec, w_mod);
    named_bar_sync(10 + wg, 160);
    if (wg == 2 && blockIdx.x < 128) head_stats(hm, sbase + 3 * 32768, b_x, threadIdx.x - 256);
    if (single) {
      mod_rest(hm, t0, sbase, bars + 464, threadIdx.x - 128, (int)blockIdx.x - AT_NFULL, cvec, w_r);
      named_bar_sync(5, 256);
      if (threadIdx.x == 128) mbar_arrive(b_go);
    }
    if (wg == 1) { wait_clock(t0, GDLY); head_gather(hm, sbase + 4 * 32768, threadIdx.x - 128); }
    reg_alloc<AT_CREG>();
    const int cwg = wg - 1;
    const int tid = __shfl_sync(0xffffffffu, threadIdx.x, threadIdx.x) & 127;
    const int warp = wid & 3, lane = tid & 31;
    const uint32_t dbase = (sbase & 0x3FFFFu) >> 4;
    const uint32_t k_base = dbase + (1u << 16);
    const uint32_t v_base = dbase + (1024u << 16);
    const uint32_t w_base = dbase + (512u << 16);
    const uint32_t frag = cwg * 8192 + (16 * warp + (lane & 7) + 8 * ((lane >> 3) & 1)) * 128;
    if (cwg == 1) named_bar_arrive(1, 256);
    bool raw = false;
    constexpr int nkb = T_D / 64;
    float acc[128], c0, c1;
    {
      FS(0, 0);
      uint32_t af[2][16], rw[16];
      uint4 tb[4];
      uint32_t xa[4];
      #pragma unroll
      for (int st = 0; st < 4; st++) xa[st] = __shfl_sync(0xffffffffu, (sbase + AT_SQ + frag + (((lane >> 4) ^ (lane & 7)) << 4)) ^ (st * 32), lane);
      const uint32_t xt = __shfl_sync(0xffffffffu, sbase + 4 * 32768 + (lane & 3) * 16, lane);
      auto qp_fetch = [&](int j) {
        #pragma unroll
        for (int st = 0; st < 4; st++) {
          ldmatrix_x4(xa[st] + (j & 3) * 16384, rw[4 * st], rw[4 * st + 1], rw[4 * st + 2], rw[4 * st + 3]);
          tb[st] = lds_u32x4(xt + (j & 15) * 256 + st * 64);
        }
      };
      zero_regs(acc);
      #pragma unroll
      for (int i = 0; i < 16; i++) af[1][i] = 0u;
      const float2* stp = hm->stat + (item0 & 15) * 256 + (cwg * 4 + warp) * 32 + (lane & 3) * 8 + (lane >> 2);
      HS(4);
      wait_clock(t0, SDLY);
      float2 sv = ld_tagged2(stp);
      named_bar_sync(5, 256);
      mbar_wait(b_full, 0);
      HS(5);
      qp_fetch(0);
      #pragma unroll 1
      for (unsigned int spin = 0; spin < (1u << 22); spin++) {
        if (__all_sync(0xffffffffu, (__float_as_uint(sv.x) != 0u) & (__float_as_uint(sv.y) != 0u))) break;
        sv = ld_tagged2(stp);
      }
      HS(6);
      if (lane == 0) mbar_arrive(b_a0 + (rw[3] & rw[7] & rw[11] & rw[15] & zero));
      const uint32_t st = ln_stat(sv.x + __shfl_xor_sync(0xffffffffu, sv.x, 1), sv.y + __shfl_xor_sync(0xffffffffu, sv.y, 1)), so = __shfl_xor_sync(0xffffffffu, st, 2);
      const uint32_t sta = (lane & 2) ? so : st, stb = (lane & 2) ? st : so;
      const uint32_t mean_a = __byte_perm(sta, 0u, 0x1010), mean_b = __byte_perm(stb, 0u, 0x1010), sd_a = __byte_perm(sta, 0u, 0x3232), sd_b = __byte_perm(stb, 0u, 0x3232);
      c0 = AT_C * rcp_approx(bfhi(sta)); c1 = AT_C * rcp_approx(bfhi(stb));
      sts_u32(sbase + OG_SMISC + 256 + (cwg * 4 + warp) * 64 + (lane & 28) + (lane & 2) * 16, __float_as_uint((lane & 2) ? c1 : c0));
      int jst = item0 < 112 ? h_first(item0, cwg) : 99;
      #pragma unroll 1
      for (int j2 = 0; j2 < nkb; j2 += 2) {
        #pragma unroll
        for (int u = 0; u < 2; u++) {
          const int j = j2 + u;
          const uint32_t bt = b_tab + 4 * ((j + 1) & 15);
          if (u == 1) {
            #pragma unroll 1
            for (uint32_t z = 0; z < zero; z++)
              #pragma unroll
              for (int i = 0; i < 16; i += 4) sts_u32x4(xt + i * 4, af[1][i], af[1][i + 1], af[1][i + 2], af[1][i + 3]);
          }
          bool ok = mbar_test(b_full + 8 * (j & 3), (j >> 2) & 1);
          if (u == 1) ok &= mbar_test(bt, 0);
          auto conv = [&](int st) {
            af[u][4 * st + 0] = bfma2(bsub2(rw[4 * st + 0], mean_a), tb[st].x, bmul2(tb[st].z, sd_a));
            af[u][4 * st + 1] = bfma2(bsub2(rw[4 * st + 1], mean_b), tb[st].x, bmul2(tb[st].z, sd_b));
            af[u][4 * st + 2] = bfma2(bsub2(rw[4 * st + 2], mean_a), tb[st].y, bmul2(tb[st].w, sd_a));
            af[u][4 * st + 3] = bfma2(bsub2(rw[4 * st + 3], mean_b), tb[st].y, bmul2(tb[st].w, sd_b));
          };
          conv(0); conv(1);
          if (RSO < 2) { conv(2); conv(3); }
          if (!ok || j == jst) {
            if (!ok) { mbar_wait(b_full + 8 * (j & 3), (j >> 2) & 1); if (u == 1) mbar_wait(bt, 0); }
            if (j == jst) {
              if (j >= 7) mbar_wait(b_hs + 16 + 8 * cwg, j >= 14);
              #pragma unroll
              for (int st = 0; st < 4; st++) stmatrix_x4(xa[st] - 16384, af[u][4 * st], af[u][4 * st + 1], af[u][4 * st + 2], af[u][4 * st + 3]);
              __syncwarp();
              if (lane == 0) mbar_arrive(b_hs + 8 * cwg);
              jst += 7;
            }
          }
          if (RSO == 0) qp_fetch(j + 1);
          if (cwg == 1 && j == nkb - QP_STAG) named_bar_sync(7, 256);
          const bool turn = QTN > 0 && (uint32_t)(j - QT0) <= (uint32_t)(QTN - 1);
          if (turn) named_bar_sync(1 + cwg, 256);
          const uint32_t b_lo = w_base + (j & 3) * 2048;
          wgmma_fence();
          wgmma_m64n256k16_rs_tb<0>(acc, af[u][0], af[u][1], af[u][2], af[u][3], b_lo, 1);
          if (RSO == 1) qp_fetch(j + 1);
          wgmma_m64n256k16_rs_tb<128>(acc, af[u][4], af[u][5], af[u][6], af[u][7], b_lo, 1);
          if (RSO == 2) { conv(2); conv(3); qp_fetch(j + 1); wgmma_fence(); }
          wgmma_m64n256k16_rs_tb<256>(acc, af[u][8], af[u][9], af[u][10], af[u][11], b_lo, 1);
          wgmma_m64n256k16_rs_tb<384>(acc, af[u][12], af[u][13], af[u][14], af[u][15], b_lo, 1);
          wgmma_commit();
          if (turn) named_bar_arrive(1 + (cwg ^ 1), 256);
          if (cwg == 0 && j == nkb - 1) named_bar_arrive(7, 256);
          if (j == 0) HS(7);
          wgmma_wait<1>();
          if (tid == 0) mbar_arrive(j > 0 ? b_empty + 8 * ((j - 1) & 3) : b_pin);
        }
      }
      wgmma_wait<0>();
      fence_regs(acc);
    }
    #pragma unroll 1
    for (int it = 0;;) {
      const int item = item0 + it * 128, hp = item >> 4;
      const bool more = it + 1 < n_items;
      const int ta = __shfl_sync(0xffffffffu, 4 * it, 0);
      FS(2 * it, 1);
      PS(1 + 2 * it, threadIdx.x == 256);
      if (tid == 0) mbar_arrive(b_empty + 24);
      float o[64], s[64];
      uint32_t p[32], q[32];
      #pragma unroll
      for (int i = 0; i < 32; i++) q[i] = pack_bf16(acc[2 * i] * ((i & 1) ? c1 : c0), acc[2 * i + 1] * ((i & 1) ? c1 : c0));
      zero_regs(s);
      const uint32_t sq = sbase + AT_SQ + cwg * 8192;
      const bool last_wg1 = cwg == 1 && !more;
      float mc0, mc1, al0 = 1.0f, al1 = 1.0f, l0 = 0.f, l1 = 0.f, lp0 = 0.f, lp1 = 0.f;
      bool redo0 = false;
      FS(2 * it, 2);
      {
        uint32_t dep = zero;
        #pragma unroll
        for (int i = 0; i < 32; i += PINQ) dep &= q[i];
        mbar_wait(b_full + 8 * ring_slot(ta) + dep, ring_par(ta));
      }
      named_bar_sync(1 + cwg, 256);
      FS(2 * it, 3);
      issue_qk(s, q, k_base + ring_slot(ta) * 2048);
      named_bar_arrive(1 + (cwg ^ 1), 256);
      const uint32_t rdy = (uint32_t)mbar_test(b_full + 8 * ring_slot(ta + 1), ring_par(ta + 1));
      bool ready = rdy & mbar_test(b_full + 8 * ring_slot(ta + 2), ring_par(ta + 2));
      stage_o(*reinterpret_cast<const float (*)[64]>(&acc[64]), c0, c1, sbase + AT_SQ + 32768 + frag, lane);
      wgmma_wait<0>();
      fence_regs(s);
      if (tid == 0) mbar_arrive(b_empty + 8 * ring_slot(ta));
      mc0 = 0.f; mc1 = 0.f;
      if (!raw) {
        raw = softmax_mode(s, mc0, mc1);
        if (__builtin_expect(!raw, 0)) softmax_sub(s, mc0, mc1);
      }
      softmax_exp<0, 64>(s);
      stage_qregs(q, sbase + AT_SQ + frag, lane);
      pack_p(p, s);
      zero_regs(o);
      FS(2 * it, 4);
      uint32_t ks = ring_slot(ta + 1), vs = ring_slot(ta + 2), kp = ring_par(ta + 1), vp = ring_par(ta + 2);
      if (!ready) { mbar_wait(b_full + 8 * ks, kp); mbar_wait(b_full + 8 * vs, vp); }
      #pragma unroll 1
      for (int n = 1; n < 2 * AT_NBLK; n++) {
        named_bar_sync(1 + cwg, 256);
        issue_qk(s, q, k_base + ks * 2048);
        if (n == AT_NBLK + 1) {
          redo0 = finish_l(lp0, lp1);
          if (!redo0) stage_o(o, lp0, lp1, sbase + AT_SQ + frag, lane);
        }
        issue_pv(o, p, v_base + vs * 2048, (n & 15) != 1);
        if (!(last_wg1 && n == 2 * AT_NBLK - 1)) named_bar_arrive(1 + (cwg ^ 1), 256);
        wgmma_wait<1>();
        fence_regs(s);
        if (tid == 0) mbar_arrive(b_empty + 8 * ks);
        if (__builtin_expect(!raw || (n + 1) >> 1 == AT_NBLK / 2, 0)) {
          if (n == AT_NBLK - 1) {
            #pragma unroll
            for (int J = 0; J < 16; J += 2)
              ldmatrix_x4(sbase + AT_SQ + 32768 + frag + (J >> 3) * 16384 + ((((J & 7) + (lane >> 4)) ^ (lane & 7)) << 4), q[2 * J], q[2 * J + 1], q[2 * J + 2], q[2 * J + 3]);
          }
          if (n == AT_NBLK && lane == 0) mbar_arrive(b_q1);
          if (!raw) {
            const float m0 = mc0, m1 = mc1;
            const bool ok = softmax_mode(s, mc0, mc1);
            if (n == AT_NBLK) raw = ok;
            else {
              mc0 = mc0 - AT_HEAD > m0 ? mc0 : m0; mc1 = mc1 - AT_HEAD > m1 ? mc1 : m1;
              al0 = ex2_approx(m0 - mc0); al1 = ex2_approx(m1 - mc1);
            }
            if (!raw) softmax_sub(s, mc0, mc1);
          }
        }
        softmax_exp<0, AT_SPLIT>(s);
        add_rowsum(p, l0, l1);
        if (tid == 0) {
          uint32_t dep = zero & __float_as_uint(l0) & __float_as_uint(l1);
          #pragma unroll
          for (int i = AT_SPLIT - AT_PIN - PINB; i < AT_SPLIT - PINB; i += 2) dep &= __float_as_uint(s[i]) & __float_as_uint(s[i + 1]);
          mbar_arrive(b_pin + dep);
        }
        wgmma_wait<0>();
        fence_regs(o);
        if (tid == 0) mbar_arrive(b_empty + 8 * vs);
        ks += 2; if (ks >= 5) { ks -= 5; kp ^= 1; }
        vs += 2; if (vs >= 5) { vs -= 5; vp ^= 1; }
        ready = mbar_test(b_full + 8 * ks, kp) & mbar_test(b_full + 8 * vs, vp);
        softmax_exp<AT_SPLIT, 64>(s);
        pack_p(p, s);
        if (n == AT_NBLK) { lp0 = l0; lp1 = l1; l0 = 0.f; l1 = 0.f; }
        if (__builtin_expect(!raw || !ready || n == AT_NBLK + 1, 0)) {
        if (n == AT_NBLK + 1 && !redo0) { fence_proxy_async(); __syncwarp(); if (lane == 0) mbar_arrive(b_ordy + 8 * cwg); }
        if (!raw && __any_sync(0xffffffffu, al0 != 1.0f || al1 != 1.0f)) {
          rescale_o(o, al0, al1);
          l0 *= al0; l1 *= al1;
          al0 = 1.0f; al1 = 1.0f;
        }
        if (!ready && n < 2 * AT_NBLK - 1) {
          mbar_wait(b_full + 8 * ks, kp);
          mbar_wait(b_full + 8 * vs, vp);
        }
        }
      }
      FS(2 * it + 1, 5);
      const uint32_t vl = ring_slot(ta + 63);
      vs = ring_slot(ta + 62);
      const uint32_t ob = more ? sbase + vs * 32768 : sbase + AT_SQ + 32768;
      mbar_wait(b_full + 8 * vl, ring_par(ta + 63));
      issue_pv(o, p, v_base + vl * 2048, 1);
      add_rowsum(p, l0, l1);
      const bool overflow = finish_l(l0, l1);
      mbar_wait(b_empty + 8 * vs, ring_par(ta + 62));
      wgmma_wait<0>();
      fence_regs(o);
      if (tid == 0) mbar_arrive(b_empty + 8 * vl);
      FS(2 * it + 1, 6);
      if (overflow) stage_qregs(q, ob + frag, lane);
      else stage_o(o, l0, l1, ob + frag, lane);
      if (__builtin_expect(overflow || redo0, 0)) {
        __syncwarp();
        #pragma unroll 1
        for (int h = redo0 ? 0 : 1; h < (overflow ? 2 : 1); h++)
          attn_rows_exact(h ? ob + cwg * 8192 : sq, warp, lane, kc + (size_t)(hp * 2 + h) * T_SEQ * T_DH, vc + (size_t)(hp * 2 + h) * T_SEQ * T_DH);
        fence_proxy_async();
        __syncwarp();
        if (lane == 0 && redo0) mbar_arrive(b_ordy + 8 * cwg);
        raw = false;
      }
      fence_proxy_async();
      __syncwarp();
      if (lane == 0) mbar_arrive(b_ordy + 16 + 8 * cwg);
      named_bar_sync(3 + cwg, 128);
      FS(2 * it + 1, 7);
      PS(2 + 2 * it, threadIdx.x == 256);
      if (++it == n_items) break;
      FS(2 * it, 0);
      zero_regs(acc);
      auto ss_step = [&](int j, int accumulate) {
        const uint32_t slot = ring_slot(qp_pos(j, 1));
        mbar_wait(b_full + 8 * slot, ring_par(qp_pos(j, 1)) ^ ((j >> 2) & 1));
        if (cwg == 1 && j == nkb - QP_STAG) named_bar_sync(7, 256);
        const uint32_t a_lo = dbase + ((AT_SQ + cwg * 8192) >> 4) + (1u << 16) + (j & 3) * 1024, b_lo = w_base + slot * 2048;
        wgmma_fence();
        wgmma_m64n256k16_ss_tb<0, 0>(acc, a_lo, b_lo, accumulate);
        wgmma_m64n256k16_ss_tb<2, 128>(acc, a_lo, b_lo, 1);
        wgmma_m64n256k16_ss_tb<4, 256>(acc, a_lo, b_lo, 1);
        wgmma_m64n256k16_ss_tb<6, 384>(acc, a_lo, b_lo, 1);
        wgmma_commit();
        return b_empty + 8 * slot;
      };
      uint32_t prev = ss_step(0, 0);
      c0 = lds_f32(sbase + OG_SMISC + 256 + (cwg * 4 + warp) * 64 + (lane & 28)); c1 = lds_f32(sbase + OG_SMISC + 288 + (cwg * 4 + warp) * 64 + (lane & 28));
      #pragma unroll 1
      for (int j = 1; j < nkb; j++) {
        const uint32_t cur = ss_step(j, 1);
        if (cwg == 0 && j == nkb - 1) named_bar_arrive(7, 256);
        wgmma_wait<1>();
        if (tid == 0) mbar_arrive(prev);
        prev = cur;
      }
      wgmma_wait<0>();
      fence_regs(acc);
    }
    if (single) {
      named_bar_sync(5, 256);
      if (threadIdx.x == 128) {
        #pragma unroll 1
        for (int i = 4; i < 8; i++) {
          mbar_arrive(b_full + 8 * ring_slot(i));
          mbar_arrive(b_empty + 8 * ring_slot(i)); mbar_arrive(b_empty + 8 * ring_slot(i));
        }
        mbar_arrive(b_go);
      }
      named_bar_sync(5, 256);
    }
    TL_CLK(3, 1, threadIdx.x == 128);
    TL_CTA(1, threadIdx.x == 256);
    TL_END(3, tid == 0);
    __syncwarp();
    QDUMP();
    TL_MARK2(19, tid == 0 && !single);
    mbar_wait(b_bx, 0);
    const uint32_t bx = __shfl_sync(0xffffffffu, lds_u32(s_bx), 0);
    if (bx < 128) {
      tail_consumer(hm, bx, sbase, tid, wid - 4, w_gate, w_up);
    }
  }
}

typedef CUresult (*PFN_encodeTiled)(CUtensorMap*, CUtensorMapDataType, cuuint32_t, void*, const cuuint64_t*, const cuuint64_t*,
                                    const cuuint32_t*, const cuuint32_t*, CUtensorMapInterleave, CUtensorMapSwizzle,
                                    CUtensorMapL2promotion, CUtensorMapFloatOOBfill);

CUtensorMap make_map_2d(PFN_encodeTiled enc, const void* ptr, uint64_t inner, uint64_t outer, uint64_t stride_bytes, uint32_t box_inner, uint32_t box_outer) {
  CUtensorMap m;
  cuuint64_t gd[2] = {inner, outer}; cuuint64_t gs[1] = {stride_bytes};
  cuuint32_t bx[2] = {box_inner, box_outer}; cuuint32_t es[2] = {1, 1};
  enc(&m, CU_TENSOR_MAP_DATA_TYPE_BFLOAT16, 2, const_cast<void*>(ptr), gd, gs, bx, es, CU_TENSOR_MAP_INTERLEAVE_NONE,
      CU_TENSOR_MAP_SWIZZLE_128B, CU_TENSOR_MAP_L2_PROMOTION_L2_128B, CU_TENSOR_MAP_FLOAT_OOB_FILL_NONE);
  return m;
}

CUtensorMap make_map_3d(PFN_encodeTiled enc, const void* ptr, uint64_t cols, uint64_t rows, uint32_t box_rows, uint32_t chunks) {
  CUtensorMap m;
  cuuint64_t gd[3] = {64, rows, cols / 64}; cuuint64_t gs[2] = {cols * 2, 128};
  cuuint32_t bx[3] = {64, box_rows, chunks}; cuuint32_t es[3] = {1, 1, 1};
  enc(&m, CU_TENSOR_MAP_DATA_TYPE_BFLOAT16, 3, const_cast<void*>(ptr), gd, gs, bx, es, CU_TENSOR_MAP_INTERLEAVE_NONE,
      CU_TENSOR_MAP_SWIZZLE_128B, CU_TENSOR_MAP_L2_PROMOTION_L2_128B, CU_TENSOR_MAP_FLOAT_OOB_FILL_NONE);
  return m;
}

}

extern "C" void kernel_launch(void* const* d_in, const int* in_sizes, int n_in, void* d_out, int out_size) {
  const bf16* x      = (const bf16*)d_in[0];
  const bf16* kc     = (const bf16*)d_in[1];
  const bf16* vc     = (const bf16*)d_in[2];
  const bf16* wq     = (const bf16*)d_in[3];
  const bf16* wo     = (const bf16*)d_in[4];
  const bf16* w_r    = (const bf16*)d_in[6];
  const bf16* w_gate = (const bf16*)d_in[7];
  const bf16* w_up   = (const bf16*)d_in[8];
  const bf16* w_down = (const bf16*)d_in[9];
  const bf16* cvec   = (const bf16*)d_in[10];
  const bf16* w_mod  = (const bf16*)d_in[11];
  bf16* out = (bf16*)d_out;

  static PFN_encodeTiled enc = nullptr;
  static void* p_hm = nullptr;
  if (!enc) {
    void* fn = nullptr; cudaDriverEntryPointQueryResult qres;
    cudaGetDriverEntryPoint("cuTensorMapEncodeTiled", &fn, cudaEnableDefault, &qres);
    enc = (PFN_encodeTiled)fn;
    cudaGetSymbolAddress(&p_hm, g_scr);
    cudaFuncSetAttribute(fused_kernel, cudaFuncAttributeMaxDynamicSharedMemorySize, (int)AT_SMEM);
  }
  const CUtensorMap tm_m   = make_map_2d(enc, w_mod, 6 * T_D, T_D, 6 * T_D * 2, 64, 256);
  const CUtensorMap tm_wq  = make_map_3d(enc, wq, T_DQKV, T_D, 64, 4);
  const CUtensorMap tm_k   = make_map_2d(enc, kc, T_DH, (uint64_t)T_NH * T_SEQ, T_DH * 2, 64, 128);
  const CUtensorMap tm_v   = make_map_2d(enc, vc, T_DH, (uint64_t)T_NH * T_SEQ, T_DH * 2, 64, 128);
  const CUtensorMap tm_ost = make_map_2d(enc, ((Scratch*)p_hm)->o, O_LD, T_SEQ, O_LD * 2, 64, 64);
  const CUtensorMap tm_old = make_map_2d(enc, ((Scratch*)p_hm)->o, O_LD, T_SEQ, O_LD * 2, 64, 128);
  const CUtensorMap tm_wo  = make_map_2d(enc, wo, T_D, T_DQKV, T_D * 2, 64, 64);
  const CUtensorMap tm_x   = make_map_2d(enc, x, T_D, T_SEQ, T_D * 2, 64, 128);
  const CUtensorMap tm_out = make_map_2d(enc, out, T_D, T_SEQ, T_D * 2, 64, 128);

#define TUNE_ARG
  fused_kernel<<<132, 384, AT_SMEM, cudaStreamPerThread>>>(x, cvec, w_mod, (Scratch*)p_hm, 0u, TUNE_ARG (const uint8_t*)wo, kc, vc, w_r, w_gate, w_up, w_down, out,
             tm_m, tm_wq, tm_k, tm_v, tm_ost, tm_old, tm_wo, tm_x, tm_out);
}
```

```cpp
#include <cuda_runtime.h>
#include <cuda_bf16.h>
#include <cuda.h>
#include <stdint.h>

namespace {

typedef __nv_bfloat16 bf16;

constexpr int T_SEQ = 2048, T_D = 1024, T_NH = 32, T_DH = 128, T_DQKV = 4096, T_F = 3584;

struct __align__(2048) TailMail {
  float4 part1[T_SEQ * 8];
  uint32_t key[256];
  uint4 cand[16 * 2 * 2 * 128];
  uint32_t cnt[32];
  float ypart[(T_F / 32) * 2 * T_D];
};
constexpr int O_LD = T_DQKV, O_H = 16 * T_DH;
struct __align__(2048) Scratch {
  TailMail mail;
  float mod[2 * T_D];
  float modu[16 * 512];
  float2 stat[T_SEQ * 2];
  uint32_t gkey[160];
  uint8_t col[8 * 1536];
  unsigned int hcnt[17 * 32];
  float scal[4];
  __align__(1024) bf16 o[T_SEQ * O_LD];
};
__device__ Scratch g_scr;
#define g_part1 hm->mail.part1
#define g_key hm->mail.key
#define g_cand hm->mail.cand
#define CNT_Y hm->mail.cnt
#define g_ypart hm->mail.ypart
#define g_col hm->col
#define g_scal hm->scal
#define g_hcnt hm->hcnt

__device__ __forceinline__ uint32_t smem_u32(const void* p) { return (uint32_t)__cvta_generic_to_shared(p); }
__device__ __forceinline__ void mbar_init(uint32_t bar, uint32_t cnt) { asm volatile("mbarrier.init.shared::cta.b64 [%0], %1;" :: "r"(bar), "r"(cnt)); }
__device__ __forceinline__ void mbar_expect_tx(uint32_t bar, uint32_t bytes) { asm volatile("mbarrier.arrive.expect_tx.shared::cta.b64 _, [%0], %1;" :: "r"(bar), "r"(bytes) : "memory"); }
__device__ __forceinline__ void mbar_arrive(uint32_t bar) { asm volatile("mbarrier.arrive.shared::cta.b64 _, [%0];" :: "r"(bar) : "memory"); }
__device__ __forceinline__ void mbar_wait(uint32_t bar, uint32_t parity) {
  asm volatile("{\n.reg .pred p;\nLAB_WAIT:\nmbarrier.try_wait.parity.shared::cta.b64 p, [%0], %1;\n@!p bra LAB_WAIT;\n}\n" :: "r"(bar), "r"(parity) : "memory");
}
__device__ __forceinline__ bool mbar_test(uint32_t bar, uint32_t parity) {
  uint32_t r; asm volatile("{\n.reg .pred p;\nmbarrier.test_wait.parity.shared::cta.b64 p, [%1], %2;\nselp.u32 %0, 1, 0, p;\n}\n" : "=r"(r) : "r"(bar), "r"(parity) : "memory");
  return r != 0;
}
__device__ __forceinline__ void fence_mbar_init() { asm volatile("fence.mbarrier_init.release.cluster;" ::: "memory"); }
__device__ __forceinline__ uint64_t policy_evict_first() {
  uint64_t p; asm volatile("createpolicy.fractional.L2::evict_first.b64 %0, 1.0;" : "=l"(p)); return p;
}
__device__ __forceinline__ void tma_load_2d_hint(uint32_t dst, const CUtensorMap* map, int c0, int c1, uint32_t bar, uint64_t pol) {
  asm volatile("cp.async.bulk.tensor.2d.shared::cluster.global.mbarrier::complete_tx::bytes.L2::cache_hint [%0], [%1, {%3, %4}], [%2], %5;"
    :: "r"(dst), "l"(map), "r"(bar), "r"(c0), "r"(c1), "l"(pol) : "memory");
}
__device__ __forceinline__ void tma_load_3d_hint(uint32_t dst, const CUtensorMap* map, int c1, int c2, uint32_t bar, uint64_t pol) {
  asm volatile("cp.async.bulk.tensor.3d.shared::cluster.global.mbarrier::complete_tx::bytes.L2::cache_hint [%0], [%1, {%6, %3, %4}], [%2], %5;"
    :: "r"(dst), "l"(map), "r"(bar), "r"(c1), "r"(c2), "l"(pol), "r"(0) : "memory");
}
__device__ __forceinline__ void tma_store_2d(const CUtensorMap* map, uint32_t src, int c0, int c1) {
  asm volatile("cp.async.bulk.tensor.2d.global.shared::cta.bulk_group [%0, {%2, %3}], [%1];" :: "l"(map), "r"(src), "r"(c0), "r"(c1) : "memory");
}
__device__ __forceinline__ void prefetch_tmap(const CUtensorMap* map) { asm volatile("prefetch.tensormap [%0];" :: "l"(map) : "memory"); }
__device__ __forceinline__ void l2_prefetch_bulk(const void* p, uint32_t bytes) {
  asm volatile("cp.async.bulk.prefetch.L2.global [%0], %1;" :: "l"(p), "r"(bytes) : "memory");
}
__device__ __forceinline__ void bulk_commit() { asm volatile("cp.async.bulk.commit_group;" ::: "memory"); }
template<int N> __device__ __forceinline__ void bulk_wait_read() { asm volatile("cp.async.bulk.wait_group.read %0;" :: "n"(N) : "memory"); }
template<int N> __device__ __forceinline__ void bulk_wait() { asm volatile("cp.async.bulk.wait_group %0;" :: "n"(N) : "memory"); }
__device__ __forceinline__ void named_bar_sync(int id, int nthreads) { asm volatile("bar.sync %0, %1;" :: "r"(id), "r"(nthreads) : "memory"); }
__device__ __forceinline__ void named_bar_arrive(int id, int nthreads) { asm volatile("bar.arrive %0, %1;" :: "r"(id), "r"(nthreads) : "memory"); }
__device__ __forceinline__ void wgmma_fence() { asm volatile("wgmma.fence.sync.aligned;" ::: "memory"); }
__device__ __forceinline__ void wgmma_commit() { asm volatile("wgmma.commit_group.sync.aligned;" ::: "memory"); }
template<int N> __device__ __forceinline__ void wgmma_wait() { asm volatile("wgmma.wait_group.sync.aligned %0;" :: "n"(N) : "memory"); }
template<int R> __device__ __forceinline__ void reg_alloc() { asm volatile("setmaxnreg.inc.sync.aligned.u32 %0;" :: "n"(R)); }
template<int R> __device__ __forceinline__ void reg_dealloc() { asm volatile("setmaxnreg.dec.sync.aligned.u32 %0;" :: "n"(R)); }
__device__ __forceinline__ bool elect_one() {
  uint32_t pred; asm volatile("{\n.reg .pred p;\nelect.sync _|p, 0xffffffff;\nselp.u32 %0, 1, 0, p;\n}\n" : "=r"(pred)); return pred != 0;
}
__device__ __forceinline__ uint32_t pack_bf16(float lo, float hi) {
  uint32_t r; asm("cvt.rn.bf16x2.f32 %0, %1, %2;" : "=r"(r) : "f"(hi), "f"(lo)); return r;
}
__device__ __forceinline__ void stmatrix_x4(uint32_t addr, uint32_t r0, uint32_t r1, uint32_t r2, uint32_t r3) {
  asm volatile("stmatrix.sync.aligned.m8n8.x4.shared.b16 [%0], {%1, %2, %3, %4};" :: "r"(addr), "r"(r0), "r"(r1), "r"(r2), "r"(r3) : "memory");
}
__device__ __forceinline__ void fence_proxy_async() { asm volatile("fence.proxy.async.shared::cta;" ::: "memory"); }
__device__ __forceinline__ float ex2_approx(float x) { float y; asm("ex2.approx.ftz.f32 %0, %1;" : "=f"(y) : "f"(x)); return y; }
template<int N> __device__ __forceinline__ void fence_regs(float (&r)[N]) {
  #pragma unroll
  for (int i = 0; i < N; i++) asm volatile("" : "+f"(r[i]) :: "memory");
}
template<int N> __device__ __forceinline__ void zero_regs(float (&r)[N]) {
  #pragma unroll
  for (int i = 0; i < N; i += 2) asm volatile("mov.b64 {%0, %1}, 0;" : "=f"(r[i]), "=f"(r[i + 1]));
}
__device__ __forceinline__ float rbf(float x) { return __uint_as_float(pack_bf16(0.f, x)); }
__device__ __forceinline__ float bflo(uint32_t v) { return __uint_as_float(v << 16); }
__device__ __forceinline__ float bfhi(uint32_t v) { return __uint_as_float(v & 0xffff0000u); }

#define TL_START(k) do {} while (0)
#define TL_END(k, cond) do {} while (0)
#define TL_CTA(i, cond) do {} while (0)
#define FS(slot, k) do {} while (0)
#define QS(idx) do {} while (0)
#define QDUMP() do {} while (0)
#define TL_MARK2(k, cond) do {} while (0)
#define TL_CLK(k, i, cond) do {} while (0)

#define HS(k) do {} while (0)
#define HSD(k, dep) do {} while (0)
#define HSDUMP() do {} while (0)
#define PS(k, cond) do {} while (0)
#define PSV(k, cond, v) do {} while (0)
#define PF(k) do {} while (0)
#define TS(k, cond) do {} while (0)
template <int OFFA, int OFFB>
__device__ __forceinline__ void wgmma_m64n256k16_ss_tb(float (&d)[128], uint32_t a_lo, uint32_t b_lo, int scaleD) {
  asm volatile("{\n.reg .pred p;\n.reg .b32 ta, tb;\n.reg .b64 da, db;\nsetp.ne.b32 p, %130, 0;\n"
    "add.u32 ta, %128, %131;\nadd.u32 tb, %129, %132;\n"
    "mov.b64 da, {ta, 0x40000040};\nmov.b64 db, {tb, 0x40000040};\n"
    "wgmma.mma_async.sync.aligned.m64n256k16.f32.bf16.bf16 "
    "{%0, %1, %2, %3, %4, %5, %6, %7, %8, %9, %10, %11, %12, %13, %14, %15, %16, %17, %18, %19, %20, %21, %22, %23, %24, %25, %26, %27, %28, %29, %30, %31, %32, %33, %34, %35, %36, %37, %38, %39, %40, %41, %42, %43, %44, %45, %46, %47, %48, %49, %50, %51, %52, %53, %54, %55, %56, %57, %58, %59, %60, %61, %62, %63, %64, %65, %66, %67, %68, %69, %70, %71, %72, %73, %74, %75, %76, %77, %78, %79, %80, %81, %82, %83, %84, %85, %86, %87, %88, %89, %90, %91, %92, %93, %94, %95, %96, %97, %98, %99, %100, %101, %102, %103, %104, %105, %106, %107, %108, %109, %110, %111, %112, %113, %114, %115, %116, %117, %118, %119, %120, %121, %122, %123, %124, %125, %126, %127}, "
    "da, db, p, 1, 1, 0, 1;\n}\n"
    : "+f"(d[0]), "+f"(d[1]), "+f"(d[2]), "+f"(d[3]), "+f"(d[4]), "+f"(d[5]), "+f"(d[6]), "+f"(d[7]), "+f"(d[8]), "+f"(d[9]), "+f"(d[10]), "+f"(d[11]), "+f"(d[12]), "+f"(d[13]), "+f"(d[14]), "+f"(d[15]), "+f"(d[16]), "+f"(d[17]), "+f"(d[18]), "+f"(d[19]), "+f"(d[20]), "+f"(d[21]), "+f"(d[22]), "+f"(d[23]), "+f"(d[24]), "+f"(d[25]), "+f"(d[26]), "+f"(d[27]), "+f"(d[28]), "+f"(d[29]), "+f"(d[30]), "+f"(d[31]), "+f"(d[32]), "+f"(d[33]), "+f"(d[34]), "+f"(d[35]), "+f"(d[36]), "+f"(d[37]), "+f"(d[38]), "+f"(d[39]), "+f"(d[40]), "+f"(d[41]), "+f"(d[42]), "+f"(d[43]), "+f"(d[44]), "+f"(d[45]), "+f"(d[46]), "+f"(d[47]), "+f"(d[48]), "+f"(d[49]), "+f"(d[50]), "+f"(d[51]), "+f"(d[52]), "+f"(d[53]), "+f"(d[54]), "+f"(d[55]), "+f"(d[56]), "+f"(d[57]), "+f"(d[58]), "+f"(d[59]), "+f"(d[60]), "+f"(d[61]), "+f"(d[62]), "+f"(d[63]), "+f"(d[64]), "+f"(d[65]), "+f"(d[66]), "+f"(d[67]), "+f"(d[68]), "+f"(d[69]), "+f"(d[70]), "+f"(d[71]), "+f"(d[72]), "+f"(d[73]), "+f"(d[74]), "+f"(d[75]), "+f"(d[76]), "+f"(d[77]), "+f"(d[78]), "+f"(d[79]), "+f"(d[80]), "+f"(d[81]), "+f"(d[82]), "+f"(d[83]), "+f"(d[84]), "+f"(d[85]), "+f"(d[86]), "+f"(d[87]), "+f"(d[88]), "+f"(d[89]), "+f"(d[90]), "+f"(d[91]), "+f"(d[92]), "+f"(d[93]), "+f"(d[94]), "+f"(d[95]), "+f"(d[96]), "+f"(d[97]), "+f"(d[98]), "+f"(d[99]), "+f"(d[100]), "+f"(d[101]), "+f"(d[102]), "+f"(d[103]), "+f"(d[104]), "+f"(d[105]), "+f"(d[106]), "+f"(d[107]), "+f"(d[108]), "+f"(d[109]), "+f"(d[110]), "+f"(d[111]), "+f"(d[112]), "+f"(d[113]), "+f"(d[114]), "+f"(d[115]), "+f"(d[116]), "+f"(d[117]), "+f"(d[118]), "+f"(d[119]), "+f"(d[120]), "+f"(d[121]), "+f"(d[122]), "+f"(d[123]), "+f"(d[124]), "+f"(d[125]), "+f"(d[126]), "+f"(d[127])
    : "r"(a_lo), "r"(b_lo), "r"(scaleD), "n"(OFFA), "n"(OFFB));
}

template <int OFFA, int OFFB>
__device__ __forceinline__ void wgmma_m64n128k16_ss_tb(float (&d)[64], uint32_t a_lo, uint32_t b_lo, int scaleD) {
  asm volatile("{\n.reg .pred p;\n.reg .b32 ta, tb;\n.reg .b64 da, db;\nsetp.ne.b32 p, %66, 0;\n"
    "add.u32 ta, %64, %67;\nadd.u32 tb, %65, %68;\n"
    "mov.b64 da, {ta, 0x40000040};\nmov.b64 db, {tb, 0x40000040};\n"
    "wgmma.mma_async.sync.aligned.m64n128k16.f32.bf16.bf16 "
    "{%0, %1, %2, %3, %4, %5, %6, %7, %8, %9, %10, %11, %12, %13, %14, %15, %16, %17, %18, %19, %20, %21, %22, %23, %24, %25, %26, %27, %28, %29, %30, %31, %32, %33, %34, %35, %36, %37, %38, %39, %40, %41, %42, %43, %44, %45, %46, %47, %48, %49, %50, %51, %52, %53, %54, %55, %56, %57, %58, %59, %60, %61, %62, %63}, "
    "da, db, p, 1, 1, 0, 1;\n}\n"
    : "+f"(d[0]), "+f"(d[1]), "+f"(d[2]), "+f"(d[3]), "+f"(d[4]), "+f"(d[5]), "+f"(d[6]), "+f"(d[7]), "+f"(d[8]), "+f"(d[9]), "+f"(d[10]), "+f"(d[11]), "+f"(d[12]), "+f"(d[13]), "+f"(d[14]), "+f"(d[15]), "+f"(d[16]), "+f"(d[17]), "+f"(d[18]), "+f"(d[19]), "+f"(d[20]), "+f"(d[21]), "+f"(d[22]), "+f"(d[23]), "+f"(d[24]), "+f"(d[25]), "+f"(d[26]), "+f"(d[27]), "+f"(d[28]), "+f"(d[29]), "+f"(d[30]), "+f"(d[31]), "+f"(d[32]), "+f"(d[33]), "+f"(d[34]), "+f"(d[35]), "+f"(d[36]), "+f"(d[37]), "+f"(d[38]), "+f"(d[39]), "+f"(d[40]), "+f"(d[41]), "+f"(d[42]), "+f"(d[43]), "+f"(d[44]), "+f"(d[45]), "+f"(d[46]), "+f"(d[47]), "+f"(d[48]), "+f"(d[49]), "+f"(d[50]), "+f"(d[51]), "+f"(d[52]), "+f"(d[53]), "+f"(d[54]), "+f"(d[55]), "+f"(d[56]), "+f"(d[57]), "+f"(d[58]), "+f"(d[59]), "+f"(d[60]), "+f"(d[61]), "+f"(d[62]), "+f"(d[63])
    : "r"(a_lo), "r"(b_lo), "r"(scaleD), "n"(OFFA), "n"(OFFB));
}

template <int OFFB>
__device__ __forceinline__ void wgmma_m64n256k16_rs_tb(float (&d)[128], uint32_t a0, uint32_t a1, uint32_t a2, uint32_t a3, uint32_t b_lo, int scaleD) {
  asm volatile("{\n.reg .pred p;\n.reg .b32 tb;\n.reg .b64 db;\nsetp.ne.b32 p, %133, 0;\n"
    "add.u32 tb, %132, %134;\n"
    "mov.b64 db, {tb, 0x40000040};\n"
    "wgmma.mma_async.sync.aligned.m64n256k16.f32.bf16.bf16 "
    "{%0, %1, %2, %3, %4, %5, %6, %7, %8, %9, %10, %11, %12, %13, %14, %15, %16, %17, %18, %19, %20, %21, %22, %23, %24, %25, %26, %27, %28, %29, %30, %31, %32, %33, %34, %35, %36, %37, %38, %39, %40, %41, %42, %43, %44, %45, %46, %47, %48, %49, %50, %51, %52, %53, %54, %55, %56, %57, %58, %59, %60, %61, %62, %63, %64, %65, %66, %67, %68, %69, %70, %71, %72, %73, %74, %75, %76, %77, %78, %79, %80, %81, %82, %83, %84, %85, %86, %87, %88, %89, %90, %91, %92, %93, %94, %95, %96, %97, %98, %99, %100, %101, %102, %103, %104, %105, %106, %107, %108, %109, %110, %111, %112, %113, %114, %115, %116, %117, %118, %119, %120, %121, %122, %123, %124, %125, %126, %127}, "
    "{%128, %129, %130, %131}, db, p, 1, 1, 1;\n}\n"
    : "+f"(d[0]), "+f"(d[1]), "+f"(d[2]), "+f"(d[3]), "+f"(d[4]), "+f"(d[5]), "+f"(d[6]), "+f"(d[7]), "+f"(d[8]), "+f"(d[9]), "+f"(d[10]), "+f"(d[11]), "+f"(d[12]), "+f"(d[13]), "+f"(d[14]), "+f"(d[15]), "+f"(d[16]), "+f"(d[17]), "+f"(d[18]), "+f"(d[19]), "+f"(d[20]), "+f"(d[21]), "+f"(d[22]), "+f"(d[23]), "+f"(d[24]), "+f"(d[25]), "+f"(d[26]), "+f"(d[27]), "+f"(d[28]), "+f"(d[29]), "+f"(d[30]), "+f"(d[31]), "+f"(d[32]), "+f"(d[33]), "+f"(d[34]), "+f"(d[35]), "+f"(d[36]), "+f"(d[37]), "+f"(d[38]), "+f"(d[39]), "+f"(d[40]), "+f"(d[41]), "+f"(d[42]), "+f"(d[43]), "+f"(d[44]), "+f"(d[45]), "+f"(d[46]), "+f"(d[47]), "+f"(d[48]), "+f"(d[49]), "+f"(d[50]), "+f"(d[51]), "+f"(d[52]), "+f"(d[53]), "+f"(d[54]), "+f"(d[55]), "+f"(d[56]), "+f"(d[57]), "+f"(d[58]), "+f"(d[59]), "+f"(d[60]), "+f"(d[61]), "+f"(d[62]), "+f"(d[63]), "+f"(d[64]), "+f"(d[65]), "+f"(d[66]), "+f"(d[67]), "+f"(d[68]), "+f"(d[69]), "+f"(d[70]), "+f"(d[71]), "+f"(d[72]), "+f"(d[73]), "+f"(d[74]), "+f"(d[75]), "+f"(d[76]), "+f"(d[77]), "+f"(d[78]), "+f"(d[79]), "+f"(d[80]), "+f"(d[81]), "+f"(d[82]), "+f"(d[83]), "+f"(d[84]), "+f"(d[85]), "+f"(d[86]), "+f"(d[87]), "+f"(d[88]), "+f"(d[89]), "+f"(d[90]), "+f"(d[91]), "+f"(d[92]), "+f"(d[93]), "+f"(d[94]), "+f"(d[95]), "+f"(d[96]), "+f"(d[97]), "+f"(d[98]), "+f"(d[99]), "+f"(d[100]), "+f"(d[101]), "+f"(d[102]), "+f"(d[103]), "+f"(d[104]), "+f"(d[105]), "+f"(d[106]), "+f"(d[107]), "+f"(d[108]), "+f"(d[109]), "+f"(d[110]), "+f"(d[111]), "+f"(d[112]), "+f"(d[113]), "+f"(d[114]), "+f"(d[115]), "+f"(d[116]), "+f"(d[117]), "+f"(d[118]), "+f"(d[119]), "+f"(d[120]), "+f"(d[121]), "+f"(d[122]), "+f"(d[123]), "+f"(d[124]), "+f"(d[125]), "+f"(d[126]), "+f"(d[127])
    : "r"(a0), "r"(a1), "r"(a2), "r"(a3), "r"(b_lo), "r"(scaleD), "n"(OFFB));
}

template <int OFFB>
__device__ __forceinline__ void wgmma_m64n128k16_rs_tb(float (&d)[64], uint32_t a0, uint32_t a1, uint32_t a2, uint32_t a3, uint32_t b_lo, int scaleD) {
  asm volatile("{\n.reg .pred p;\n.reg .b32 tb;\n.reg .b64 db;\nsetp.ne.b32 p, %69, 0;\n"
    "add.u32 tb, %68, %70;\n"
    "mov.b64 db, {tb, 0x40000040};\n"
    "wgmma.mma_async.sync.aligned.m64n128k16.f32.bf16.bf16 "
    "{%0, %1, %2, %3, %4, %5, %6, %7, %8, %9, %10, %11, %12, %13, %14, %15, %16, %17, %18, %19, %20, %21, %22, %23, %24, %25, %26, %27, %28, %29, %30, %31, %32, %33, %34, %35, %36, %37, %38, %39, %40, %41, %42, %43, %44, %45, %46, %47, %48, %49, %50, %51, %52, %53, %54, %55, %56, %57, %58, %59, %60, %61, %62, %63}, "
    "{%64, %65, %66, %67}, db, p, 1, 1, 1;\n}\n"
    : "+f"(d[0]), "+f"(d[1]), "+f"(d[2]), "+f"(d[3]), "+f"(d[4]), "+f"(d[5]), "+f"(d[6]), "+f"(d[7]), "+f"(d[8]), "+f"(d[9]), "+f"(d[10]), "+f"(d[11]), "+f"(d[12]), "+f"(d[13]), "+f"(d[14]), "+f"(d[15]), "+f"(d[16]), "+f"(d[17]), "+f"(d[18]), "+f"(d[19]), "+f"(d[20]), "+f"(d[21]), "+f"(d[22]), "+f"(d[23]), "+f"(d[24]), "+f"(d[25]), "+f"(d[26]), "+f"(d[27]), "+f"(d[28]), "+f"(d[29]), "+f"(d[30]), "+f"(d[31]), "+f"(d[32]), "+f"(d[33]), "+f"(d[34]), "+f"(d[35]), "+f"(d[36]), "+f"(d[37]), "+f"(d[38]), "+f"(d[39]), "+f"(d[40]), "+f"(d[41]), "+f"(d[42]), "+f"(d[43]), "+f"(d[44]), "+f"(d[45]), "+f"(d[46]), "+f"(d[47]), "+f"(d[48]), "+f"(d[49]), "+f"(d[50]), "+f"(d[51]), "+f"(d[52]), "+f"(d[53]), "+f"(d[54]), "+f"(d[55]), "+f"(d[56]), "+f"(d[57]), "+f"(d[58]), "+f"(d[59]), "+f"(d[60]), "+f"(d[61]), "+f"(d[62]), "+f"(d[63])
    : "r"(a0), "r"(a1), "r"(a2), "r"(a3), "r"(b_lo), "r"(scaleD), "n"(OFFB));
}

template <int OFFB>
__device__ __forceinline__ void wgmma_m64n128k16_rs(float (&d)[64], uint32_t a0, uint32_t a1, uint32_t a2, uint32_t a3, uint32_t b_lo, int scaleD) {
  asm volatile("{\n.reg .pred p;\n.reg .b32 tb;\n.reg .b64 db;\nsetp.ne.b32 p, %69, 0;\n"
    "add.u32 tb, %68, %70;\n"
    "mov.b64 db, {tb, 0x40000040};\n"
    "wgmma.mma_async.sync.aligned.m64n128k16.f32.bf16.bf16 "
    "{%0, %1, %2, %3, %4, %5, %6, %7, %8, %9, %10, %11, %12, %13, %14, %15, %16, %17, %18, %19, %20, %21, %22, %23, %24, %25, %26, %27, %28, %29, %30, %31, %32, %33, %34, %35, %36, %37, %38, %39, %40, %41, %42, %43, %44, %45, %46, %47, %48, %49, %50, %51, %52, %53, %54, %55, %56, %57, %58, %59, %60, %61, %62, %63}, "
    "{%64, %65, %66, %67}, db, p, 1, 1, 0;\n}\n"
    : "+f"(d[0]), "+f"(d[1]), "+f"(d[2]), "+f"(d[3]), "+f"(d[4]), "+f"(d[5]), "+f"(d[6]), "+f"(d[7]), "+f"(d[8]), "+f"(d[9]), "+f"(d[10]), "+f"(d[11]), "+f"(d[12]), "+f"(d[13]), "+f"(d[14]), "+f"(d[15]), "+f"(d[16]), "+f"(d[17]), "+f"(d[18]), "+f"(d[19]), "+f"(d[20]), "+f"(d[21]), "+f"(d[22]), "+f"(d[23]), "+f"(d[24]), "+f"(d[25]), "+f"(d[26]), "+f"(d[27]), "+f"(d[28]), "+f"(d[29]), "+f"(d[30]), "+f"(d[31]), "+f"(d[32]), "+f"(d[33]), "+f"(d[34]), "+f"(d[35]), "+f"(d[36]), "+f"(d[37]), "+f"(d[38]), "+f"(d[39]), "+f"(d[40]), "+f"(d[41]), "+f"(d[42]), "+f"(d[43]), "+f"(d[44]), "+f"(d[45]), "+f"(d[46]), "+f"(d[47]), "+f"(d[48]), "+f"(d[49]), "+f"(d[50]), "+f"(d[51]), "+f"(d[52]), "+f"(d[53]), "+f"(d[54]), "+f"(d[55]), "+f"(d[56]), "+f"(d[57]), "+f"(d[58]), "+f"(d[59]), "+f"(d[60]), "+f"(d[61]), "+f"(d[62]), "+f"(d[63])
    : "r"(a0), "r"(a1), "r"(a2), "r"(a3), "r"(b_lo), "r"(scaleD), "n"(OFFB));
}

__device__ __forceinline__ uint4 ldg_nc_v4(const void* p) {
  uint4 v;
    asm volatile("{\n.reg .b64 pol;\ncreatepolicy.fractional.L2::evict_first.b64 pol, 1.0;\n"
                 "ld.global.nc.L1::no_allocate.L2::cache_hint.v4.u32 {%0, %1, %2, %3}, [%4], pol;\n}\n" : "=r"(v.x), "=r"(v.y), "=r"(v.z), "=r"(v.w) : "l"(p));
  return v;
}
__device__ __forceinline__ uint64_t pol_normal() {
  uint64_t p; asm volatile("createpolicy.fractional.L2::evict_normal.b64 %0, 1.0;" : "=l"(p)); return p;
}
__device__ __forceinline__ float rcp_approx(float x) { float y; asm("rcp.approx.ftz.f32 %0, %1;" : "=f"(y) : "f"(x)); return y; }
__device__ __forceinline__ float sigmoid_f(float v) { return rcp_approx(1.0f + ex2_approx(v * -1.4426950408889634f)); }
__device__ __forceinline__ float silu_bf(float v) { return rbf(v * sigmoid_f(v)); }
__device__ __forceinline__ uint32_t rank_key(float r, int idx) {
  const uint32_t b = __float_as_uint(r) >> 16;
  const uint32_t u = (r != r) ? 0u : ((b & 0x8000u) ? (~b & 0xffffu) : (b | 0x8000u));
  return (u << 16) | (0xffffu - (uint32_t)idx);
}
__device__ __forceinline__ void warp_top2(uint32_t& k1, uint32_t& k2) {
  const uint32_t m1 = __reduce_max_sync(0xffffffffu, k1);
  k2 = __reduce_max_sync(0xffffffffu, k1 == m1 ? k2 : k1);
  k1 = m1;
}
__device__ __forceinline__ uint32_t bmul2(uint32_t a, uint32_t b) { uint32_t r; asm("mul.rn.bf16x2 %0, %1, %2;" : "=r"(r) : "r"(a), "r"(b)); return r; }
__device__ __forceinline__ uint32_t badd2(uint32_t a, uint32_t b) { uint32_t r; asm("add.rn.bf16x2 %0, %1, %2;" : "=r"(r) : "r"(a), "r"(b)); return r; }
__device__ __forceinline__ uint32_t bsub2(uint32_t a, uint32_t b) { uint32_t r; asm("sub.rn.bf16x2 %0, %1, %2;" : "=r"(r) : "r"(a), "r"(b)); return r; }
__device__ __forceinline__ float sqrt_approx(float x) { float y; asm("sqrt.approx.f32 %0, %1;" : "=f"(y) : "f"(x)); return y; }
__device__ __forceinline__ uint32_t ln_norm2(uint32_t x1, uint32_t mb2, float inv) {
  const uint32_t d = bsub2(x1, mb2);
  return pack_bf16(bflo(d) * inv, bfhi(d) * inv);
}
__device__ __forceinline__ uint32_t ln_mod2(uint32_t x1, uint32_t mb2, float inv, uint32_t c1, uint32_t sb) { return badd2(bmul2(ln_norm2(x1, mb2, inv), c1), sb); }
__device__ __forceinline__ void ldmatrix_x4(uint32_t addr, uint32_t& r0, uint32_t& r1, uint32_t& r2, uint32_t& r3) {
  asm volatile("ldmatrix.sync.aligned.m8n8.x4.shared.b16 {%0, %1, %2, %3}, [%4];" : "=r"(r0), "=r"(r1), "=r"(r2), "=r"(r3) : "r"(addr) : "memory");
}
__device__ __forceinline__ uint4 ldg_stream_v4(const void* p, uint64_t pol) {
  uint4 v; asm volatile("ld.global.nc.L1::no_allocate.L2::cache_hint.L2::128B.v4.u32 {%0, %1, %2, %3}, [%4], %5;" : "=r"(v.x), "=r"(v.y), "=r"(v.z), "=r"(v.w) : "l"(p), "l"(pol)); return v;
}
__device__ __forceinline__ void bulk_load_hint(uint32_t dst, const void* src, uint32_t bytes, uint32_t bar, uint64_t pol) {
  asm volatile("cp.async.bulk.shared::cluster.global.mbarrier::complete_tx::bytes.L2::cache_hint [%0], [%1], %2, [%3], %4;"
    :: "r"(dst), "l"(src), "r"(bytes), "r"(bar), "l"(pol) : "memory");
}
__device__ __forceinline__ void red_release_add(unsigned int* p, unsigned int v) { asm volatile("red.release.gpu.global.add.u32 [%0], %1;" :: "l"(p), "r"(v) : "memory"); }
__device__ __forceinline__ unsigned int ld_acquire(const unsigned int* p) { unsigned int v; asm volatile("ld.acquire.gpu.global.u32 %0, [%1];" : "=r"(v) : "l"(p) : "memory"); return v; }
__device__ __forceinline__ void spin_until(const unsigned int* p, unsigned int target) {
  #pragma unroll 1
  for (unsigned int i = 0; i < (1u << 22); i++) { if (ld_acquire(p) >= target) return; }
}
__device__ __forceinline__ float lds_f32(uint32_t a) { float v; asm volatile("ld.shared.f32 %0, [%1];" : "=f"(v) : "r"(a) : "memory"); return v; }
__device__ __forceinline__ uint2 lds_u32x2(uint32_t a) { uint2 v; asm volatile("ld.shared.v2.u32 {%0, %1}, [%2];" : "=r"(v.x), "=r"(v.y) : "r"(a) : "memory"); return v; }
__device__ __forceinline__ uint32_t lds_u32(uint32_t a) { uint32_t v; asm volatile("ld.shared.u32 %0, [%1];" : "=r"(v) : "r"(a) : "memory"); return v; }
__device__ __forceinline__ void sts_u32(uint32_t a, uint32_t v) { asm volatile("st.shared.u32 [%0], %1;" :: "r"(a), "r"(v) : "memory"); }
__device__ __forceinline__ void sts_u32x2(uint32_t a, uint32_t x, uint32_t y) { asm volatile("st.shared.v2.u32 [%0], {%1, %2};" :: "r"(a), "r"(x), "r"(y) : "memory"); }
__device__ __forceinline__ void sts_f32(uint32_t a, float v) { asm volatile("st.shared.f32 [%0], %1;" :: "r"(a), "f"(v) : "memory"); }
__device__ __forceinline__ void sts_f32x4(uint32_t a, float x, float y, float z, float w) { asm volatile("st.shared.v4.f32 [%0], {%1, %2, %3, %4};" :: "r"(a), "f"(x), "f"(y), "f"(z), "f"(w) : "memory"); }

__device__ __forceinline__ uint4 lds_u32x4(uint32_t a) { uint4 v; asm volatile("ld.shared.v4.u32 {%0, %1, %2, %3}, [%4];" : "=r"(v.x), "=r"(v.y), "=r"(v.z), "=r"(v.w) : "r"(a) : "memory"); return v; }
__device__ __forceinline__ void sts_u32x4(uint32_t a, uint32_t x, uint32_t y, uint32_t z, uint32_t w) { asm volatile("st.shared.v4.u32 [%0], {%1, %2, %3, %4};" :: "r"(a), "r"(x), "r"(y), "r"(z), "r"(w) : "memory"); }
__device__ __forceinline__ void st_tagged(float* p, float v) {
  const uint32_t b = __float_as_uint(v);
  asm volatile("st.relaxed.gpu.global.u32 [%0], %1;" :: "l"(p), "r"(b == 0u ? 0x80000000u : b) : "memory");
}
__device__ __forceinline__ void st_tagged4(float* p, float x, float y, float z, float w) {
  const uint32_t a = __float_as_uint(x), b = __float_as_uint(y), c = __float_as_uint(z), d = __float_as_uint(w);
  asm volatile("st.relaxed.gpu.global.v4.u32 [%0], {%1, %2, %3, %4};" :: "l"(p), "r"(a == 0u ? 0x80000000u : a), "r"(b == 0u ? 0x80000000u : b),
               "r"(c == 0u ? 0x80000000u : c), "r"(d == 0u ? 0x80000000u : d) : "memory");
}
__device__ __forceinline__ void st_relaxed2(void* p, uint32_t a, uint32_t b) { asm volatile("st.relaxed.gpu.global.v2.u32 [%0], {%1, %2};" :: "l"(p), "r"(a), "r"(b) : "memory"); }
__device__ __forceinline__ float4 ld_tagged4(const float* p) {
  float4 v; asm volatile("ld.relaxed.gpu.global.v4.f32 {%0, %1, %2, %3}, [%4];" : "=f"(v.x), "=f"(v.y), "=f"(v.z), "=f"(v.w) : "l"(p) : "memory"); return v;
}
__device__ __forceinline__ bool tagged4(const float4& v) {
  return __float_as_uint(v.x) != 0u && __float_as_uint(v.y) != 0u && __float_as_uint(v.z) != 0u && __float_as_uint(v.w) != 0u;
}
__device__ __forceinline__ void hint_arrive(uint32_t* p) { asm volatile("red.relaxed.gpu.global.add.u32 [%0], 1;" :: "l"(p) : "memory"); }
__device__ __forceinline__ void hint_wait(const uint32_t* p, uint32_t target) {
  uint32_t v = 0u;
  #pragma unroll 1
  for (unsigned int i = 0; i < (1u << 22) && v < target; i++) asm volatile("ld.relaxed.gpu.global.u32 %0, [%1];" : "=r"(v) : "l"(p) : "memory");
}
__device__ __forceinline__ void fence_proxy_async_global() { asm volatile("fence.proxy.async.global;" ::: "memory"); }

__device__ __forceinline__ void mma_bf16(float (&d)[4], uint32_t a0, uint32_t a1, uint32_t a2, uint32_t a3, uint32_t b0, uint32_t b1) {
  asm volatile("mma.sync.aligned.m16n8k16.row.col.f32.bf16.bf16.f32 {%0, %1, %2, %3}, {%4, %5, %6, %7}, {%8, %9}, {%0, %1, %2, %3};"
               : "+f"(d[0]), "+f"(d[1]), "+f"(d[2]), "+f"(d[3]) : "r"(a0), "r"(a1), "r"(a2), "r"(a3), "r"(b0), "r"(b1));
}
__device__ __forceinline__ uint32_t bfma2(uint32_t a, uint32_t b, uint32_t c) { uint32_t r; asm("fma.rn.bf16x2 %0, %1, %2, %3;" : "=r"(r) : "r"(a), "r"(b), "r"(c)); return r; }
#define XDLY 1000
#define PRE_T 1000
#define GDLY 4150
#define A_T 4800
#define SDLY 5800
#define ST1_T 6000
#define GDLY2 8000
#define WDLY 3800
#define W_OFF 2000
#define W_GAP 300
#define W_RND 3600
#define W_LATE 27000
#define CLR_T 70000
#define SGL_T 79000
#define NDUM 16
__device__ __forceinline__ uint32_t clock_lo() { uint32_t c; asm volatile("mov.u32 %0, %%clock;" : "=r"(c) :: "memory"); return c; }
__device__ __forceinline__ void wait_clock(uint32_t t0, uint32_t n) {
  #pragma unroll 1
  while (clock_lo() - t0 < n) {}
}
__device__ __forceinline__ void sleep_until(uint32_t t0, uint32_t n) {
  #pragma unroll 1
  while (clock_lo() - t0 < n) __nanosleep(500);
}
__device__ __forceinline__ float2 ld_tagged2(const float2* p) {
  float2 v; asm volatile("ld.relaxed.gpu.global.v2.f32 {%0, %1}, [%2];" : "=f"(v.x), "=f"(v.y) : "l"(p) : "memory"); return v;
}
template <int N>
__device__ __forceinline__ void gemv64(float (&d)[2][4], const uint4 (&w)[N], const uint32_t (&sv)[N / 2], int lane) {
  const int g = lane >> 2;
  const uint32_t lo = (g & 1) ? 0x1044u : 0x4410u, hi = (g & 1) ? 0x3244u : 0x4432u;
  const uint32_t lo0 = g < 2 ? lo : 0x4444u, hi0 = g < 2 ? hi : 0x4444u, lo1 = (g & 6) == 2 ? lo : 0x4444u, hi1 = (g & 6) == 2 ? hi : 0x4444u;
  #pragma unroll
  for (int i = 0; i < N; i++)
    mma_bf16(d[i & 1], w[i].x, w[i].y, w[i].z, w[i].w, __byte_perm(sv[i >> 1], 0u, (i & 1) ? hi0 : lo0), __byte_perm(sv[i >> 1], 0u, (i & 1) ? hi1 : lo1));
}
template <int NW>
__device__ __forceinline__ float gemv64_sum(const float (&d)[2][4], uint32_t scr, int t2) {
  if ((t2 & 2) == 0) sts_f32x4(scr + (t2 >> 2) * 32 + (t2 & 1) * 16, d[0][0] + d[1][0], d[0][1] + d[1][1], d[0][2] + d[1][2], d[0][3] + d[1][3]);
  named_bar_sync(NW == 8 ? 5 : 3, NW * 32);
  float sum = 0.f;
  #pragma unroll
  for (int i = 0; i < NW; i += 2) sum += lds_f32(scr + i * 256 + (t2 & 63) * 4) + lds_f32(scr + i * 256 + 256 + (t2 & 63) * 4);
  return sum;
}
__device__ __forceinline__ uint32_t silu2(uint32_t c) { return pack_bf16(silu_bf(bflo(c)), silu_bf(bfhi(c))); }
__device__ __forceinline__ void head_first(Scratch* hm, uint32_t scr, int t2, const bf16* __restrict__ cvec, const bf16* __restrict__ w_mod) {
  const int row = (blockIdx.x >> 3) * 64 + (t2 >> 5) * 16 + (t2 & 3) * 4;
  const bf16* wp = w_mod + (size_t)row * (6 * T_D) + (blockIdx.x & 4) * 256 + (blockIdx.x & 3) * 64 + (t2 & 28) * 2;
  uint4 w[4];
  #pragma unroll
  for (int i = 0; i < 4; i++) w[i] = ldg_nc_v4(wp + i * 6 * T_D);
  const uint2 c = *reinterpret_cast<const uint2*>(cvec + row);
  const uint32_t sv[2] = {silu2(c.x), silu2(c.y)};
  float d[2][4] = {{0.f, 0.f, 0.f, 0.f}, {0.f, 0.f, 0.f, 0.f}};
  gemv64<4>(d, w, sv, t2 & 31);
  const float sum = gemv64_sum<4>(d, scr, t2);
  if (t2 < 64) st_tagged(hm->modu + (blockIdx.x >> 3) * 512 + (blockIdx.x & 7) * 64 + t2, sum);
  HS(1);
}
__device__ __forceinline__ void head_stats(Scratch* hm, uint32_t xs, uint32_t b_x, int tid) {
  const int lane = tid & 31, w = tid >> 5, g = lane >> 2;
  float d[4][4] = {{0.f, 0.f, 0.f, 0.f}, {0.f, 0.f, 0.f, 0.f}, {0.f, 0.f, 0.f, 0.f}, {0.f, 0.f, 0.f, 0.f}};
  const uint32_t xa = xs + ((w & 1) * 8 + g) * 2048 + (w >> 1) * 1024 + (g & 1) * 64 + (lane & 3) * 16;
  float2* dst = hm->stat + ((blockIdx.x * 2 + (w & 1)) * 2 + (w >> 1)) * 8 + g;
  mbar_wait(b_x, 0);
  #pragma unroll
  for (int j = 0; j < 16; j++) {
    const uint4 v = lds_u32x4((xa ^ ((j & 1) * 64)) + (j >> 1) * 128);
    mma_bf16(d[2 * (j & 1)], v.x, 0x3F803F80u, v.y, 0x3F803F80u, v.x, v.y);
    mma_bf16(d[2 * (j & 1) + 1], v.z, 0x3F803F80u, v.w, 0x3F803F80u, v.z, v.w);
  }
  #pragma unroll
  for (int e = 0; e < 4; e++) d[0][e] = (d[0][e] + d[1][e]) + (d[2][e] + d[3][e]);
  const uint32_t sm = __float_as_uint((g & 1) ? d[0][3] : d[0][2]), sq = __float_as_uint((g & 1) ? d[0][1] : d[0][0]);
  if ((lane & 3) == (g >> 1)) st_relaxed2(dst, sm == 0u ? 0x80000000u : sm, sq == 0u ? 0x80000000u : sq);
  HSD(3, sm);
}
__device__ __forceinline__ void put_table(uint32_t tab, int l, bool ca, const float4& v) {
  uint32_t m0 = pack_bf16(v.x, v.y), m1 = pack_bf16(v.z, v.w);
  if (ca) { m0 = badd2(m0, 0x3F803F80u); m1 = badd2(m1, 0x3F803F80u); }
  tab += (l >> 2) * 64 + (l & 1) * 32 + (l & 2) * 2 + (ca ? 0 : 8);
  sts_u32(tab, m0); sts_u32(tab + 16, m1);
}
__device__ __forceinline__ void head_gather(Scratch* hm, uint32_t tab, int tid) {
  float4 p[16];
  #pragma unroll 1
  for (unsigned int spin = 0; spin < (1u << 22); spin++) {
    uint32_t m = 0xffffffffu;
    #pragma unroll
    for (int k = 0; k < 16; k++) p[k] = ld_tagged4(hm->modu + k * 512 + tid * 4);
    #pragma unroll
    for (int k = 0; k < 16; k++) m = min(min(m, min(__float_as_uint(p[k].x), __float_as_uint(p[k].y))), min(__float_as_uint(p[k].z), __float_as_uint(p[k].w)));
    if (m != 0u) break;
  }
  #pragma unroll
  for (int o = 1; o < 16; o <<= 1)
    #pragma unroll
    for (int k = 0; k < 16; k += 2 * o) { p[k].x += p[k + o].x; p[k].y += p[k + o].y; p[k].z += p[k + o].z; p[k].w += p[k + o].w; }
  put_table(tab, tid & 63, tid >= 64, p[0]);
  __syncwarp();
  HS(2);
}
__device__ __forceinline__ uint32_t ln_stat(float sm, float sq) {
  const float mean = sm * (1.0f / T_D), var = fmaxf(fmaf(-mean, mean, sq * (1.0f / T_D)), 0.f);
  return pack_bf16(mean, sqrt_approx(rbf(rbf(var) + 1e-05f)));
}
__device__ __forceinline__ void gather_table(Scratch* hm, uint32_t tab0, uint32_t b_tab, int a, int lane) {
  #pragma unroll 1
  for (int r = 2; r < 8; r++) {
    float4 v;
    #pragma unroll 1
    for (unsigned int spin = 0; spin < (1u << 22); spin++) {
      v = ld_tagged4(hm->mod + a * T_D + r * 128 + lane * 4);
      if (__all_sync(0xffffffffu, tagged4(v))) break;
      __nanosleep(50);
    }
    put_table(tab0 + r * 512, lane, a, v);
    __syncwarp();
    if (lane == 0) mbar_arrive(b_tab + 8 * r);
    if (r < 6) HS(2 + r);
  }
}

__device__ __forceinline__ uint32_t assign_tile(Scratch* hm, uint32_t t0, int lane) {
  uint32_t me; asm("mov.u32 %0, %%smid;" : "=r"(me));
  me = (me & 255u) + 1u;
  if (lane == 0) asm volatile("st.relaxed.gpu.global.u32 [%0], %1;" :: "l"(hm->gkey + blockIdx.x), "r"((t0 & ~511u) | me) : "memory");
  uint32_t k[5];
  #pragma unroll 1
  for (unsigned int spin = 0; spin < (1u << 20); spin++) {
    __nanosleep(200);
    #pragma unroll
    for (int m = 0; m < 5; m++) asm volatile("ld.relaxed.gpu.global.u32 %0, [%1];" : "=r"(k[m]) : "l"(hm->gkey + m * 32 + lane) : "memory");
    if (__all_sync(0xffffffffu, k[0] != 0u && k[1] != 0u && k[2] != 0u && k[3] != 0u && (k[4] != 0u || lane >= 4))) break;
  }
  uint32_t sz = 0u, g = 0u, rank = 0u, w[5];
  #pragma unroll
  for (int m = 0; m < 5; m++) w[m] = k[m] == 0u ? 0u : (k[m] & 511u) < me ? 257u : (k[m] & 511u) == me ? 65537u : 1u;
  #pragma unroll 1
  for (int i = 0; i < 16; i++) {
    const uint32_t v = __reduce_max_sync(0xffffffffu, max(max(max(k[0], k[1]), max(k[2], k[3])), k[4])), lo = (i == 15 || v < 4096u) ? 0u : v - 4096u;
    uint32_t n = 0u;
    #pragma unroll
    for (int m = 0; m < 5; m++) { const bool in = k[m] >= lo; n += in ? w[m] : 0u; w[m] = in ? 0u : w[m]; k[m] = in ? 0u : k[m]; }
    n = __reduce_add_sync(0xffffffffu, n);
    if (lane == i) sz = n & 255u;
    if (n >> 16) { g = i; rank = (n >> 8) & 255u; }
  }
  #pragma unroll 1
  for (int d = 0; d < 4; d += 2)
    if ((__reduce_max_sync(0xffffffffu, sz * 32u + lane) & 31u) == (uint32_t)lane) sz -= 2;
  const uint32_t gs = __shfl_sync(0xffffffffu, sz, g);
  const uint32_t off = __reduce_add_sync(0xffffffffu, (sz != 16u) * 32u + lane < (gs != 16u) * 32u + g ? sz : 0u);
  return rank < gs ? off + rank : 128u;
}

__device__ __forceinline__ int col_pos(int c) { return (c & ~31) + ((c >> 1) & 3) * 8 + ((c >> 3) & 3) * 2 + (c & 1); }
__device__ __forceinline__ int mod_col0(int j, int b) { return b < 0 ? (j & 1) * T_D + (b + 4) * 256 + ((j >> 1) ^ 2) * 64 : 2 * T_D + j * 512 + b * 64; }
__device__ __noinline__ void mod_rest(Scratch* hm, uint32_t t0, uint32_t sbase, uint32_t bar, int t2, int j, const bf16* __restrict__ cvec, const bf16* __restrict__ w_r) {
  const uint32_t scr = sbase + 4 * 32768 + 8192;
  const int kind = j >> 1;
  const uint2 c4 = *reinterpret_cast<const uint2*>(cvec + t2 * 4);
  sts_u32x2(scr + t2 * 8, silu2(c4.x), silu2(c4.y));
  const int w8 = t2 >> 5, t = t2 & 3, g = (t2 >> 2) & 7;
  float dot = 0.f;
  uint32_t buf = 0, par = 0;
  named_bar_sync(5, 256);
  #pragma unroll 1
  for (int b = -3; b < 8; b++) {
    float d[2][4] = {{0.f, 0.f, 0.f, 0.f}, {0.f, 0.f, 0.f, 0.f}};
    #pragma unroll 1
    for (int k = 0; k < 4; k++) {
      const uint32_t wa = sbase + (buf + (buf > 2 ? 2 : 0)) * 32768 + w8 * 4096 + t * 256;
      uint4 w[8];
      uint32_t sv[4];
      #pragma unroll
      for (int i = 0; i < 4; i++) sv[i] = lds_u32(scr + k * 512 + w8 * 64 + i * 16 + t * 4);
      mbar_wait(bar + buf * 8, par);
      #pragma unroll
      for (int i = 0; i < 8; i++) w[i] = lds_u32x4(wa + (i >> 1) * 1024 + (i & 1) * 128 + ((g ^ (t * 2 + (i & 1))) << 4));
      gemv64<8>(d, w, sv, t2 & 31);
      named_bar_sync(5, 256);
      if (t2 == 0) sts_u32(bar + 40, b * 4 + k + 18);
      if (++buf == 5) { buf = 0; par ^= 1; }
    }
    const int c0 = mod_col0(j, b);
    float v = gemv64_sum<8>(d, scr + 2048, t2);
    if (t2 < 64) {
      if (b < 0) st_tagged(hm->mod + c0 + t2, v);
      else {
        const int col = (c0 + t2) & 1023;
        uint8_t* dst = g_col + (col >> 7) * 1536;
        v = rbf(v);
        if (kind == 2) v = rbf(1.0f + v);
        const float vw = v * __bfloat162float(w_r[col]);
        dot += vw;
        if (kind == 2) {
          reinterpret_cast<bf16*>(dst)[col_pos(col & 127)] = __float2bfloat16_rn(vw);
          reinterpret_cast<bf16*>(dst)[128 + col_pos(col & 127)] = __float2bfloat16_rn(vw - rbf(vw));
        }
        reinterpret_cast<bf16*>(dst + 512 + (kind == 0 ? 0 : kind == 2 ? 256 : kind == 1 ? 512 : 768))[col_pos(col & 127)] = __float2bfloat16_rn(v);
      }
    }
  }
  #pragma unroll
  for (int o = 16; o > 0; o >>= 1) dot += __shfl_xor_sync(0xffffffffu, dot, o);
  if (t2 == 32) sts_f32(scr + 4096, dot);
  fence_proxy_async();
  named_bar_sync(5, 256);
  if (t2 == 0 && (kind == 1 || kind == 2)) g_scal[(kind == 2 ? 0 : 2) + (j & 1)] = dot + lds_f32(scr + 4096);
  sleep_until(t0, CLR_T);
  #pragma unroll 1
  for (int i = j * 256 + t2; i < (int)(sizeof(TailMail) / 16); i += 8 * 256) reinterpret_cast<uint4*>(&hm->mail)[i] = make_uint4(0u, 0u, 0u, 0u);
  named_bar_sync(5, 256);
  if (t2 == 0) red_release_add(&g_hcnt[0], 1u);
  sleep_until(t0, SGL_T);
}

constexpr int AT_NBLK = T_SEQ / 128;
constexpr float AT_HEAD = 7.0f;
#define WOL 12
constexpr int WO_LATE = WOL;
#define QSTG 3
constexpr int QP_STAG = QSTG;
constexpr int AT_SPLIT = 28, AT_PIN = 8, PINB = 4;
constexpr int AT_NFULL = 124;
constexpr int AT_PREG = 40, AT_CREG = 232;
constexpr uint32_t AT_SQ = 5 * 32768;
constexpr float AT_C = 0.08838834764831845f * 1.4426950408889634f;
constexpr float AT_RAW_LO = -16.0f, AT_RAW_HI = 24.0f;
constexpr float AT_RAW_SUM = 281474976710656.0f, AT_RAW_MIN = 9.094947017729282e-13f;
constexpr uint32_t AT_SBAR = AT_SQ + 65536 + 256;
constexpr uint32_t AT_SMEM = AT_SQ + 65536 + 3072;

__device__ __forceinline__ uint32_t ring_slot(uint32_t t) { return t - 5u * ((t * 205u) >> 10); }
__device__ __forceinline__ uint32_t qp_pos(uint32_t j, uint32_t it) { return 4u * it + (j & 3u) + ((j & 3u) == 3u ? it : 0u); }
__device__ __forceinline__ uint32_t ring_par(uint32_t t) { return ((t * 205u) >> 10) & 1u; }
__device__ __forceinline__ void softmax_rowmax(const float (&s)[64], float& mx0, float& mx1) {
  float a0 = fmaxf(s[0], s[1]), a1 = fmaxf(s[4], s[5]), a2 = fmaxf(s[8], s[9]), a3 = fmaxf(s[12], s[13]);
  float b0 = fmaxf(s[2], s[3]), b1 = fmaxf(s[6], s[7]), b2 = fmaxf(s[10], s[11]), b3 = fmaxf(s[14], s[15]);
  #pragma unroll
  for (int j = 4; j < 16; j += 4) {
    a0 = fmaxf(a0, fmaxf(s[4 * j + 0], s[4 * j + 1]));  b0 = fmaxf(b0, fmaxf(s[4 * j + 2], s[4 * j + 3]));
    a1 = fmaxf(a1, fmaxf(s[4 * j + 4], s[4 * j + 5]));  b1 = fmaxf(b1, fmaxf(s[4 * j + 6], s[4 * j + 7]));
    a2 = fmaxf(a2, fmaxf(s[4 * j + 8], s[4 * j + 9]));  b2 = fmaxf(b2, fmaxf(s[4 * j + 10], s[4 * j + 11]));
    a3 = fmaxf(a3, fmaxf(s[4 * j + 12], s[4 * j + 13])); b3 = fmaxf(b3, fmaxf(s[4 * j + 14], s[4 * j + 15]));
  }
  mx0 = fmaxf(fmaxf(a0, a1), fmaxf(a2, a3));
  mx1 = fmaxf(fmaxf(b0, b1), fmaxf(b2, b3));
  mx0 = fmaxf(mx0, __shfl_xor_sync(0xffffffffu, mx0, 1));
  mx1 = fmaxf(mx1, __shfl_xor_sync(0xffffffffu, mx1, 1));
  mx0 = fmaxf(mx0, __shfl_xor_sync(0xffffffffu, mx0, 2));
  mx1 = fmaxf(mx1, __shfl_xor_sync(0xffffffffu, mx1, 2));
}
__device__ __forceinline__ void softmax_sub(float (&s)[64], float mc0, float mc1) {
  #pragma unroll
  for (int j = 0; j < 16; j++) { s[4 * j] -= mc0; s[4 * j + 1] -= mc0; s[4 * j + 2] -= mc1; s[4 * j + 3] -= mc1; }
}
template <int LO, int HI>
__device__ __forceinline__ void softmax_exp(float (&s)[64]) {
  #pragma unroll
  for (int i = LO; i < HI; i++) s[i] = ex2_approx(s[i]);
}
__device__ __forceinline__ bool softmax_mode(const float (&s)[64], float& mc0, float& mc1) {
  softmax_rowmax(s, mc0, mc1);
  const bool raw = __all_sync(0xffffffffu, mc0 >= AT_RAW_LO && mc0 <= AT_RAW_HI && mc1 >= AT_RAW_LO && mc1 <= AT_RAW_HI);
  mc0 += AT_HEAD; mc1 += AT_HEAD;
  return raw;
}
__device__ __forceinline__ void rowsum_p(const uint32_t (&p)[32], uint32_t& t0, uint32_t& t1) {
  uint32_t a[16];
  #pragma unroll
  for (int i = 0; i < 8; i++) { a[2 * i] = badd2(p[4 * i], p[4 * i + 2]); a[2 * i + 1] = badd2(p[4 * i + 1], p[4 * i + 3]); }
  #pragma unroll
  for (int i = 0; i < 4; i++) { a[2 * i] = badd2(a[4 * i], a[4 * i + 2]); a[2 * i + 1] = badd2(a[4 * i + 1], a[4 * i + 3]); }
  t0 = badd2(badd2(a[0], a[2]), badd2(a[4], a[6]));
  t1 = badd2(badd2(a[1], a[3]), badd2(a[5], a[7]));
}
__device__ __forceinline__ void add_rowsum(const uint32_t (&p)[32], float& l0, float& l1) {
  uint32_t t0, t1;
  rowsum_p(p, t0, t1);
  l0 += bflo(t0) + bfhi(t0); l1 += bflo(t1) + bfhi(t1);
}
__device__ __forceinline__ void pack_p(uint32_t (&p)[32], const float (&s)[64]) {
  #pragma unroll
  for (int i = 0; i < 32; i++) p[i] = pack_bf16(s[2 * i], s[2 * i + 1]);
}
__device__ __noinline__ void attn_rows_exact(uint32_t sq, int warp, int lane, const bf16* __restrict__ kh, const bf16* __restrict__ vh) {
  #pragma unroll 1
  for (int r = 16 * warp; r < 16 * warp + 16; r++) {
    const uint32_t ad = (lane >> 4) * 16384 + r * 128 + ((((lane & 15) >> 1) ^ (r & 7)) << 4) + (lane & 1) * 8;
    uint2 qv; asm volatile("ld.shared.v2.u32 {%0, %1}, [%2];" : "=r"(qv.x), "=r"(qv.y) : "r"(sq + ad) : "memory");
    const float q0 = bflo(qv.x), q1 = bfhi(qv.x), q2 = bflo(qv.y), q3 = bfhi(qv.y);
    float m = -INFINITY, l = 0.f, o0 = 0.f, o1 = 0.f, o2 = 0.f, o3 = 0.f;
    #pragma unroll 1
    for (int key = 0; key < T_SEQ; key++) {
      const uint2 kv = *reinterpret_cast<const uint2*>(kh + (size_t)key * T_DH + lane * 4);
      const uint2 vv = *reinterpret_cast<const uint2*>(vh + (size_t)key * T_DH + lane * 4);
      float sc = (q0 * bflo(kv.x) + q1 * bfhi(kv.x)) + (q2 * bflo(kv.y) + q3 * bfhi(kv.y));
      #pragma unroll
      for (int o = 16; o > 0; o >>= 1) sc += __shfl_xor_sync(0xffffffffu, sc, o);
      const float mn = fmaxf(m, sc);
      const float al = (m == mn) ? 1.0f : ex2_approx(m - mn), p = rbf(ex2_approx(sc - mn));
      m = mn;
      l = fmaf(l, al, p);
      o0 = fmaf(o0, al, p * bflo(vv.x)); o1 = fmaf(o1, al, p * bfhi(vv.x));
      o2 = fmaf(o2, al, p * bflo(vv.y)); o3 = fmaf(o3, al, p * bfhi(vv.y));
    }
    const float inv = rcp_approx(l);
    asm volatile("st.shared.v2.u32 [%0], {%1, %2};" :: "r"(sq + ad), "r"(pack_bf16(o0 * inv, o1 * inv)), "r"(pack_bf16(o2 * inv, o3 * inv)) : "memory");
  }
}
__device__ __forceinline__ void issue_qk(float (&s)[64], const uint32_t (&q)[32], uint32_t k_lo) {
  wgmma_fence();
  wgmma_m64n128k16_rs<0>(s, q[0], q[1], q[2], q[3], k_lo, 0);
  wgmma_m64n128k16_rs<2>(s, q[4], q[5], q[6], q[7], k_lo, 1);
  wgmma_m64n128k16_rs<4>(s, q[8], q[9], q[10], q[11], k_lo, 1);
  wgmma_m64n128k16_rs<6>(s, q[12], q[13], q[14], q[15], k_lo, 1);
  wgmma_m64n128k16_rs<1024>(s, q[16], q[17], q[18], q[19], k_lo, 1);
  wgmma_m64n128k16_rs<1026>(s, q[20], q[21], q[22], q[23], k_lo, 1);
  wgmma_m64n128k16_rs<1028>(s, q[24], q[25], q[26], q[27], k_lo, 1);
  wgmma_m64n128k16_rs<1030>(s, q[28], q[29], q[30], q[31], k_lo, 1);
  wgmma_commit();
}
__device__ __forceinline__ void issue_pv(float (&o)[64], const uint32_t (&p)[32], uint32_t v_lo, int accumulate) {
  wgmma_fence();
  wgmma_m64n128k16_rs_tb<0>(o, p[0], p[1], p[2], p[3], v_lo, accumulate);
  wgmma_m64n128k16_rs_tb<128>(o, p[4], p[5], p[6], p[7], v_lo, 1);
  wgmma_m64n128k16_rs_tb<256>(o, p[8], p[9], p[10], p[11], v_lo, 1);
  wgmma_m64n128k16_rs_tb<384>(o, p[12], p[13], p[14], p[15], v_lo, 1);
  wgmma_m64n128k16_rs_tb<512>(o, p[16], p[17], p[18], p[19], v_lo, 1);
  wgmma_m64n128k16_rs_tb<640>(o, p[20], p[21], p[22], p[23], v_lo, 1);
  wgmma_m64n128k16_rs_tb<768>(o, p[24], p[25], p[26], p[27], v_lo, 1);
  wgmma_m64n128k16_rs_tb<896>(o, p[28], p[29], p[30], p[31], v_lo, 1);
  wgmma_commit();
}
__device__ __forceinline__ void rescale_o(float (&o)[64], float al0, float al1) {
  #pragma unroll
  for (int j = 0; j < 16; j++) { o[4 * j] *= al0; o[4 * j + 1] *= al0; o[4 * j + 2] *= al1; o[4 * j + 3] *= al1; }
}

__device__ __forceinline__ void stage_o(const float (&o)[64], float i0, float i1, uint32_t dst, int lane) {
  #pragma unroll
  for (int J = 0; J < 16; J += 2)
    stmatrix_x4(dst + (J >> 3) * 16384 + ((((J & 7) + (lane >> 4)) ^ (lane & 7)) << 4),
                pack_bf16(o[4 * J + 0] * i0, o[4 * J + 1] * i0), pack_bf16(o[4 * J + 2] * i1, o[4 * J + 3] * i1),
                pack_bf16(o[4 * J + 4] * i0, o[4 * J + 5] * i0), pack_bf16(o[4 * J + 6] * i1, o[4 * J + 7] * i1));
}
__device__ __forceinline__ bool finish_l(float& l0, float& l1) {
  l0 += __shfl_xor_sync(0xffffffffu, l0, 1); l1 += __shfl_xor_sync(0xffffffffu, l1, 1);
  l0 += __shfl_xor_sync(0xffffffffu, l0, 2); l1 += __shfl_xor_sync(0xffffffffu, l1, 2);
  const bool redo = __any_sync(0xffffffffu, !(l0 <= AT_RAW_SUM && l1 <= AT_RAW_SUM && l0 >= AT_RAW_MIN && l1 >= AT_RAW_MIN));
  l0 = rcp_approx(l0); l1 = rcp_approx(l1);
  return redo;
}
__device__ __forceinline__ void stage_qregs(const uint32_t (&q)[32], uint32_t dst, int lane) {
  #pragma unroll
  for (int J = 0; J < 16; J += 2)
    stmatrix_x4(dst + (J >> 3) * 16384 + ((((J & 7) + (lane >> 4)) ^ (lane & 7)) << 4), q[2 * J], q[2 * J + 1], q[2 * J + 2], q[2 * J + 3]);
}
__device__ __forceinline__ void store_o(const CUtensorMap* tmO, uint32_t src, int head, int row) {
  tma_store_2d(tmO, src, head * T_DH, row);
  tma_store_2d(tmO, src + 16384, head * T_DH + 64, row);
  bulk_commit();
}
struct GemvSel { uint32_t lo0, hi0, lo1, hi1; };
__device__ __forceinline__ GemvSel gemv_sel(int lane) {
  const uint32_t lo = (lane & 8) ? 0x1044u : 0x4410u, hi = (lane & 8) ? 0x3244u : 0x4432u;
  GemvSel s; s.lo0 = (lane & 16) ? 0x4444u : lo; s.hi0 = (lane & 16) ? 0x4444u : hi; s.lo1 = (lane & 16) ? lo : 0x4444u; s.hi1 = (lane & 16) ? hi : 0x4444u;
  return s;
}
#define GEMV_B0(j, h, s) __byte_perm((j) < 2 ? (h).x : (h).y, 0u, ((j) & 1) ? (s).hi0 : (s).lo0)
#define GEMV_B1(j, h, s) __byte_perm((j) < 2 ? (h).x : (h).y, 0u, ((j) & 1) ? (s).hi1 : (s).lo1)
__device__ __forceinline__ float4 gemv_out(const float (&d)[4], int lane) {
  const bool tk = lane & 1;
  const float r0 = __shfl_xor_sync(0xffffffffu, tk ? d[0] : d[1], 1), r1 = __shfl_xor_sync(0xffffffffu, tk ? d[2] : d[3], 1);
  return tk ? make_float4(r0, d[1], r1, d[3]) : make_float4(d[0], r0, d[2], r1);
}
#define OG_NG 8
#define OG_GRP (64 / OG_NG)
constexpr int OG_ST = 5, OG_NKB = T_DQKV / 64, OG_MOE = T_F / 32;
constexpr int OG_POS = 8;
constexpr uint32_t OG_STAGE = 32768;
constexpr uint32_t OG_SWD = AT_SQ;
constexpr uint32_t OG_SCOL = AT_SBAR + 512;
constexpr uint32_t OG_SMISC = AT_SBAR + 2048;
constexpr uint32_t OG_XSLOT = ((OG_POS + OG_NKB) % OG_ST) * OG_STAGE;
constexpr uint32_t OG_OSLOT = ((OG_POS + OG_NKB + 1) % OG_ST) * OG_STAGE;
constexpr uint32_t OG_SH2 = ((OG_POS + OG_NKB + 2) % OG_ST) * OG_STAGE;
constexpr uint32_t OG_SRED = ((OG_POS + OG_NKB + 3) % OG_ST) * OG_STAGE;
constexpr uint32_t OG_SSTAT = OG_SRED + 16384;
constexpr uint32_t OG_SGU = OG_SRED + 8192;
constexpr uint32_t OG_SFIN = OG_SGU + 256;
#define OGM 2
#define OG_MT(b) ((((b) >> OGM) & 15) ^ (((b) & 64) ? 15 : 0))
#define OG_NT(b) (((b) & ((1 << OGM) - 1)) + (((b) >> (4 + OGM)) << OGM))
#define TAIL_SETUP \
  const uint32_t bar_full = sbase + AT_SBAR, bar_empty = bar_full + 40; \
  const uint32_t bar_wd = bar_full + 168, bar_col = bar_full + 176, bar_out = bar_full + 184, bar_end = bar_full + 192; \
  const uint32_t bar_key = bar_full + 200, bar_h2 = bar_full + 208, bar_sel = bar_full + 216; \
  const int mt = OG_MT(bx), nt = OG_NT(bx); \
  const int m0 = mt * 128, n0 = nt * 128; \
  const bool has_moe = (int)bx < OG_MOE; \
  (void)bar_empty; (void)bar_wd; (void)bar_col; (void)bar_out; (void)bar_end; (void)bar_key; (void)bar_h2; (void)bar_sel; (void)m0; (void)n0; (void)has_moe;

__device__ __forceinline__ void tail_producer(Scratch* hm, uint32_t bx, uint32_t sbase, uint32_t ph, uint32_t obpar, uint64_t pol, const CUtensorMap* tmA, const CUtensorMap* tmB,
                                              const CUtensorMap* tmX, const bf16* __restrict__ w_down) {
  TAIL_SETUP
  const uint32_t b_ob = bar_full + 96, b_acq = bar_full + 264;
  uint32_t stage = OG_POS % OG_ST;
  const uint8_t* wdp = (const uint8_t*)w_down + (size_t)bx * 65536;
  if (has_moe) mbar_expect_tx(bar_wd, 65536);
  mbar_expect_tx(bar_col, 1536 + 16);
  #pragma unroll 1
  for (int kb = 0; kb <= OG_NKB; kb++) {
    const uint32_t fb = bar_full + 8 * stage, sa = sbase + stage * OG_STAGE, sb = sa + 16384;
    mbar_wait(bar_empty + 8 * stage, ph);
    mbar_expect_tx(fb, OG_STAGE);
    if (kb < OG_NKB) {
      tma_load_2d_hint(sb, tmB, n0, kb * 64, fb, pol);
      tma_load_2d_hint(sb + 8192, tmB, n0 + 64, kb * 64, fb, pol);
      if ((kb & 31) == 0) { mbar_wait(b_acq, kb >> 5); fence_proxy_async_global(); }
      tma_load_2d_hint(sa, tmA, kb * 64, m0, fb, pol);
    } else {
      tma_load_2d_hint(sa, tmX, n0, m0, fb, pol);
      tma_load_2d_hint(sb, tmX, n0 + 64, m0, fb, pol);
    }
    if (kb == 32) {
      bulk_load_hint(sbase + OG_SCOL, g_col + nt * 1536, 1536, bar_col, pol);
      bulk_load_hint(sbase + OG_SMISC, g_scal, 16, bar_col, pol);
    }
    if (kb == 6) mbar_wait(b_ob, obpar);
    if (has_moe && (kb & 7) == 6) {
      bulk_load_hint(sbase + OG_SWD + (kb >> 3) * 8224, wdp, 8192, bar_wd, pol);
      wdp += 8192;
    }
    if (++stage == OG_ST) { stage = 0; ph ^= 1; }
  }
}

__device__ __forceinline__ uint32_t out2(uint32_t x1, uint32_t mb2, uint32_t ih, uint32_t il, uint32_t c1, uint32_t sb, uint32_t gb) {
  const uint32_t d = bsub2(x1, mb2);
  return bfma2(gb, bfma2(bfma2(d, ih, bmul2(d, il)), c1, sb), x1);
}
__device__ __forceinline__ void tail_exchange(Scratch* hm, uint32_t bx, uint32_t sbase, int wid, uint32_t tx, const CUtensorMap* tmOut, bf16* __restrict__ out) {
    TAIL_SETUP
    mbar_wait(bar_end, 0);
    const int lane = tx & 31;
    TL_MARK2(22, lane == 0);
    if (tx == 96) PF(5);
    if (wid == 0) {
      uint32_t k1 = 0u, k2 = 0u;
      #pragma unroll 1
      for (unsigned int spin = 0; spin < (1u << 22); spin++) {
        if (k1 == 0u) asm volatile("ld.relaxed.gpu.global.u32 %0, [%1];" : "=r"(k1) : "l"(g_key + lane) : "memory");
        if (__all_sync(0xffffffffu, k1 != 0u)) break;
      }
      TS(6, lane == 0);
      warp_top2(k1, k2);
      if (lane == 0) {
        const uint32_t r1 = 0xffffu - (k1 & 0xffffu), r2 = 0xffffu - (k2 & 0xffffu);
        sts_u32x4(sbase + OG_SMISC + 64, k1, k2, (r1 >> 7) * 2, (r2 >> 7) * 2 + ((r1 >> 7) == (r2 >> 7)));
        mbar_arrive(bar_sel);
      }
    } else if (wid < 3) {
      const uint32_t ch = lane & 15, ca = sbase + OG_SCOL + 768 + (ch >> 2) * 64 + (ch & 3) * 4;
      const uint4 c1 = make_uint4(lds_u32(ca), lds_u32(ca + 16), lds_u32(ca + 32), lds_u32(ca + 48)), sh = make_uint4(lds_u32(ca + 256), lds_u32(ca + 272), lds_u32(ca + 288), lds_u32(ca + 304));
      float* dst = reinterpret_cast<float*>(g_cand + (mt * 2 + (lane >> 4)) * 256 + nt * 16 + ch);
      mbar_wait(bar_key, 0);
      const uint4 kk = lds_u32x4(sbase + OG_SSTAT + 1024 + lane * 16);
      uint32_t k1 = max(kk.x, kk.y), k2 = min(kk.x, kk.y);
      k2 = max(max(k2, min(kk.z, kk.w)), min(k1, max(kk.z, kk.w))); k1 = max(k1, max(kk.z, kk.w));
      warp_top2(k1, k2);
      if (wid == 1) {
        if (lane == 0 && nt == (mt & 7)) st_relaxed2(g_key + mt * 2, k1, k2);
        TS(4, lane == 0);
      } else {
        const uint32_t r = (~((lane & 16) ? k2 : k1)) & 127u;
        const uint2 st = lds_u32x2(sbase + OG_SSTAT + r * 8);
        const uint4 xc = lds_u32x4(sbase + OG_XSLOT + (ch >> 3) * 16384 + r * 128 + (((ch ^ r) & 7) << 4));
        const float inr = __uint_as_float(st.y);
        const float h0 = __uint_as_float(ln_mod2(xc.x, st.x, inr, c1.x, sh.x)), h1 = __uint_as_float(ln_mod2(xc.y, st.x, inr, c1.y, sh.y));
        const float h2 = __uint_as_float(ln_mod2(xc.z, st.x, inr, c1.z, sh.z)), h3 = __uint_as_float(ln_mod2(xc.w, st.x, inr, c1.w, sh.w));
        st_tagged4(dst + 512, h0, h1, h2, h3);
        st_tagged4(dst, __uint_as_float(xc.x), __uint_as_float(xc.y), __uint_as_float(xc.z), __uint_as_float(xc.w));
      }
    }
    mbar_wait(bar_sel, 0);
    mbar_wait(bar_out, 0);
    {
      const int sel0 = 0xffff - (lds_u32(sbase + OG_SMISC + 64) & 0xffffu), sel1 = 0xffff - (lds_u32(sbase + OG_SMISC + 68) & 0xffffu);
      if ((sel0 >> 7) == mt || (sel1 >> 7) == mt) {
        #pragma unroll 2
        for (int i = 0; i < 16; i++) {
          const int r = i * 8 + (tx >> 4), ch = tx & 15;
          if (m0 + r != sel0 && m0 + r != sel1)
            *reinterpret_cast<uint4*>(out + (size_t)(m0 + r) * T_D + n0 + ch * 8) =
                lds_u32x4(sbase + OG_OSLOT + (ch >> 3) * 16384 + r * 128 + (((ch & 7) ^ (r & 7)) << 4));
        }
      } else if (tx == 96) {
        tma_store_2d(tmOut, sbase + OG_OSLOT, n0, m0);
        tma_store_2d(tmOut, sbase + OG_OSLOT + 16384, n0 + 64, m0);
        bulk_commit();
      }
      __syncwarp();
    }
    {
      const int tk = bx >> 6, c0 = (bx & 63) * 16;
      const uint32_t gb2 = *reinterpret_cast<const uint32_t*>(g_col + (c0 >> 7) * 1536 + 512 + 768 + col_pos((c0 & 127) + (tx & 14)) * 2);
      const float* src = g_ypart + (size_t)((tx >> 2) * 2 + tk) * T_D + c0 + (tx & 3) * 4;
      const bool four = tx < (OG_MOE - 96) * 4;
      mbar_wait(bar_h2, 0);
      float fx = 0.f, fh = 0.f, rs = 0.f;
      bf16* op = out;
      if (wid == 1) {
        const uint32_t key = lds_u32(sbase + OG_SMISC + 64 + tk * 4);
        const uint32_t* xp = reinterpret_cast<const uint32_t*>(g_cand + lds_u32(sbase + OG_SMISC + 72 + tk * 4) * 256) + ((c0 + (tx & 14)) >> 1);
        uint32_t x2 = 0u;
        #pragma unroll 1
        for (unsigned int spin = 0; spin < (1u << 20); spin++) { asm volatile("ld.relaxed.gpu.global.u32 %0, [%1];" : "=r"(x2) : "l"(xp) : "memory"); if (__all_sync(0xffffffffu, x2 != 0u)) break; }
        const uint32_t h2p = lds_u32(sbase + OG_SH2 + tk * 2048 + (c0 + (tx & 14)) * 2);
        fx = (lane & 1) ? bfhi(x2) : bflo(x2); fh = (lane & 1) ? bfhi(h2p) : bflo(h2p);
        rs = rbf(sigmoid_f(bfhi((key & 0x80000000u) ? key ^ 0x80000000u : ~key)));
        op += (size_t)(0xffffu - (key & 0xffffu)) * T_D + c0 + (lane & 15);
      }
      if (bx == 0 && tx < 68) g_hcnt[32 * (tx >> 2) + (tx & 3)] = 0u;
      if (tx < 64) hm->modu[bx * 64 + tx] = 0.f;
      else if (tx < 96) hm->stat[bx * 32 + tx - 64] = make_float2(0.f, 0.f);
      else if (tx < 112) hm->mod[bx * 16 + tx - 96] = 0.f;
      else if (tx < 114 && bx < 66) hm->gkey[bx * 2 + tx - 112] = 0u;
      if (tx == 0) hint_wait(CNT_Y, (uint32_t)OG_MOE);
      named_bar_sync(10, 128);
      TS(11, lane == 0);
      float4 p0, p1, p2, p3;
      #pragma unroll 1
      for (unsigned int spin = 0; spin < (1u << 20); spin++) {
        p0 = ld_tagged4(src); p1 = ld_tagged4(src + 64 * T_D); p2 = ld_tagged4(src + 128 * T_D); p3 = ld_tagged4(four ? src + 192 * T_D : src);
        if (__all_sync(0xffffffffu, tagged4(p0) & tagged4(p1) & tagged4(p2) & tagged4(p3))) break;
      }
      if (four) { p2.x += p3.x; p2.y += p3.y; p2.z += p3.z; p2.w += p3.w; }
      p0.x = (p0.x + p1.x) + p2.x; p0.y = (p0.y + p1.y) + p2.y; p0.z = (p0.z + p1.z) + p2.z; p0.w = (p0.w + p1.w) + p2.w;
      #pragma unroll
      for (int o = 4; o <= 16; o <<= 1) {
        p0.x += __shfl_xor_sync(0xffffffffu, p0.x, o); p0.y += __shfl_xor_sync(0xffffffffu, p0.y, o);
        p0.z += __shfl_xor_sync(0xffffffffu, p0.z, o); p0.w += __shfl_xor_sync(0xffffffffu, p0.w, o);
      }
      if (lane < 4) sts_f32x4(sbase + OG_SFIN + (tx >> 5) * 64 + lane * 16, p0.x, p0.y, p0.z, p0.w);
      named_bar_sync(10, 128);
      TS(12, lane == 0);
      if (wid == 1 && lane < 16) {
        const uint32_t ya = sbase + OG_SFIN + lane * 4;
        const float y = rbf(rbf((lds_f32(ya) + lds_f32(ya + 64)) + (lds_f32(ya + 128) + lds_f32(ya + 192))) * rs);
        *op = __float2bfloat16_rn(fx + rbf(((lane & 1) ? bfhi(gb2) : bflo(gb2)) * rbf(fh + y)));
      }
      if (tx == 96) bulk_wait_read<0>();
    }
    TL_END(4, tx == 0);
    PS(6, tx == 32);
    TS(13, tx == 32);
}

__device__ __forceinline__ void tail_consumer(Scratch* hm, uint32_t bx, uint32_t sbase, int tid, int w8, const bf16* __restrict__ w_gate, const bf16* __restrict__ w_up) {
    TAIL_SETUP
    const int warp = w8 & 3, lane = tid & 31, cwg = w8 >> 2, t2 = cwg * 128 + tid;
    const uint32_t dbase = (sbase & 0x3FFFFu) >> 4;
    const uint32_t a_base = dbase + ((cwg * 8192) >> 4) + (1u << 16);
    const uint32_t b_base = dbase + (16384 >> 4) + (512u << 16);
    TL_MARK2(25, threadIdx.x == 128);
    const uint64_t pol = policy_evict_first();
    const bf16* pw = ((lane & 16) ? w_up : w_gate) + (size_t)(w8 * 128 + (lane & 3) * 4) * T_F + (has_moe ? bx : 0) * 32 + ((lane >> 2) & 3) * 8;
    uint4 wv[32];
    float acc[64];
    {
      uint32_t stage = OG_POS % OG_ST, phase = (OG_POS / OG_ST) & 1, prev = 0;
      #pragma unroll
      for (int g = 0; g < OG_NG; g++) {
        #pragma unroll
        for (int j = 0; j < 4; j++) wv[4 * g + j] = ldg_stream_v4(pw + (size_t)(16 * g + j) * T_F, pol);
        #pragma unroll 1
        for (int kb = g * OG_GRP; kb < (g == OG_NG - 1 ? OG_NKB : (g + 1) * OG_GRP); kb++) {
          mbar_wait(bar_full + 8 * stage, phase);
          const uint32_t a_lo = a_base + stage * (OG_STAGE >> 4), b_lo = b_base + stage * (OG_STAGE >> 4);
          wgmma_fence();
          wgmma_m64n128k16_ss_tb<0, 0>(acc, a_lo, b_lo, kb != 0);
          wgmma_m64n128k16_ss_tb<2, 128>(acc, a_lo, b_lo, 1);
          wgmma_m64n128k16_ss_tb<4, 256>(acc, a_lo, b_lo, 1);
          wgmma_m64n128k16_ss_tb<6, 384>(acc, a_lo, b_lo, 1);
          wgmma_commit();
          wgmma_wait<1>();
          if (kb > 0 && tid == 0) mbar_arrive(bar_empty + 8 * prev);
          prev = stage;
          if (++stage == OG_ST) { stage = 0; phase ^= 1; }
        }
      }
    }
    const uint32_t frag = (64 * cwg + 16 * warp + (lane & 15)) * 128 + (((lane >> 4) ^ (lane & 7)) << 4);
    const uint32_t tcol = sbase + OG_SCOL + (lane & 3) * 16, g = lane >> 2;
    float* sdst = reinterpret_cast<float*>(g_part1 + ((mt * 8 + w8) * 8 + nt) * 16 + g + (lane & 1) * 8);
    uint32_t xr[32];
    uint4 ga[4], cw[4];
    auto ld_quarter = [&](int q, uint32_t dep) {
      #pragma unroll
      for (int i = 2 * q; i < 2 * q + 2; i++) ldmatrix_x4(sbase + OG_XSLOT + (i >> 2) * 16384 + (frag ^ ((i & 3) * 32)) + dep, xr[4 * i], xr[4 * i + 1], xr[4 * i + 2], xr[4 * i + 3]);
      ga[q] = lds_u32x4(tcol + 512 + q * 64 + dep);
      cw[q] = lds_u32x4((g ? tcol + (lane & 8) * 32 + q * 64 : sbase + OG_SMISC + 32) + dep);
    };
    mbar_wait(bar_col, 0);
    mbar_wait(bar_full + 8 * ((OG_POS + OG_NKB) % OG_ST), ((OG_POS + OG_NKB) / OG_ST) & 1);
    ld_quarter(0, 0);
    wgmma_wait<0>();
    fence_regs(acc);
    if (tid == 0) mbar_arrive(bar_end);
    TL_MARK2(9, lane == 0);
    TS(0, lane == 0);
    PS(5, threadIdx.x == 256);
    {
      float dl[4] = {0.f, 0.f, 0.f, 0.f}, da[4] = {0.f, 0.f, 0.f, 0.f}, db[4] = {0.f, 0.f, 0.f, 0.f};
      #pragma unroll
      for (int q = 0; q < 4; q++) {
        uint32_t pk[8];
        #pragma unroll
        for (int i = 0; i < 8; i++) pk[i] = pack_bf16(acc[16 * q + 2 * i], acc[16 * q + 2 * i + 1]);
        if (q < 3) ld_quarter(q + 1, 0u);
        #pragma unroll
        for (int i = 2 * q; i < 2 * q + 2; i++) {
          #pragma unroll
          for (int k = 0; k < 4; k++) xr[4 * i + k] = badd2(xr[4 * i + k], bmul2((i & 1) ? (k < 2 ? ga[q].z : ga[q].w) : (k < 2 ? ga[q].x : ga[q].y), pk[4 * (i & 1) + k]));
          mma_bf16(dl, xr[4 * i], xr[4 * i + 1], xr[4 * i + 2], xr[4 * i + 3], (i & 1) ? cw[q].z : cw[q].x, (i & 1) ? cw[q].w : cw[q].y);
          mma_bf16(da, xr[4 * i], xr[4 * i + 1], xr[4 * i + 2], xr[4 * i + 3], xr[4 * i], xr[4 * i + 2]);
          mma_bf16(db, xr[4 * i], xr[4 * i + 1], xr[4 * i + 2], xr[4 * i + 3], xr[4 * i + 1], xr[4 * i + 3]);
        }
      }
      {
        const int dsrc = (lane & ~3) + (g >> 1);
        const float qa = __shfl_sync(0xffffffffu, (g & 1) ? da[1] : da[0], dsrc), qb = __shfl_sync(0xffffffffu, (g & 1) ? db[3] : db[2], dsrc);
        const float e0 = __shfl_xor_sync(0xffffffffu, (lane & 1) ? dl[0] : dl[2], 1), e1 = __shfl_xor_sync(0xffffffffu, dl[3], 1);
        const bool hi = lane & 1;
        if ((lane & 3) < 2) st_tagged4(sdst, hi ? e0 : dl[0], hi ? qb : qa, hi ? e1 + dl[2] : dl[1] + e0, 1.0f);
      }
    }
    TL_MARK2(10, lane == 0);
    TS(1, lane == 0);
    uint4 tc[4], ts[4], tg[4];
    #pragma unroll
    for (int i = 0; i < 8; i++) stmatrix_x4(sbase + OG_XSLOT + (i >> 2) * 16384 + (frag ^ ((i & 3) * 32)), xr[4 * i], xr[4 * i + 1], xr[4 * i + 2], xr[4 * i + 3]);
    #pragma unroll
    for (int i = 0; i < 8; i++) ldmatrix_x4(sbase + OG_XSLOT + (i >> 2) * 16384 + (frag ^ ((i & 3) * 32)), xr[4 * i], xr[4 * i + 1], xr[4 * i + 2], xr[4 * i + 3]);
    #pragma unroll
    for (int i = 0; i < 2; i++) { tc[i] = lds_u32x4(tcol + 768 + i * 64); ts[i] = lds_u32x4(tcol + 1024 + i * 64); tg[i] = lds_u32x4(tcol + 1280 + i * 64); }
    {
      const float* src = reinterpret_cast<const float*>(g_part1 + ((mt * 8 + w8) * 8 + (lane & 1) * 4) * 16 + (lane >> 1));
      float4 v, v1, v2, v3;
      #pragma unroll 1
      for (unsigned int spin = 0; spin < (1u << 22); spin++) {
        v = ld_tagged4(src); v1 = ld_tagged4(src + 64); v2 = ld_tagged4(src + 128); v3 = ld_tagged4(src + 192);
        if (tagged4(v) & tagged4(v1) & tagged4(v2) & tagged4(v3)) break;
        __nanosleep(100);
      }
      __syncwarp();
      TL_MARK2(26, lane == 0);
    TS(2, lane == 0);
      v.x = (v.x + v1.x) + (v2.x + v3.x); v.y = (v.y + v1.y) + (v2.y + v3.y); v.z = (v.z + v1.z) + (v2.z + v3.z);
      v.x += __shfl_xor_sync(0xffffffffu, v.x, 1); v.y += __shfl_xor_sync(0xffffffffu, v.y, 1); v.z += __shfl_xor_sync(0xffffffffu, v.z, 1);
      const float mean = v.x * (1.0f / T_D);
      const float var = fmaxf(fmaf(-mean, mean, v.y * (1.0f / T_D)), 0.f);
      const uint32_t mb2 = pack_bf16(mean, mean);
      const float inv = rcp_approx(rbf(sqrt_approx(rbf(rbf(var) + 1e-05f))));
      {
        const uint4 sc = lds_u32x4(sbase + OG_SMISC);
        const uint32_t key = rank_key(rbf(fmaf(fmaf(-bflo(mb2), __uint_as_float(sc.x) + __uint_as_float(sc.y), v.z), inv, __uint_as_float(sc.z) + __uint_as_float(sc.w))), m0 + 16 * w8 + (lane >> 1));
        mbar_wait(bar_end, 0);
        if (lane & 1) sts_u32(sbase + OG_SSTAT + 1024 + (16 * w8 + (lane >> 1)) * 4, key);
        else sts_u32x2(sbase + OG_SSTAT + (16 * w8 + (lane >> 1)) * 8, mb2, __float_as_uint(inv));
        __syncwarp();
        TS(3, lane == 0);
        if (lane == 0) mbar_arrive(bar_key);
      }
      const uint32_t ih = pack_bf16(inv, inv), il = pack_bf16(inv - bflo(ih), inv - bflo(ih));
      const uint32_t mba = __shfl_sync(0xffffffffu, mb2, 2 * (lane >> 2)), mbb = __shfl_sync(0xffffffffu, mb2, 2 * (lane >> 2) + 16);
      const uint32_t iha = __shfl_sync(0xffffffffu, ih, 2 * (lane >> 2)), ihb = __shfl_sync(0xffffffffu, ih, 2 * (lane >> 2) + 16);
      const uint32_t ila = __shfl_sync(0xffffffffu, il, 2 * (lane >> 2)), ilb = __shfl_sync(0xffffffffu, il, 2 * (lane >> 2) + 16);
      #pragma unroll
      for (int i = 2; i < 4; i++) { tc[i] = lds_u32x4(tcol + 768 + i * 64); ts[i] = lds_u32x4(tcol + 1024 + i * 64); tg[i] = lds_u32x4(tcol + 1280 + i * 64); }
      #pragma unroll
      for (int i = 0; i < 8; i++) {
        const uint4 &c = tc[i >> 1], &s = ts[i >> 1], &b = tg[i >> 1];
        const bool u = i & 1;
        stmatrix_x4(sbase + OG_OSLOT + (i >> 2) * 16384 + (frag ^ ((i & 3) * 32)),
                    out2(xr[4 * i], mba, iha, ila, u ? c.z : c.x, u ? s.z : s.x, u ? b.z : b.x), out2(xr[4 * i + 1], mbb, ihb, ilb, u ? c.z : c.x, u ? s.z : s.x, u ? b.z : b.x),
                    out2(xr[4 * i + 2], mba, iha, ila, u ? c.w : c.y, u ? s.w : s.y, u ? b.w : b.y), out2(xr[4 * i + 3], mbb, ihb, ilb, u ? c.w : c.y, u ? s.w : s.y, u ? b.w : b.y));
      }
      fence_proxy_async();
      __syncwarp();
      if (lane == 0) mbar_arrive(bar_out);
      TL_MARK2(24, lane == 0);
    TS(5, lane == 0);
    }
    uint4 wd[16];
    {
      mbar_wait(bar_sel, 0);
      TL_MARK2(12, lane == 0);
    TS(7, lane == 0);
      const float* src = reinterpret_cast<const float*>(g_cand + lds_u32(sbase + OG_SMISC + 72 + cwg * 4) * 256 + 128 + tid);
      float4 hf = ld_tagged4(src);
      if (has_moe) mbar_wait(bar_wd, 0);
      #pragma unroll
      for (int i = 0; i < 16; i++) wd[i] = lds_u32x4(sbase + OG_SWD + (((i >> 2) & 1) * 4 + (lane & 3)) * 8224 + (i & 3) * 2048 + w8 * 256 + (i >> 3) * 128 + (lane >> 2) * 16);
      #pragma unroll 1
      for (unsigned int spin = 0; spin < (1u << 20) && !tagged4(hf); spin++) hf = ld_tagged4(src);
      const uint4 hv = make_uint4(__float_as_uint(hf.x), __float_as_uint(hf.y), __float_as_uint(hf.z), __float_as_uint(hf.w));
      sts_u32x4(sbase + OG_SH2 + t2 * 16, hv.x, hv.y, hv.z, hv.w);
    }
    named_bar_sync(9, 256);
    if (t2 == 0) mbar_arrive(bar_h2);
    TL_MARK2(13, lane == 0);
    TS(8, lane == 0);
    if (has_moe) {
      const GemvSel sel = gemv_sel(lane);
      {
        float d[4][4];
        #pragma unroll
        for (int c = 0; c < 4; c++) { d[c][0] = 0.f; d[c][1] = 0.f; d[c][2] = 0.f; d[c][3] = 0.f; }
        #pragma unroll
        for (int st = 0; st < 8; st++) {
          const uint2 hb = lds_u32x2(sbase + OG_SH2 + ((lane >> 2) & 1) * 2048 + (w8 * 128 + st * 16 + (lane & 3) * 4) * 2);
          #pragma unroll
          for (int j = 0; j < 4; j++) mma_bf16(d[j], wv[4 * st + j].x, wv[4 * st + j].y, wv[4 * st + j].z, wv[4 * st + j].w, GEMV_B0(j, hb, sel), GEMV_B1(j, hb, sel));
        }
        #pragma unroll
        for (int e = 0; e < 4; e++) d[0][e] = (d[0][e] + d[1][e]) + (d[2][e] + d[3][e]);
        const float4 r = gemv_out(d[0], lane);
        sts_f32x4(sbase + OG_SRED + w8 * 512 + (((lane >> 4) * 2 + (lane & 1)) * 32 + ((lane >> 2) & 3) * 8 + (lane & 2) * 2) * 4, r.x, r.y, r.z, r.w);
      }
      named_bar_sync(9, 256);
      if (t2 < 64) {
        float gp[8], up[8];
        #pragma unroll
        for (int w = 0; w < 8; w++) { gp[w] = lds_f32(sbase + OG_SRED + w * 512 + t2 * 4); up[w] = lds_f32(sbase + OG_SRED + w * 512 + 256 + t2 * 4); }
        const float gs = ((gp[0] + gp[1]) + (gp[2] + gp[3])) + ((gp[4] + gp[5]) + (gp[6] + gp[7]));
        const float us = ((up[0] + up[1]) + (up[2] + up[3])) + ((up[4] + up[5]) + (up[6] + up[7]));
        asm volatile("st.shared.u16 [%0], %1;" :: "r"(sbase + OG_SGU + t2 * 2), "h"((uint16_t)pack_bf16(silu_bf(rbf(gs)) * rbf(us), 0.f)) : "memory");
      }
      named_bar_sync(9, 256);
      TS(9, lane == 0);
      float d[4][4];
      #pragma unroll
      for (int c = 0; c < 4; c++) { d[c][0] = 0.f; d[c][1] = 0.f; d[c][2] = 0.f; d[c][3] = 0.f; }
      #pragma unroll
      for (int st = 0; st < 2; st++) {
        const uint2 g = lds_u32x2(sbase + OG_SGU + ((lane >> 2) & 1) * 64 + st * 32 + (lane & 3) * 8);
        #pragma unroll
        for (int j = 0; j < 4; j++) {
          const uint32_t b0 = GEMV_B0(j, g, sel), b1 = GEMV_B1(j, g, sel);
          mma_bf16(d[j & 1], wd[4 * st + j].x, wd[4 * st + j].y, wd[4 * st + j].z, wd[4 * st + j].w, b0, b1);
          mma_bf16(d[2 + (j & 1)], wd[8 + 4 * st + j].x, wd[8 + 4 * st + j].y, wd[8 + 4 * st + j].z, wd[8 + 4 * st + j].w, b0, b1);
        }
      }
      #pragma unroll
      for (int e = 0; e < 4; e++) { d[0][e] += d[1][e]; d[2][e] += d[3][e]; }
      const float4 y0 = gemv_out(d[0], lane), y1 = gemv_out(d[2], lane);
      float* yp = g_ypart + (size_t)(bx * 2 + (lane & 1)) * T_D + w8 * 128 + (lane >> 2) * 8 + (lane & 2) * 2;
      st_tagged4(yp, y0.x, y0.y, y0.z, y0.w);
      st_tagged4(yp + 64, y1.x, y1.y, y1.z, y1.w);
      named_bar_sync(9, 256);
      if (t2 == 0) hint_arrive(CNT_Y);
    }
    TS(10, lane == 0);
    TL_CLK(4, 1, threadIdx.x == 128);
}

__device__ __forceinline__ void store_warp(Scratch* hm, uint32_t sbase, const CUtensorMap* tmO, int item0, int n_items) {
  if (elect_one()) {
    const uint32_t bars = sbase + AT_SBAR, b_q0 = bars + 80, b_ob = bars + 96, b_ordy = bars + 104, b_acq = bars + 264;
    mbar_wait(bars + 232, 0);
    const uint32_t bx = lds_u32(bars + 240);
    const unsigned int* cnt = &g_hcnt[32 * (1 + OG_MT(bx)) + 2];
    #pragma unroll 1
    for (int q = 0; q < 4 * n_items; q++) {
      const int item = item0 + (q >> 2) * 128, h = (q >> 1) & 1, w = q & 1;
      const bool last = (q >> 2) == n_items - 1;
      mbar_wait(b_ordy + 8 * (q & 3), q >> 2);
      if (q == 4 && item < 192) spin_until(&g_hcnt[32 * (1 + (item & 15)) + 1], (item & 15) < 12 ? 8u : 7u);
      store_o(tmO, (h ? (last ? sbase + AT_SQ + 32768 : sbase + 2 * 32768) : sbase + AT_SQ) + w * 8192, (item >> 4) * 2 + h, (item & 15) * 128 + w * 64);
      if (w) {
        PF(1 + (q >> 1));
        bulk_wait_read<0>();
        mbar_arrive(h ? b_ob : b_q0);
        bulk_wait<0>();
        fence_proxy_async_global();
        red_release_add(&g_hcnt[32 * (1 + (item & 15)) + 2 + (item >> 7)], 1u);
        if (bx < 128 && q == (n_items == 2 ? 5 : 3)) { spin_until(cnt, 16u); mbar_arrive(b_acq); }
      }
    }
    if (bx < 128) { spin_until(&g_hcnt[0], 8u); spin_until(cnt + 1, 16u); mbar_arrive(b_acq); }
  }
}

#define TUNE_PARAM
__device__ __forceinline__ int h_first(int item, int c) { const int j = (item >> 4) + 3 * c; return j >= 7 ? j - 7 : j; }
__global__ void __launch_bounds__(384, 1)
fused_kernel(const bf16* __restrict__ x, const bf16* __restrict__ cvec, const bf16* __restrict__ w_mod, Scratch* hm, uint32_t zero, TUNE_PARAM
            const uint8_t* __restrict__ pf_wo, const bf16* __restrict__ kc, const bf16* __restrict__ vc, const bf16* __restrict__ w_r,
            const bf16* __restrict__ w_gate, const bf16* __restrict__ w_up, const bf16* __restrict__ w_down, bf16* __restrict__ out,
            const __grid_constant__ CUtensorMap tmM, const __grid_constant__ CUtensorMap tmW, const __grid_constant__ CUtensorMap tmK,
            const __grid_constant__ CUtensorMap tmV, const __grid_constant__ CUtensorMap tmO, const __grid_constant__ CUtensorMap tmOl, const __grid_constant__ CUtensorMap tmWo,
            const __grid_constant__ CUtensorMap tmX, const __grid_constant__ CUtensorMap tmOut)
{
  extern __shared__ __align__(1024) uint8_t smem_raw[];
  const uint32_t sbase = smem_u32(smem_raw);
  const uint32_t bars = sbase + AT_SBAR;
  const uint32_t b_full = bars, b_empty = bars + 40;
  const uint32_t b_q0 = bars + 80, b_q1 = bars + 88;
  const uint32_t b_ob = bars + 96;
  const uint32_t b_ordy = bars + 104;
  const uint32_t b_pin = bars + 136;
  const uint32_t b_a0 = bars + 144;
  const uint32_t b_x = bars + 160;
  const uint32_t b_w = bars + 152, b_go = bars + 224;
  const uint32_t b_bx = bars + 232, s_bx = bars + 240;
  const uint32_t b_hs = bars + 464;
  const uint32_t b_tab = bars + 272;
  const int wid = __shfl_sync(0xffffffffu, threadIdx.x >> 5, 0), wg = wid >> 2;
  const bool single = blockIdx.x >= AT_NFULL;
  const int item0 = __shfl_sync(0xffffffffu, blockIdx.x < 128 ? (int)blockIdx.x : (int)blockIdx.x + 124, 0), n_items = __shfl_sync(0xffffffffu, single ? 1 : 2, 0);
  const uint32_t t0 = clock_lo();
  TL_START(3);
  HS(0);
  if (threadIdx.x == 0) {
    if (sbase & 1023u) __trap();
    for (int i = 0; i < 5; i++) { mbar_init(b_full + 8 * i, 1); mbar_init(b_empty + 8 * i, 2); mbar_init(b_hs + 8 * i, i < 2 && !single ? 4 : 1); }
    sts_u32(bars + 504, 5u);
    mbar_init(b_q0, 1); mbar_init(b_q1, 8); mbar_init(b_ob, 1);
    for (int i = 0; i < 4; i++) mbar_init(b_ordy + 8 * i, 4);
    mbar_init(b_pin, 1); mbar_init(b_a0, 8); mbar_init(b_x, 1); mbar_init(b_w, 1); mbar_init(b_go, 1); mbar_init(b_bx, 1);
    for (int i = 0; i < 8; i++) mbar_init(b_tab + 8 * i, i < 2 ? 1 : 2);
    mbar_init(bars + 168, 1); mbar_init(bars + 176, 1); mbar_init(bars + 184, 8); mbar_init(bars + 192, 2);
    mbar_init(bars + 200, 8); mbar_init(bars + 208, 1); mbar_init(bars + 216, 1); mbar_init(bars + 264, 1);
    sts_u32x4(sbase + OG_SMISC + 32, 0x3F803F80u, 0x3F803F80u, 0x3F803F80u, 0x3F803F80u);
    fence_mbar_init();
    if (blockIdx.x < 128) {
      HS(1);
      wait_clock(t0, XDLY);
      mbar_expect_tx(b_x, 32768);
      bulk_load_hint(sbase + 3 * 32768, x + (size_t)blockIdx.x * 16 * T_D, 32768, b_x, pol_normal());
    }
    mbar_arrive(b_tab); mbar_arrive(b_tab + 8);
  }

  if (wg == 0) {
    reg_dealloc<AT_PREG>();
    if (wid == 0) { __syncwarp(); named_bar_arrive(6, 128); named_bar_arrive(11, 160); named_bar_arrive(12, 160); }
    if (wid >= 2) {
      named_bar_sync(6, 128);
      wait_clock(t0, GDLY2);
      gather_table(hm, sbase + 4 * 32768, b_tab, wid & 1, threadIdx.x & 31);
      if (threadIdx.x == 64) PF(0);
      if (threadIdx.x == 96 && !single) { sleep_until(t0, 40000); spin_until(&g_hcnt[32 * (1 + (item0 & 15))], 7u); mbar_arrive(b_w); }
    } else if (wid == 1) {
      named_bar_sync(6, 128);
      if (item0 < 112) {
        const int lane = threadIdx.x & 31;
        #pragma unroll 1
        for (int j0 = h_first(item0, 0), j1 = h_first(item0, 1); j0 < 16 || j1 < 16;) {
          const int c = j1 < j0, j = c ? j1 : j0;
          bf16* hg = hm->o + (size_t)((item0 & 15) * 128 + c * 64 + (lane >> 3)) * O_LD + O_H + (lane & 7) * 8 + j * 64;
          uint32_t src = sbase + AT_SQ - 16384 + c * 8192 + (lane >> 3) * 128 + (((lane ^ (lane >> 3)) & 7) << 4);
          mbar_wait(b_hs + 8 * c, j >= 7 && j < 14);
          #pragma unroll 1
          for (int i = 0; i < 4; i++, hg += 16 * O_LD, src += 2048) {
            uint4 v[4];
            #pragma unroll
            for (int k = 0; k < 4; k++) v[k] = lds_u32x4((src ^ ((k & 1) * 64)) + k * 512);
            #pragma unroll
            for (int k = 0; k < 4; k++) *reinterpret_cast<uint4*>(hg + k * 4 * O_LD) = v[k];
          }
          __syncwarp();
          if (lane == 0) mbar_arrive(b_hs + 16 + 8 * c);
          if (c) j1 += 7; else j0 += 7;
        }
        if (lane == 0) mbar_arrive(b_go);
        if (lane == 0) red_release_add(&g_hcnt[32 * (1 + (item0 & 15))], 1u);
      }
      sleep_until(t0, 26000);
      const uint32_t v = assign_tile(hm, t0, threadIdx.x & 31);
      if (threadIdx.x == 32) { sts_u32(s_bx, v); mbar_arrive(b_bx); }
      __syncwarp();
      store_warp(hm, sbase, &tmO, item0, n_items);
      __syncwarp();
    } else {
     if (elect_one()) {
      const uint64_t pol = policy_evict_first();
      prefetch_tmap(&tmW); prefetch_tmap(&tmX); prefetch_tmap(&tmWo); prefetch_tmap(&tmOl);
      if (single) {
        prefetch_tmap(&tmM);
        #pragma unroll 1
        for (uint32_t i = 0, buf = 0; i < 44; i++) {
          wait_clock(t0, i < 12 ? (blockIdx.x < 128 ? WDLY + W_OFF : WDLY) + (i & 3) * W_GAP + (i >> 2) * W_RND : W_LATE);
          #pragma unroll 1
          for (uint32_t spin = 0, n = 0; spin < (1u << 24) && n <= i; spin++) asm volatile("ld.volatile.shared.u32 %0, [%1];" : "=r"(n) : "r"(bars + 504) : "memory");
          mbar_expect_tx(bars + 464 + buf * 8, 32768);
          tma_load_2d_hint(sbase + (buf + (buf > 2 ? 2 : 0)) * 32768, &tmM, mod_col0(blockIdx.x - AT_NFULL, (int)(i >> 2) - 3), (i & 3) * 256, bars + 464 + buf * 8, pol);
          if (++buf == 5) buf = 0;
        }
        mbar_wait(b_go, 0);
      }
      {
        #pragma unroll 1
        for (int j = 0; j < T_D / 64; j++) {
          const uint32_t fb = b_full + 8 * (j & 3);
          mbar_wait(b_empty + 8 * (j & 3), ((j >> 2) & 1) ^ 1);
          mbar_expect_tx(fb, j == 0 ? 65536 : j == T_D / 64 - 1 ? 32768 : 49152);
          if (j < 2) wait_clock(t0, j ? ST1_T : PRE_T);
          if (j == 3) mbar_wait(b_a0, 0);
          if (j < 4) HS(2 + j);
          tma_load_3d_hint(sbase + (j & 3) * 32768, &tmW, j * 64, (item0 >> 4) * 4, fb, pol);
          if (j == 0) { wait_clock(t0, A_T); tma_load_2d_hint(sbase + AT_SQ, &tmX, 0, (item0 & 15) * 128, fb, pol); }
          if (j < T_D / 64 - 1) tma_load_2d_hint(sbase + AT_SQ + ((j + 1) & 3) * 16384, &tmX, (j + 1) * 64, (item0 & 15) * 128, fb, pol);
        }
      }
      uint32_t slot = 0, ph = 1;
      #pragma unroll 1
      for (int it = 0; it < n_items; it++) {
        const int item = item0 + it * 128, hp = item >> 4, qt = item & 15;
        const bool first = it == 0;
        if (!first) {
          #pragma unroll 1
          for (int j = 0; j < T_D / 64; j++) {
            const uint32_t sl = ring_slot(qp_pos(j, 1)), fb = b_full + 8 * sl;
            mbar_wait(b_empty + 8 * sl, ring_par(qp_pos(j, 1)) ^ ((j >> 2) & 1) ^ 1);
            mbar_expect_tx(fb, 49152);
            tma_load_3d_hint(sbase + sl * 32768, &tmW, j * 64, hp * 4, fb, pol);
            if (j == 0) { mbar_wait(b_q0, 0); mbar_wait(b_q1, 0); mbar_wait(b_w, 0); fence_proxy_async_global(); }
            tma_load_2d_hint(sbase + AT_SQ + (j & 3) * 16384, &tmOl, O_H + j * 64, qt * 128, fb, pol);
          }
        }
        #pragma unroll 1
        for (int j = 0; j < 4 * AT_NBLK; j++) {
          const bool isv = (j > 0 && !(j & 1)) || j == 4 * AT_NBLK - 1;
          const int row = hp * 2 * T_SEQ + (isv ? (j - 1) >> 1 : (j + 1) >> 1) * 128;
          const uint32_t fb = b_full + 8 * slot;
          mbar_wait(b_empty + 8 * slot, ph);
          if (!first && j == 3) mbar_wait(b_ob, 0);
          if (!first && j == 4) hint_arrive(&g_hcnt[32 * (1 + qt) + 1]);
          if (first && j == 4 && item0 < 112) mbar_wait(b_go, 0);
          mbar_expect_tx(fb, 32768);
          tma_load_2d_hint(sbase + slot * 32768, isv ? &tmV : &tmK, 0, row, fb, pol);
          tma_load_2d_hint(sbase + slot * 32768 + 16384, isv ? &tmV : &tmK, 64, row, fb, pol);
          if (it == 1 && isv && j >= 2 * WO_LATE && j < 2 * WO_LATE + 32 && blockIdx.x < 64)
            l2_prefetch_bulk(pf_wo + (size_t)blockIdx.x * 131072 + ((j >> 1) - WO_LATE) * 8192, 8192);
          if (++slot == 5) { slot = 0; ph ^= 1; }
        }
      }
      mbar_wait(b_bx, 0);
      const uint32_t bx = lds_u32(s_bx);
      if (bx < 128) {
        if (single) mbar_wait(b_go, 1);
        tail_producer(hm, bx, sbase, 0, n_items - 1, pol, &tmOl, &tmWo, &tmX, w_down);
      }
     }
    }
    __syncwarp();
    PSV(0, threadIdx.x == 96, t0);
    mbar_wait(b_bx, 0);
    const uint32_t bx = __shfl_sync(0xffffffffu, lds_u32(s_bx), 0);
    if (bx < 128) tail_exchange(hm, bx, sbase, wid, __shfl_sync(0xffffffffu, threadIdx.x, threadIdx.x), &tmOut, out);
  } else {
    if (wg == 1 && blockIdx.x < 128) head_first(hm, sbase + 4 * 32768 + 4096, threadIdx.x - 128, cvec, w_mod);
    named_bar_sync(10 + wg, 160);
    if (wg == 2 && blockIdx.x < 128) head_stats(hm, sbase + 3 * 32768, b_x, threadIdx.x - 256);
    if (single) {
      mod_rest(hm, t0, sbase, bars + 464, threadIdx.x - 128, (int)blockIdx.x - AT_NFULL, cvec, w_r);
      named_bar_sync(5, 256);
      if (threadIdx.x == 128) mbar_arrive(b_go);
    }
    if (wg == 1) { wait_clock(t0, GDLY); head_gather(hm, sbase + 4 * 32768, threadIdx.x - 128); }
    reg_alloc<AT_CREG>();
    const int cwg = wg - 1;
    const int tid = __shfl_sync(0xffffffffu, threadIdx.x, threadIdx.x) & 127;
    const int warp = wid & 3, lane = tid & 31;
    const uint32_t dbase = (sbase & 0x3FFFFu) >> 4;
    const uint32_t k_base = dbase + (1u << 16);
    const uint32_t v_base = dbase + (1024u << 16);
    const uint32_t w_base = dbase + (512u << 16);
    const uint32_t frag = cwg * 8192 + (16 * warp + (lane & 7) + 8 * ((lane >> 3) & 1)) * 128;
    if (cwg == 1) named_bar_arrive(1, 256);
    bool raw = false;
    constexpr int nkb = T_D / 64;
    float acc[128], c0, c1;
    {
      FS(0, 0);
      uint32_t af[2][16], rw[16];
      uint4 tb[4];
      uint32_t xa[4];
      #pragma unroll
      for (int st = 0; st < 4; st++) xa[st] = __shfl_sync(0xffffffffu, (sbase + AT_SQ + frag + (((lane >> 4) ^ (lane & 7)) << 4)) ^ (st * 32), lane);
      const uint32_t xt = __shfl_sync(0xffffffffu, sbase + 4 * 32768 + (lane & 3) * 16, lane);
      auto qp_fetch = [&](int j) {
        #pragma unroll
        for (int st = 0; st < 4; st++) {
          ldmatrix_x4(xa[st] + (j & 3) * 16384, rw[4 * st], rw[4 * st + 1], rw[4 * st + 2], rw[4 * st + 3]);
          tb[st] = lds_u32x4(xt + (j & 15) * 256 + st * 64);
        }
      };
      zero_regs(acc);
      #pragma unroll
      for (int i = 0; i < 16; i++) af[1][i] = 0u;
      const float2* stp = hm->stat + (item0 & 15) * 256 + (cwg * 4 + warp) * 32 + (lane & 3) * 8 + (lane >> 2);
      HS(4);
      wait_clock(t0, SDLY);
      float2 sv = ld_tagged2(stp);
      named_bar_sync(5, 256);
      mbar_wait(b_full, 0);
      HS(5);
      qp_fetch(0);
      #pragma unroll 1
      for (unsigned int spin = 0; spin < (1u << 22); spin++) {
        if (__all_sync(0xffffffffu, (__float_as_uint(sv.x) != 0u) & (__float_as_uint(sv.y) != 0u))) break;
        sv = ld_tagged2(stp);
      }
      HS(6);
      if (lane == 0) mbar_arrive(b_a0 + (rw[3] & rw[7] & rw[11] & rw[15] & zero));
      const uint32_t st = ln_stat(sv.x + __shfl_xor_sync(0xffffffffu, sv.x, 1), sv.y + __shfl_xor_sync(0xffffffffu, sv.y, 1)), so = __shfl_xor_sync(0xffffffffu, st, 2);
      const uint32_t sta = (lane & 2) ? so : st, stb = (lane & 2) ? st : so;
      const uint32_t mean_a = __byte_perm(sta, 0u, 0x1010), mean_b = __byte_perm(stb, 0u, 0x1010), sd_a = __byte_perm(sta, 0u, 0x3232), sd_b = __byte_perm(stb, 0u, 0x3232);
      c0 = AT_C * rcp_approx(bfhi(sta)); c1 = AT_C * rcp_approx(bfhi(stb));
      sts_u32(sbase + OG_SMISC + 256 + (cwg * 4 + warp) * 64 + (lane & 28) + (lane & 2) * 16, __float_as_uint((lane & 2) ? c1 : c0));
      int jst = item0 < 112 ? h_first(item0, cwg) : 99;
      #pragma unroll 1
      for (int j2 = 0; j2 < nkb; j2 += 2) {
        #pragma unroll
        for (int u = 0; u < 2; u++) {
          const int j = j2 + u;
          const uint32_t bt = b_tab + 4 * ((j + 1) & 15);
          if (u == 1) {
            #pragma unroll 1
            for (uint32_t z = 0; z < zero; z++)
              #pragma unroll
              for (int i = 0; i < 16; i += 4) sts_u32x4(xt + i * 4, af[1][i], af[1][i + 1], af[1][i + 2], af[1][i + 3]);
          }
          bool ok = mbar_test(b_full + 8 * (j & 3), (j >> 2) & 1);
          if (u == 1) ok &= mbar_test(bt, 0);
          #pragma unroll
          for (int st = 0; st < 4; st++) {
            af[u][4 * st + 0] = bfma2(bsub2(rw[4 * st + 0], mean_a), tb[st].x, bmul2(tb[st].z, sd_a));
            af[u][4 * st + 1] = bfma2(bsub2(rw[4 * st + 1], mean_b), tb[st].x, bmul2(tb[st].z, sd_b));
            af[u][4 * st + 2] = bfma2(bsub2(rw[4 * st + 2], mean_a), tb[st].y, bmul2(tb[st].w, sd_a));
            af[u][4 * st + 3] = bfma2(bsub2(rw[4 * st + 3], mean_b), tb[st].y, bmul2(tb[st].w, sd_b));
          }
          if (!ok || j == jst) {
            if (!ok) { mbar_wait(b_full + 8 * (j & 3), (j >> 2) & 1); if (u == 1) mbar_wait(bt, 0); }
            if (j == jst) {
              if (j >= 7) mbar_wait(b_hs + 16 + 8 * cwg, j >= 14);
              #pragma unroll
              for (int st = 0; st < 4; st++) stmatrix_x4(xa[st] - 16384, af[u][4 * st], af[u][4 * st + 1], af[u][4 * st + 2], af[u][4 * st + 3]);
              __syncwarp();
              if (lane == 0) mbar_arrive(b_hs + 8 * cwg);
              jst += 7;
            }
          }
          qp_fetch(j + 1);
          if (cwg == 1 && j == nkb - QP_STAG) named_bar_sync(7, 256);
          const uint32_t b_lo = w_base + (j & 3) * 2048;
          wgmma_fence();
          wgmma_m64n256k16_rs_tb<0>(acc, af[u][0], af[u][1], af[u][2], af[u][3], b_lo, 1);
          wgmma_m64n256k16_rs_tb<128>(acc, af[u][4], af[u][5], af[u][6], af[u][7], b_lo, 1);
          wgmma_m64n256k16_rs_tb<256>(acc, af[u][8], af[u][9], af[u][10], af[u][11], b_lo, 1);
          wgmma_m64n256k16_rs_tb<384>(acc, af[u][12], af[u][13], af[u][14], af[u][15], b_lo, 1);
          wgmma_commit();
          if (cwg == 0 && j == nkb - 1) named_bar_arrive(7, 256);
          if (j == 0) HS(7);
          wgmma_wait<1>();
          if (tid == 0) mbar_arrive(j > 0 ? b_empty + 8 * ((j - 1) & 3) : b_pin);
        }
      }
      wgmma_wait<0>();
      fence_regs(acc);
    }
    #pragma unroll 1
    for (int it = 0;;) {
      const int item = item0 + it * 128, hp = item >> 4;
      const bool more = it + 1 < n_items;
      const int ta = __shfl_sync(0xffffffffu, 4 * it, 0);
      FS(2 * it, 1);
      PS(1 + 2 * it, threadIdx.x == 256);
      if (tid == 0) mbar_arrive(b_empty + 24);
      float o[64], s[64];
      uint32_t p[32], q[32];
      #pragma unroll
      for (int i = 0; i < 32; i++) q[i] = pack_bf16(acc[2 * i] * ((i & 1) ? c1 : c0), acc[2 * i + 1] * ((i & 1) ? c1 : c0));
      zero_regs(s);
      const uint32_t sq = sbase + AT_SQ + cwg * 8192;
      const bool last_wg1 = cwg == 1 && !more;
      float mc0, mc1, al0 = 1.0f, al1 = 1.0f, l0 = 0.f, l1 = 0.f, lp0 = 0.f, lp1 = 0.f;
      bool redo0 = false;
      FS(2 * it, 2);
      {
        uint32_t dep = zero;
        #pragma unroll
        for (int i = 0; i < 32; i++) dep &= q[i];
        mbar_wait(b_full + 8 * ring_slot(ta) + dep, ring_par(ta));
      }
      named_bar_sync(1 + cwg, 256);
      FS(2 * it, 3);
      issue_qk(s, q, k_base + ring_slot(ta) * 2048);
      named_bar_arrive(1 + (cwg ^ 1), 256);
      const uint32_t rdy = (uint32_t)mbar_test(b_full + 8 * ring_slot(ta + 1), ring_par(ta + 1));
      bool ready = rdy & mbar_test(b_full + 8 * ring_slot(ta + 2), ring_par(ta + 2));
      stage_o(*reinterpret_cast<const float (*)[64]>(&acc[64]), c0, c1, sbase + AT_SQ + 32768 + frag, lane);
      wgmma_wait<0>();
      fence_regs(s);
      if (tid == 0) mbar_arrive(b_empty + 8 * ring_slot(ta));
      mc0 = 0.f; mc1 = 0.f;
      if (!raw) {
        raw = softmax_mode(s, mc0, mc1);
        if (__builtin_expect(!raw, 0)) softmax_sub(s, mc0, mc1);
      }
      softmax_exp<0, 64>(s);
      stage_qregs(q, sbase + AT_SQ + frag, lane);
      pack_p(p, s);
      zero_regs(o);
      FS(2 * it, 4);
      uint32_t ks = ring_slot(ta + 1), vs = ring_slot(ta + 2), kp = ring_par(ta + 1), vp = ring_par(ta + 2);
      if (!ready) { mbar_wait(b_full + 8 * ks, kp); mbar_wait(b_full + 8 * vs, vp); }
      #pragma unroll 1
      for (int n = 1; n < 2 * AT_NBLK; n++) {
        named_bar_sync(1 + cwg, 256);
        issue_qk(s, q, k_base + ks * 2048);
        if (n == AT_NBLK + 1) {
          redo0 = finish_l(lp0, lp1);
          if (!redo0) stage_o(o, lp0, lp1, sbase + AT_SQ + frag, lane);
        }
        issue_pv(o, p, v_base + vs * 2048, (n & 15) != 1);
        if (!(last_wg1 && n == 2 * AT_NBLK - 1)) named_bar_arrive(1 + (cwg ^ 1), 256);
        wgmma_wait<1>();
        fence_regs(s);
        if (tid == 0) mbar_arrive(b_empty + 8 * ks);
        if (__builtin_expect(!raw || (n + 1) >> 1 == AT_NBLK / 2, 0)) {
          if (n == AT_NBLK - 1) {
            #pragma unroll
            for (int J = 0; J < 16; J += 2)
              ldmatrix_x4(sbase + AT_SQ + 32768 + frag + (J >> 3) * 16384 + ((((J & 7) + (lane >> 4)) ^ (lane & 7)) << 4), q[2 * J], q[2 * J + 1], q[2 * J + 2], q[2 * J + 3]);
          }
          if (n == AT_NBLK && lane == 0) mbar_arrive(b_q1);
          if (!raw) {
            const float m0 = mc0, m1 = mc1;
            const bool ok = softmax_mode(s, mc0, mc1);
            if (n == AT_NBLK) raw = ok;
            else {
              mc0 = mc0 - AT_HEAD > m0 ? mc0 : m0; mc1 = mc1 - AT_HEAD > m1 ? mc1 : m1;
              al0 = ex2_approx(m0 - mc0); al1 = ex2_approx(m1 - mc1);
            }
            if (!raw) softmax_sub(s, mc0, mc1);
          }
        }
        softmax_exp<0, AT_SPLIT>(s);
        add_rowsum(p, l0, l1);
        if (tid == 0) {
          uint32_t dep = zero & __float_as_uint(l0) & __float_as_uint(l1);
          #pragma unroll
          for (int i = AT_SPLIT - AT_PIN - PINB; i < AT_SPLIT - PINB; i += 2) dep &= __float_as_uint(s[i]) & __float_as_uint(s[i + 1]);
          mbar_arrive(b_pin + dep);
        }
        wgmma_wait<0>();
        fence_regs(o);
        if (tid == 0) mbar_arrive(b_empty + 8 * vs);
        ks += 2; if (ks >= 5) { ks -= 5; kp ^= 1; }
        vs += 2; if (vs >= 5) { vs -= 5; vp ^= 1; }
        ready = mbar_test(b_full + 8 * ks, kp) & mbar_test(b_full + 8 * vs, vp);
        softmax_exp<AT_SPLIT, 64>(s);
        pack_p(p, s);
        if (n == AT_NBLK) { lp0 = l0; lp1 = l1; l0 = 0.f; l1 = 0.f; }
        if (__builtin_expect(!raw || !ready || n == AT_NBLK + 1, 0)) {
        if (n == AT_NBLK + 1 && !redo0) { fence_proxy_async(); __syncwarp(); if (lane == 0) mbar_arrive(b_ordy + 8 * cwg); }
        if (!raw && __any_sync(0xffffffffu, al0 != 1.0f || al1 != 1.0f)) {
          rescale_o(o, al0, al1);
          l0 *= al0; l1 *= al1;
          al0 = 1.0f; al1 = 1.0f;
        }
        if (!ready && n < 2 * AT_NBLK - 1) {
          mbar_wait(b_full + 8 * ks, kp);
          mbar_wait(b_full + 8 * vs, vp);
        }
        }
      }
      FS(2 * it + 1, 5);
      const uint32_t vl = ring_slot(ta + 63);
      vs = ring_slot(ta + 62);
      const uint32_t ob = more ? sbase + vs * 32768 : sbase + AT_SQ + 32768;
      mbar_wait(b_full + 8 * vl, ring_par(ta + 63));
      issue_pv(o, p, v_base + vl * 2048, 1);
      add_rowsum(p, l0, l1);
      const bool overflow = finish_l(l0, l1);
      mbar_wait(b_empty + 8 * vs, ring_par(ta + 62));
      wgmma_wait<0>();
      fence_regs(o);
      if (tid == 0) mbar_arrive(b_empty + 8 * vl);
      FS(2 * it + 1, 6);
      if (overflow) stage_qregs(q, ob + frag, lane);
      else stage_o(o, l0, l1, ob + frag, lane);
      if (__builtin_expect(overflow || redo0, 0)) {
        __syncwarp();
        #pragma unroll 1
        for (int h = redo0 ? 0 : 1; h < (overflow ? 2 : 1); h++)
          attn_rows_exact(h ? ob + cwg * 8192 : sq, warp, lane, kc + (size_t)(hp * 2 + h) * T_SEQ * T_DH, vc + (size_t)(hp * 2 + h) * T_SEQ * T_DH);
        fence_proxy_async();
        __syncwarp();
        if (lane == 0 && redo0) mbar_arrive(b_ordy + 8 * cwg);
        raw = false;
      }
      fence_proxy_async();
      __syncwarp();
      if (lane == 0) mbar_arrive(b_ordy + 16 + 8 * cwg);
      named_bar_sync(3 + cwg, 128);
      FS(2 * it + 1, 7);
      PS(2 + 2 * it, threadIdx.x == 256);
      if (++it == n_items) break;
      FS(2 * it, 0);
      zero_regs(acc);
      auto ss_step = [&](int j, int accumulate) {
        const uint32_t slot = ring_slot(qp_pos(j, 1));
        mbar_wait(b_full + 8 * slot, ring_par(qp_pos(j, 1)) ^ ((j >> 2) & 1));
        if (cwg == 1 && j == nkb - QP_STAG) named_bar_sync(7, 256);
        const uint32_t a_lo = dbase + ((AT_SQ + cwg * 8192) >> 4) + (1u << 16) + (j & 3) * 1024, b_lo = w_base + slot * 2048;
        wgmma_fence();
        wgmma_m64n256k16_ss_tb<0, 0>(acc, a_lo, b_lo, accumulate);
        wgmma_m64n256k16_ss_tb<2, 128>(acc, a_lo, b_lo, 1);
        wgmma_m64n256k16_ss_tb<4, 256>(acc, a_lo, b_lo, 1);
        wgmma_m64n256k16_ss_tb<6, 384>(acc, a_lo, b_lo, 1);
        wgmma_commit();
        return b_empty + 8 * slot;
      };
      uint32_t prev = ss_step(0, 0);
      c0 = lds_f32(sbase + OG_SMISC + 256 + (cwg * 4 + warp) * 64 + (lane & 28)); c1 = lds_f32(sbase + OG_SMISC + 288 + (cwg * 4 + warp) * 64 + (lane & 28));
      #pragma unroll 1
      for (int j = 1; j < nkb; j++) {
        const uint32_t cur = ss_step(j, 1);
        if (cwg == 0 && j == nkb - 1) named_bar_arrive(7, 256);
        wgmma_wait<1>();
        if (tid == 0) mbar_arrive(prev);
        prev = cur;
      }
      wgmma_wait<0>();
      fence_regs(acc);
    }
    if (single) {
      named_bar_sync(5, 256);
      if (threadIdx.x == 128) {
        #pragma unroll 1
        for (int i = 4; i < 8; i++) {
          mbar_arrive(b_full + 8 * ring_slot(i));
          mbar_arrive(b_empty + 8 * ring_slot(i)); mbar_arrive(b_empty + 8 * ring_slot(i));
        }
        mbar_arrive(b_go);
      }
      named_bar_sync(5, 256);
    }
    TL_CLK(3, 1, threadIdx.x == 128);
    TL_CTA(1, threadIdx.x == 256);
    TL_END(3, tid == 0);
    __syncwarp();
    QDUMP();
    TL_MARK2(19, tid == 0 && !single);
    mbar_wait(b_bx, 0);
    const uint32_t bx = __shfl_sync(0xffffffffu, lds_u32(s_bx), 0);
    if (bx < 128) {
      tail_consumer(hm, bx, sbase, tid, wid - 4, w_gate, w_up);
    }
  }
}

typedef CUresult (*PFN_encodeTiled)(CUtensorMap*, CUtensorMapDataType, cuuint32_t, void*, const cuuint64_t*, const cuuint64_t*,
                                    const cuuint32_t*, const cuuint32_t*, CUtensorMapInterleave, CUtensorMapSwizzle,
                                    CUtensorMapL2promotion, CUtensorMapFloatOOBfill);

CUtensorMap make_map_2d(PFN_encodeTiled enc, const void* ptr, uint64_t inner, uint64_t outer, uint64_t stride_bytes, uint32_t box_inner, uint32_t box_outer) {
  CUtensorMap m;
  cuuint64_t gd[2] = {inner, outer}; cuuint64_t gs[1] = {stride_bytes};
  cuuint32_t bx[2] = {box_inner, box_outer}; cuuint32_t es[2] = {1, 1};
  enc(&m, CU_TENSOR_MAP_DATA_TYPE_BFLOAT16, 2, const_cast<void*>(ptr), gd, gs, bx, es, CU_TENSOR_MAP_INTERLEAVE_NONE,
      CU_TENSOR_MAP_SWIZZLE_128B, CU_TENSOR_MAP_L2_PROMOTION_L2_128B, CU_TENSOR_MAP_FLOAT_OOB_FILL_NONE);
  return m;
}

CUtensorMap make_map_3d(PFN_encodeTiled enc, const void* ptr, uint64_t cols, uint64_t rows, uint32_t box_rows, uint32_t chunks) {
  CUtensorMap m;
  cuuint64_t gd[3] = {64, rows, cols / 64}; cuuint64_t gs[2] = {cols * 2, 128};
  cuuint32_t bx[3] = {64, box_rows, chunks}; cuuint32_t es[3] = {1, 1, 1};
  enc(&m, CU_TENSOR_MAP_DATA_TYPE_BFLOAT16, 3, const_cast<void*>(ptr), gd, gs, bx, es, CU_TENSOR_MAP_INTERLEAVE_NONE,
      CU_TENSOR_MAP_SWIZZLE_128B, CU_TENSOR_MAP_L2_PROMOTION_L2_128B, CU_TENSOR_MAP_FLOAT_OOB_FILL_NONE);
  return m;
}

}

extern "C" void kernel_launch(void* const* d_in, const int* in_sizes, int n_in, void* d_out, int out_size) {
  const bf16* x      = (const bf16*)d_in[0];
  const bf16* kc     = (const bf16*)d_in[1];
  const bf16* vc     = (const bf16*)d_in[2];
  const bf16* wq     = (const bf16*)d_in[3];
  const bf16* wo     = (const bf16*)d_in[4];
  const bf16* w_r    = (const bf16*)d_in[6];
  const bf16* w_gate = (const bf16*)d_in[7];
  const bf16* w_up   = (const bf16*)d_in[8];
  const bf16* w_down = (const bf16*)d_in[9];
  const bf16* cvec   = (const bf16*)d_in[10];
  const bf16* w_mod  = (const bf16*)d_in[11];
  bf16* out = (bf16*)d_out;

  static PFN_encodeTiled enc = nullptr;
  static void* p_hm = nullptr;
  if (!enc) {
    void* fn = nullptr; cudaDriverEntryPointQueryResult qres;
    cudaGetDriverEntryPoint("cuTensorMapEncodeTiled", &fn, cudaEnableDefault, &qres);
    enc = (PFN_encodeTiled)fn;
    cudaGetSymbolAddress(&p_hm, g_scr);
    cudaFuncSetAttribute(fused_kernel, cudaFuncAttributeMaxDynamicSharedMemorySize, (int)AT_SMEM);
  }
  const CUtensorMap tm_m   = make_map_2d(enc, w_mod, 6 * T_D, T_D, 6 * T_D * 2, 64, 256);
  const CUtensorMap tm_wq  = make_map_3d(enc, wq, T_DQKV, T_D, 64, 4);
  const CUtensorMap tm_k   = make_map_2d(enc, kc, T_DH, (uint64_t)T_NH * T_SEQ, T_DH * 2, 64, 128);
  const CUtensorMap tm_v   = make_map_2d(enc, vc, T_DH, (uint64_t)T_NH * T_SEQ, T_DH * 2, 64, 128);
  const CUtensorMap tm_ost = make_map_2d(enc, ((Scratch*)p_hm)->o, O_LD, T_SEQ, O_LD * 2, 64, 64);
  const CUtensorMap tm_old = make_map_2d(enc, ((Scratch*)p_hm)->o, O_LD, T_SEQ, O_LD * 2, 64, 128);
  const CUtensorMap tm_wo  = make_map_2d(enc, wo, T_D, T_DQKV, T_D * 2, 64, 64);
  const CUtensorMap tm_x   = make_map_2d(enc, x, T_D, T_SEQ, T_D * 2, 64, 128);
  const CUtensorMap tm_out = make_map_2d(enc, out, T_D, T_SEQ, T_D * 2, 64, 128);

#define TUNE_ARG
  fused_kernel<<<132, 384, AT_SMEM, cudaStreamPerThread>>>(x, cvec, w_mod, (Scratch*)p_hm, 0u, TUNE_ARG (const uint8_t*)wo, kc, vc, w_r, w_gate, w_up, w_down, out,
             tm_m, tm_wq, tm_k, tm_v, tm_ost, tm_old, tm_wo, tm_x, tm_out);
}
```

```cpp
#include <cuda_runtime.h>
#include <cuda_bf16.h>
#include <cuda.h>
#include <stdint.h>

namespace {

typedef __nv_bfloat16 bf16;

constexpr int T_SEQ = 2048, T_D = 1024, T_NH = 32, T_DH = 128, T_DQKV = 4096, T_F = 3584;

struct __align__(2048) TailMail {
  float4 part1[T_SEQ * 8];
  uint32_t key[256];
  uint4 cand[16 * 2 * 2 * 128];
  uint32_t cnt[32];
  float ypart[(T_F / 32) * 2 * T_D];
};
constexpr int O_LD = T_DQKV, O_H = 16 * T_DH;
struct __align__(2048) Scratch {
  TailMail mail;
  float mod[2 * T_D];
  float modu[16 * 512];
  float2 stat[T_SEQ * 2];
  uint32_t gkey[160];
  uint8_t col[8 * 1536];
  unsigned int hcnt[17 * 32];
  float scal[4];
  __align__(1024) bf16 o[T_SEQ * O_LD];
};
__device__ Scratch g_scr;
#define g_part1 hm->mail.part1
#define g_key hm->mail.key
#define g_cand hm->mail.cand
#define CNT_Y hm->mail.cnt
#define g_ypart hm->mail.ypart
#define g_col hm->col
#define g_scal hm->scal
#define g_hcnt hm->hcnt

__device__ __forceinline__ uint32_t smem_u32(const void* p) { return (uint32_t)__cvta_generic_to_shared(p); }
__device__ __forceinline__ void mbar_init(uint32_t bar, uint32_t cnt) { asm volatile("mbarrier.init.shared::cta.b64 [%0], %1;" :: "r"(bar), "r"(cnt)); }
__device__ __forceinline__ void mbar_expect_tx(uint32_t bar, uint32_t bytes) { asm volatile("mbarrier.arrive.expect_tx.shared::cta.b64 _, [%0], %1;" :: "r"(bar), "r"(bytes) : "memory"); }
__device__ __forceinline__ void mbar_arrive(uint32_t bar) { asm volatile("mbarrier.arrive.shared::cta.b64 _, [%0];" :: "r"(bar) : "memory"); }
__device__ __forceinline__ void mbar_wait(uint32_t bar, uint32_t parity) {
  asm volatile("{\n.reg .pred p;\nLAB_WAIT:\nmbarrier.try_wait.parity.shared::cta.b64 p, [%0], %1;\n@!p bra LAB_WAIT;\n}\n" :: "r"(bar), "r"(parity) : "memory");
}
__device__ __forceinline__ bool mbar_test(uint32_t bar, uint32_t parity) {
  uint32_t r; asm volatile("{\n.reg .pred p;\nmbarrier.test_wait.parity.shared::cta.b64 p, [%1], %2;\nselp.u32 %0, 1, 0, p;\n}\n" : "=r"(r) : "r"(bar), "r"(parity) : "memory");
  return r != 0;
}
__device__ __forceinline__ void fence_mbar_init() { asm volatile("fence.mbarrier_init.release.cluster;" ::: "memory"); }
__device__ __forceinline__ uint64_t policy_evict_first() {
  uint64_t p; asm volatile("createpolicy.fractional.L2::evict_first.b64 %0, 1.0;" : "=l"(p)); return p;
}
__device__ __forceinline__ void tma_load_2d_hint(uint32_t dst, const CUtensorMap* map, int c0, int c1, uint32_t bar, uint64_t pol) {
  asm volatile("cp.async.bulk.tensor.2d.shared::cluster.global.mbarrier::complete_tx::bytes.L2::cache_hint [%0], [%1, {%3, %4}], [%2], %5;"
    :: "r"(dst), "l"(map), "r"(bar), "r"(c0), "r"(c1), "l"(pol) : "memory");
}
__device__ __forceinline__ void tma_load_3d_hint(uint32_t dst, const CUtensorMap* map, int c1, int c2, uint32_t bar, uint64_t pol) {
  asm volatile("cp.async.bulk.tensor.3d.shared::cluster.global.mbarrier::complete_tx::bytes.L2::cache_hint [%0], [%1, {%6, %3, %4}], [%2], %5;"
    :: "r"(dst), "l"(map), "r"(bar), "r"(c1), "r"(c2), "l"(pol), "r"(0) : "memory");
}
__device__ __forceinline__ void tma_store_2d(const CUtensorMap* map, uint32_t src, int c0, int c1) {
  asm volatile("cp.async.bulk.tensor.2d.global.shared::cta.bulk_group [%0, {%2, %3}], [%1];" :: "l"(map), "r"(src), "r"(c0), "r"(c1) : "memory");
}
__device__ __forceinline__ void prefetch_tmap(const CUtensorMap* map) { asm volatile("prefetch.tensormap [%0];" :: "l"(map) : "memory"); }
__device__ __forceinline__ void l2_prefetch_bulk(const void* p, uint32_t bytes) {
  asm volatile("cp.async.bulk.prefetch.L2.global [%0], %1;" :: "l"(p), "r"(bytes) : "memory");
}
__device__ __forceinline__ void bulk_commit() { asm volatile("cp.async.bulk.commit_group;" ::: "memory"); }
template<int N> __device__ __forceinline__ void bulk_wait_read() { asm volatile("cp.async.bulk.wait_group.read %0;" :: "n"(N) : "memory"); }
template<int N> __device__ __forceinline__ void bulk_wait() { asm volatile("cp.async.bulk.wait_group %0;" :: "n"(N) : "memory"); }
__device__ __forceinline__ void named_bar_sync(int id, int nthreads) { asm volatile("bar.sync %0, %1;" :: "r"(id), "r"(nthreads) : "memory"); }
__device__ __forceinline__ void named_bar_arrive(int id, int nthreads) { asm volatile("bar.arrive %0, %1;" :: "r"(id), "r"(nthreads) : "memory"); }
__device__ __forceinline__ void wgmma_fence() { asm volatile("wgmma.fence.sync.aligned;" ::: "memory"); }
__device__ __forceinline__ void wgmma_commit() { asm volatile("wgmma.commit_group.sync.aligned;" ::: "memory"); }
template<int N> __device__ __forceinline__ void wgmma_wait() { asm volatile("wgmma.wait_group.sync.aligned %0;" :: "n"(N) : "memory"); }
template<int R> __device__ __forceinline__ void reg_alloc() { asm volatile("setmaxnreg.inc.sync.aligned.u32 %0;" :: "n"(R)); }
template<int R> __device__ __forceinline__ void reg_dealloc() { asm volatile("setmaxnreg.dec.sync.aligned.u32 %0;" :: "n"(R)); }
__device__ __forceinline__ bool elect_one() {
  uint32_t pred; asm volatile("{\n.reg .pred p;\nelect.sync _|p, 0xffffffff;\nselp.u32 %0, 1, 0, p;\n}\n" : "=r"(pred)); return pred != 0;
}
__device__ __forceinline__ uint32_t pack_bf16(float lo, float hi) {
  uint32_t r; asm("cvt.rn.bf16x2.f32 %0, %1, %2;" : "=r"(r) : "f"(hi), "f"(lo)); return r;
}
__device__ __forceinline__ void stmatrix_x4(uint32_t addr, uint32_t r0, uint32_t r1, uint32_t r2, uint32_t r3) {
  asm volatile("stmatrix.sync.aligned.m8n8.x4.shared.b16 [%0], {%1, %2, %3, %4};" :: "r"(addr), "r"(r0), "r"(r1), "r"(r2), "r"(r3) : "memory");
}
__device__ __forceinline__ void fence_proxy_async() { asm volatile("fence.proxy.async.shared::cta;" ::: "memory"); }
__device__ __forceinline__ float ex2_approx(float x) { float y; asm("ex2.approx.ftz.f32 %0, %1;" : "=f"(y) : "f"(x)); return y; }
template<int N> __device__ __forceinline__ void fence_regs(float (&r)[N]) {
  #pragma unroll
  for (int i = 0; i < N; i++) asm volatile("" : "+f"(r[i]) :: "memory");
}
template<int N> __device__ __forceinline__ void zero_regs(float (&r)[N]) {
  #pragma unroll
  for (int i = 0; i < N; i += 2) asm volatile("mov.b64 {%0, %1}, 0;" : "=f"(r[i]), "=f"(r[i + 1]));
}
__device__ __forceinline__ float rbf(float x) { return __uint_as_float(pack_bf16(0.f, x)); }
__device__ __forceinline__ float bflo(uint32_t v) { return __uint_as_float(v << 16); }
__device__ __forceinline__ float bfhi(uint32_t v) { return __uint_as_float(v & 0xffff0000u); }

#define TL_START(k) do {} while (0)
#define TL_END(k, cond) do {} while (0)
#define TL_CTA(i, cond) do {} while (0)
#define FS(slot, k) do {} while (0)
#define QS(idx) do {} while (0)
#define QDUMP() do {} while (0)
#define TL_MARK2(k, cond) do {} while (0)
#define TL_CLK(k, i, cond) do {} while (0)

#define HS(k) do {} while (0)
#define HSD(k, dep) do {} while (0)
#define HSDUMP() do {} while (0)
#define PS(k, cond) do {} while (0)
#define PSV(k, cond, v) do {} while (0)
#define PF(k) do {} while (0)
#define TS(k, cond) do {} while (0)
template <int OFFA, int OFFB>
__device__ __forceinline__ void wgmma_m64n256k16_ss_tb(float (&d)[128], uint32_t a_lo, uint32_t b_lo, int scaleD) {
  asm volatile("{\n.reg .pred p;\n.reg .b32 ta, tb;\n.reg .b64 da, db;\nsetp.ne.b32 p, %130, 0;\n"
    "add.u32 ta, %128, %131;\nadd.u32 tb, %129, %132;\n"
    "mov.b64 da, {ta, 0x40000040};\nmov.b64 db, {tb, 0x40000040};\n"
    "wgmma.mma_async.sync.aligned.m64n256k16.f32.bf16.bf16 "
    "{%0, %1, %2, %3, %4, %5, %6, %7, %8, %9, %10, %11, %12, %13, %14, %15, %16, %17, %18, %19, %20, %21, %22, %23, %24, %25, %26, %27, %28, %29, %30, %31, %32, %33, %34, %35, %36, %37, %38, %39, %40, %41, %42, %43, %44, %45, %46, %47, %48, %49, %50, %51, %52, %53, %54, %55, %56, %57, %58, %59, %60, %61, %62, %63, %64, %65, %66, %67, %68, %69, %70, %71, %72, %73, %74, %75, %76, %77, %78, %79, %80, %81, %82, %83, %84, %85, %86, %87, %88, %89, %90, %91, %92, %93, %94, %95, %96, %97, %98, %99, %100, %101, %102, %103, %104, %105, %106, %107, %108, %109, %110, %111, %112, %113, %114, %115, %116, %117, %118, %119, %120, %121, %122, %123, %124, %125, %126, %127}, "
    "da, db, p, 1, 1, 0, 1;\n}\n"
    : "+f"(d[0]), "+f"(d[1]), "+f"(d[2]), "+f"(d[3]), "+f"(d[4]), "+f"(d[5]), "+f"(d[6]), "+f"(d[7]), "+f"(d[8]), "+f"(d[9]), "+f"(d[10]), "+f"(d[11]), "+f"(d[12]), "+f"(d[13]), "+f"(d[14]), "+f"(d[15]), "+f"(d[16]), "+f"(d[17]), "+f"(d[18]), "+f"(d[19]), "+f"(d[20]), "+f"(d[21]), "+f"(d[22]), "+f"(d[23]), "+f"(d[24]), "+f"(d[25]), "+f"(d[26]), "+f"(d[27]), "+f"(d[28]), "+f"(d[29]), "+f"(d[30]), "+f"(d[31]), "+f"(d[32]), "+f"(d[33]), "+f"(d[34]), "+f"(d[35]), "+f"(d[36]), "+f"(d[37]), "+f"(d[38]), "+f"(d[39]), "+f"(d[40]), "+f"(d[41]), "+f"(d[42]), "+f"(d[43]), "+f"(d[44]), "+f"(d[45]), "+f"(d[46]), "+f"(d[47]), "+f"(d[48]), "+f"(d[49]), "+f"(d[50]), "+f"(d[51]), "+f"(d[52]), "+f"(d[53]), "+f"(d[54]), "+f"(d[55]), "+f"(d[56]), "+f"(d[57]), "+f"(d[58]), "+f"(d[59]), "+f"(d[60]), "+f"(d[61]), "+f"(d[62]), "+f"(d[63]), "+f"(d[64]), "+f"(d[65]), "+f"(d[66]), "+f"(d[67]), "+f"(d[68]), "+f"(d[69]), "+f"(d[70]), "+f"(d[71]), "+f"(d[72]), "+f"(d[73]), "+f"(d[74]), "+f"(d[75]), "+f"(d[76]), "+f"(d[77]), "+f"(d[78]), "+f"(d[79]), "+f"(d[80]), "+f"(d[81]), "+f"(d[82]), "+f"(d[83]), "+f"(d[84]), "+f"(d[85]), "+f"(d[86]), "+f"(d[87]), "+f"(d[88]), "+f"(d[89]), "+f"(d[90]), "+f"(d[91]), "+f"(d[92]), "+f"(d[93]), "+f"(d[94]), "+f"(d[95]), "+f"(d[96]), "+f"(d[97]), "+f"(d[98]), "+f"(d[99]), "+f"(d[100]), "+f"(d[101]), "+f"(d[102]), "+f"(d[103]), "+f"(d[104]), "+f"(d[105]), "+f"(d[106]), "+f"(d[107]), "+f"(d[108]), "+f"(d[109]), "+f"(d[110]), "+f"(d[111]), "+f"(d[112]), "+f"(d[113]), "+f"(d[114]), "+f"(d[115]), "+f"(d[116]), "+f"(d[117]), "+f"(d[118]), "+f"(d[119]), "+f"(d[120]), "+f"(d[121]), "+f"(d[122]), "+f"(d[123]), "+f"(d[124]), "+f"(d[125]), "+f"(d[126]), "+f"(d[127])
    : "r"(a_lo), "r"(b_lo), "r"(scaleD), "n"(OFFA), "n"(OFFB));
}

template <int OFFA, int OFFB>
__device__ __forceinline__ void wgmma_m64n128k16_ss_tb(float (&d)[64], uint32_t a_lo, uint32_t b_lo, int scaleD) {
  asm volatile("{\n.reg .pred p;\n.reg .b32 ta, tb;\n.reg .b64 da, db;\nsetp.ne.b32 p, %66, 0;\n"
    "add.u32 ta, %64, %67;\nadd.u32 tb, %65, %68;\n"
    "mov.b64 da, {ta, 0x40000040};\nmov.b64 db, {tb, 0x40000040};\n"
    "wgmma.mma_async.sync.aligned.m64n128k16.f32.bf16.bf16 "
    "{%0, %1, %2, %3, %4, %5, %6, %7, %8, %9, %10, %11, %12, %13, %14, %15, %16, %17, %18, %19, %20, %21, %22, %23, %24, %25, %26, %27, %28, %29, %30, %31, %32, %33, %34, %35, %36, %37, %38, %39, %40, %41, %42, %43, %44, %45, %46, %47, %48, %49, %50, %51, %52, %53, %54, %55, %56, %57, %58, %59, %60, %61, %62, %63}, "
    "da, db, p, 1, 1, 0, 1;\n}\n"
    : "+f"(d[0]), "+f"(d[1]), "+f"(d[2]), "+f"(d[3]), "+f"(d[4]), "+f"(d[5]), "+f"(d[6]), "+f"(d[7]), "+f"(d[8]), "+f"(d[9]), "+f"(d[10]), "+f"(d[11]), "+f"(d[12]), "+f"(d[13]), "+f"(d[14]), "+f"(d[15]), "+f"(d[16]), "+f"(d[17]), "+f"(d[18]), "+f"(d[19]), "+f"(d[20]), "+f"(d[21]), "+f"(d[22]), "+f"(d[23]), "+f"(d[24]), "+f"(d[25]), "+f"(d[26]), "+f"(d[27]), "+f"(d[28]), "+f"(d[29]), "+f"(d[30]), "+f"(d[31]), "+f"(d[32]), "+f"(d[33]), "+f"(d[34]), "+f"(d[35]), "+f"(d[36]), "+f"(d[37]), "+f"(d[38]), "+f"(d[39]), "+f"(d[40]), "+f"(d[41]), "+f"(d[42]), "+f"(d[43]), "+f"(d[44]), "+f"(d[45]), "+f"(d[46]), "+f"(d[47]), "+f"(d[48]), "+f"(d[49]), "+f"(d[50]), "+f"(d[51]), "+f"(d[52]), "+f"(d[53]), "+f"(d[54]), "+f"(d[55]), "+f"(d[56]), "+f"(d[57]), "+f"(d[58]), "+f"(d[59]), "+f"(d[60]), "+f"(d[61]), "+f"(d[62]), "+f"(d[63])
    : "r"(a_lo), "r"(b_lo), "r"(scaleD), "n"(OFFA), "n"(OFFB));
}

template <int OFFB>
__device__ __forceinline__ void wgmma_m64n256k16_rs_tb(float (&d)[128], uint32_t a0, uint32_t a1, uint32_t a2, uint32_t a3, uint32_t b_lo, int scaleD) {
  asm volatile("{\n.reg .pred p;\n.reg .b32 tb;\n.reg .b64 db;\nsetp.ne.b32 p, %133, 0;\n"
    "add.u32 tb, %132, %134;\n"
    "mov.b64 db, {tb, 0x40000040};\n"
    "wgmma.mma_async.sync.aligned.m64n256k16.f32.bf16.bf16 "
    "{%0, %1, %2, %3, %4, %5, %6, %7, %8, %9, %10, %11, %12, %13, %14, %15, %16, %17, %18, %19, %20, %21, %22, %23, %24, %25, %26, %27, %28, %29, %30, %31, %32, %33, %34, %35, %36, %37, %38, %39, %40, %41, %42, %43, %44, %45, %46, %47, %48, %49, %50, %51, %52, %53, %54, %55, %56, %57, %58, %59, %60, %61, %62, %63, %64, %65, %66, %67, %68, %69, %70, %71, %72, %73, %74, %75, %76, %77, %78, %79, %80, %81, %82, %83, %84, %85, %86, %87, %88, %89, %90, %91, %92, %93, %94, %95, %96, %97, %98, %99, %100, %101, %102, %103, %104, %105, %106, %107, %108, %109, %110, %111, %112, %113, %114, %115, %116, %117, %118, %119, %120, %121, %122, %123, %124, %125, %126, %127}, "
    "{%128, %129, %130, %131}, db, p, 1, 1, 1;\n}\n"
    : "+f"(d[0]), "+f"(d[1]), "+f"(d[2]), "+f"(d[3]), "+f"(d[4]), "+f"(d[5]), "+f"(d[6]), "+f"(d[7]), "+f"(d[8]), "+f"(d[9]), "+f"(d[10]), "+f"(d[11]), "+f"(d[12]), "+f"(d[13]), "+f"(d[14]), "+f"(d[15]), "+f"(d[16]), "+f"(d[17]), "+f"(d[18]), "+f"(d[19]), "+f"(d[20]), "+f"(d[21]), "+f"(d[22]), "+f"(d[23]), "+f"(d[24]), "+f"(d[25]), "+f"(d[26]), "+f"(d[27]), "+f"(d[28]), "+f"(d[29]), "+f"(d[30]), "+f"(d[31]), "+f"(d[32]), "+f"(d[33]), "+f"(d[34]), "+f"(d[35]), "+f"(d[36]), "+f"(d[37]), "+f"(d[38]), "+f"(d[39]), "+f"(d[40]), "+f"(d[41]), "+f"(d[42]), "+f"(d[43]), "+f"(d[44]), "+f"(d[45]), "+f"(d[46]), "+f"(d[47]), "+f"(d[48]), "+f"(d[49]), "+f"(d[50]), "+f"(d[51]), "+f"(d[52]), "+f"(d[53]), "+f"(d[54]), "+f"(d[55]), "+f"(d[56]), "+f"(d[57]), "+f"(d[58]), "+f"(d[59]), "+f"(d[60]), "+f"(d[61]), "+f"(d[62]), "+f"(d[63]), "+f"(d[64]), "+f"(d[65]), "+f"(d[66]), "+f"(d[67]), "+f"(d[68]), "+f"(d[69]), "+f"(d[70]), "+f"(d[71]), "+f"(d[72]), "+f"(d[73]), "+f"(d[74]), "+f"(d[75]), "+f"(d[76]), "+f"(d[77]), "+f"(d[78]), "+f"(d[79]), "+f"(d[80]), "+f"(d[81]), "+f"(d[82]), "+f"(d[83]), "+f"(d[84]), "+f"(d[85]), "+f"(d[86]), "+f"(d[87]), "+f"(d[88]), "+f"(d[89]), "+f"(d[90]), "+f"(d[91]), "+f"(d[92]), "+f"(d[93]), "+f"(d[94]), "+f"(d[95]), "+f"(d[96]), "+f"(d[97]), "+f"(d[98]), "+f"(d[99]), "+f"(d[100]), "+f"(d[101]), "+f"(d[102]), "+f"(d[103]), "+f"(d[104]), "+f"(d[105]), "+f"(d[106]), "+f"(d[107]), "+f"(d[108]), "+f"(d[109]), "+f"(d[110]), "+f"(d[111]), "+f"(d[112]), "+f"(d[113]), "+f"(d[114]), "+f"(d[115]), "+f"(d[116]), "+f"(d[117]), "+f"(d[118]), "+f"(d[119]), "+f"(d[120]), "+f"(d[121]), "+f"(d[122]), "+f"(d[123]), "+f"(d[124]), "+f"(d[125]), "+f"(d[126]), "+f"(d[127])
    : "r"(a0), "r"(a1), "r"(a2), "r"(a3), "r"(b_lo), "r"(scaleD), "n"(OFFB));
}

template <int OFFB>
__device__ __forceinline__ void wgmma_m64n128k16_rs_tb(float (&d)[64], uint32_t a0, uint32_t a1, uint32_t a2, uint32_t a3, uint32_t b_lo, int scaleD) {
  asm volatile("{\n.reg .pred p;\n.reg .b32 tb;\n.reg .b64 db;\nsetp.ne.b32 p, %69, 0;\n"
    "add.u32 tb, %68, %70;\n"
    "mov.b64 db, {tb, 0x40000040};\n"
    "wgmma.mma_async.sync.aligned.m64n128k16.f32.bf16.bf16 "
    "{%0, %1, %2, %3, %4, %5, %6, %7, %8, %9, %10, %11, %12, %13, %14, %15, %16, %17, %18, %19, %20, %21, %22, %23, %24, %25, %26, %27, %28, %29, %30, %31, %32, %33, %34, %35, %36, %37, %38, %39, %40, %41, %42, %43, %44, %45, %46, %47, %48, %49, %50, %51, %52, %53, %54, %55, %56, %57, %58, %59, %60, %61, %62, %63}, "
    "{%64, %65, %66, %67}, db, p, 1, 1, 1;\n}\n"
    : "+f"(d[0]), "+f"(d[1]), "+f"(d[2]), "+f"(d[3]), "+f"(d[4]), "+f"(d[5]), "+f"(d[6]), "+f"(d[7]), "+f"(d[8]), "+f"(d[9]), "+f"(d[10]), "+f"(d[11]), "+f"(d[12]), "+f"(d[13]), "+f"(d[14]), "+f"(d[15]), "+f"(d[16]), "+f"(d[17]), "+f"(d[18]), "+f"(d[19]), "+f"(d[20]), "+f"(d[21]), "+f"(d[22]), "+f"(d[23]), "+f"(d[24]), "+f"(d[25]), "+f"(d[26]), "+f"(d[27]), "+f"(d[28]), "+f"(d[29]), "+f"(d[30]), "+f"(d[31]), "+f"(d[32]), "+f"(d[33]), "+f"(d[34]), "+f"(d[35]), "+f"(d[36]), "+f"(d[37]), "+f"(d[38]), "+f"(d[39]), "+f"(d[40]), "+f"(d[41]), "+f"(d[42]), "+f"(d[43]), "+f"(d[44]), "+f"(d[45]), "+f"(d[46]), "+f"(d[47]), "+f"(d[48]), "+f"(d[49]), "+f"(d[50]), "+f"(d[51]), "+f"(d[52]), "+f"(d[53]), "+f"(d[54]), "+f"(d[55]), "+f"(d[56]), "+f"(d[57]), "+f"(d[58]), "+f"(d[59]), "+f"(d[60]), "+f"(d[61]), "+f"(d[62]), "+f"(d[63])
    : "r"(a0), "r"(a1), "r"(a2), "r"(a3), "r"(b_lo), "r"(scaleD), "n"(OFFB));
}

template <int OFFB>
__device__ __forceinline__ void wgmma_m64n128k16_rs(float (&d)[64], uint32_t a0, uint32_t a1, uint32_t a2, uint32_t a3, uint32_t b_lo, int scaleD) {
  asm volatile("{\n.reg .pred p;\n.reg .b32 tb;\n.reg .b64 db;\nsetp.ne.b32 p, %69, 0;\n"
    "add.u32 tb, %68, %70;\n"
    "mov.b64 db, {tb, 0x40000040};\n"
    "wgmma.mma_async.sync.aligned.m64n128k16.f32.bf16.bf16 "
    "{%0, %1, %2, %3, %4, %5, %6, %7, %8, %9, %10, %11, %12, %13, %14, %15, %16, %17, %18, %19, %20, %21, %22, %23, %24, %25, %26, %27, %28, %29, %30, %31, %32, %33, %34, %35, %36, %37, %38, %39, %40, %41, %42, %43, %44, %45, %46, %47, %48, %49, %50, %51, %52, %53, %54, %55, %56, %57, %58, %59, %60, %61, %62, %63}, "
    "{%64, %65, %66, %67}, db, p, 1, 1, 0;\n}\n"
    : "+f"(d[0]), "+f"(d[1]), "+f"(d[2]), "+f"(d[3]), "+f"(d[4]), "+f"(d[5]), "+f"(d[6]), "+f"(d[7]), "+f"(d[8]), "+f"(d[9]), "+f"(d[10]), "+f"(d[11]), "+f"(d[12]), "+f"(d[13]), "+f"(d[14]), "+f"(d[15]), "+f"(d[16]), "+f"(d[17]), "+f"(d[18]), "+f"(d[19]), "+f"(d[20]), "+f"(d[21]), "+f"(d[22]), "+f"(d[23]), "+f"(d[24]), "+f"(d[25]), "+f"(d[26]), "+f"(d[27]), "+f"(d[28]), "+f"(d[29]), "+f"(d[30]), "+f"(d[31]), "+f"(d[32]), "+f"(d[33]), "+f"(d[34]), "+f"(d[35]), "+f"(d[36]), "+f"(d[37]), "+f"(d[38]), "+f"(d[39]), "+f"(d[40]), "+f"(d[41]), "+f"(d[42]), "+f"(d[43]), "+f"(d[44]), "+f"(d[45]), "+f"(d[46]), "+f"(d[47]), "+f"(d[48]), "+f"(d[49]), "+f"(d[50]), "+f"(d[51]), "+f"(d[52]), "+f"(d[53]), "+f"(d[54]), "+f"(d[55]), "+f"(d[56]), "+f"(d[57]), "+f"(d[58]), "+f"(d[59]), "+f"(d[60]), "+f"(d[61]), "+f"(d[62]), "+f"(d[63])
    : "r"(a0), "r"(a1), "r"(a2), "r"(a3), "r"(b_lo), "r"(scaleD), "n"(OFFB));
}

__device__ __forceinline__ uint4 ldg_nc_v4(const void* p) {
  uint4 v;
    asm volatile("{\n.reg .b64 pol;\ncreatepolicy.fractional.L2::evict_first.b64 pol, 1.0;\n"
                 "ld.global.nc.L1::no_allocate.L2::cache_hint.v4.u32 {%0, %1, %2, %3}, [%4], pol;\n}\n" : "=r"(v.x), "=r"(v.y), "=r"(v.z), "=r"(v.w) : "l"(p));
  return v;
}
__device__ __forceinline__ uint64_t pol_normal() {
  uint64_t p; asm volatile("createpolicy.fractional.L2::evict_normal.b64 %0, 1.0;" : "=l"(p)); return p;
}
__device__ __forceinline__ float rcp_approx(float x) { float y; asm("rcp.approx.ftz.f32 %0, %1;" : "=f"(y) : "f"(x)); return y; }
__device__ __forceinline__ float sigmoid_f(float v) { return rcp_approx(1.0f + ex2_approx(v * -1.4426950408889634f)); }
__device__ __forceinline__ float silu_bf(float v) { return rbf(v * sigmoid_f(v)); }
__device__ __forceinline__ uint32_t rank_key(float r, int idx) {
  const uint32_t b = __float_as_uint(r) >> 16;
  const uint32_t u = (r != r) ? 0u : ((b & 0x8000u) ? (~b & 0xffffu) : (b | 0x8000u));
  return (u << 16) | (0xffffu - (uint32_t)idx);
}
__device__ __forceinline__ void warp_top2(uint32_t& k1, uint32_t& k2) {
  const uint32_t m1 = __reduce_max_sync(0xffffffffu, k1);
  k2 = __reduce_max_sync(0xffffffffu, k1 == m1 ? k2 : k1);
  k1 = m1;
}
__device__ __forceinline__ uint32_t bmul2(uint32_t a, uint32_t b) { uint32_t r; asm("mul.rn.bf16x2 %0, %1, %2;" : "=r"(r) : "r"(a), "r"(b)); return r; }
__device__ __forceinline__ uint32_t badd2(uint32_t a, uint32_t b) { uint32_t r; asm("add.rn.bf16x2 %0, %1, %2;" : "=r"(r) : "r"(a), "r"(b)); return r; }
__device__ __forceinline__ uint32_t bsub2(uint32_t a, uint32_t b) { uint32_t r; asm("sub.rn.bf16x2 %0, %1, %2;" : "=r"(r) : "r"(a), "r"(b)); return r; }
__device__ __forceinline__ float sqrt_approx(float x) { float y; asm("sqrt.approx.f32 %0, %1;" : "=f"(y) : "f"(x)); return y; }
__device__ __forceinline__ uint32_t ln_norm2(uint32_t x1, uint32_t mb2, float inv) {
  const uint32_t d = bsub2(x1, mb2);
  return pack_bf16(bflo(d) * inv, bfhi(d) * inv);
}
__device__ __forceinline__ uint32_t ln_mod2(uint32_t x1, uint32_t mb2, float inv, uint32_t c1, uint32_t sb) { return badd2(bmul2(ln_norm2(x1, mb2, inv), c1), sb); }
__device__ __forceinline__ void ldmatrix_x4(uint32_t addr, uint32_t& r0, uint32_t& r1, uint32_t& r2, uint32_t& r3) {
  asm volatile("ldmatrix.sync.aligned.m8n8.x4.shared.b16 {%0, %1, %2, %3}, [%4];" : "=r"(r0), "=r"(r1), "=r"(r2), "=r"(r3) : "r"(addr) : "memory");
}
__device__ __forceinline__ uint4 ldg_stream_v4(const void* p, uint64_t pol) {
  uint4 v; asm volatile("ld.global.nc.L1::no_allocate.L2::cache_hint.L2::128B.v4.u32 {%0, %1, %2, %3}, [%4], %5;" : "=r"(v.x), "=r"(v.y), "=r"(v.z), "=r"(v.w) : "l"(p), "l"(pol)); return v;
}
__device__ __forceinline__ void bulk_load_hint(uint32_t dst, const void* src, uint32_t bytes, uint32_t bar, uint64_t pol) {
  asm volatile("cp.async.bulk.shared::cluster.global.mbarrier::complete_tx::bytes.L2::cache_hint [%0], [%1], %2, [%3], %4;"
    :: "r"(dst), "l"(src), "r"(bytes), "r"(bar), "l"(pol) : "memory");
}
__device__ __forceinline__ void red_release_add(unsigned int* p, unsigned int v) { asm volatile("red.release.gpu.global.add.u32 [%0], %1;" :: "l"(p), "r"(v) : "memory"); }
__device__ __forceinline__ unsigned int ld_acquire(const unsigned int* p) { unsigned int v; asm volatile("ld.acquire.gpu.global.u32 %0, [%1];" : "=r"(v) : "l"(p) : "memory"); return v; }
__device__ __forceinline__ void spin_until(const unsigned int* p, unsigned int target) {
  #pragma unroll 1
  for (unsigned int i = 0; i < (1u << 22); i++) { if (ld_acquire(p) >= target) return; }
}
__device__ __forceinline__ float lds_f32(uint32_t a) { float v; asm volatile("ld.shared.f32 %0, [%1];" : "=f"(v) : "r"(a) : "memory"); return v; }
__device__ __forceinline__ uint2 lds_u32x2(uint32_t a) { uint2 v; asm volatile("ld.shared.v2.u32 {%0, %1}, [%2];" : "=r"(v.x), "=r"(v.y) : "r"(a) : "memory"); return v; }
__device__ __forceinline__ uint32_t lds_u32(uint32_t a) { uint32_t v; asm volatile("ld.shared.u32 %0, [%1];" : "=r"(v) : "r"(a) : "memory"); return v; }
__device__ __forceinline__ void sts_u32(uint32_t a, uint32_t v) { asm volatile("st.shared.u32 [%0], %1;" :: "r"(a), "r"(v) : "memory"); }
__device__ __forceinline__ void sts_u32x2(uint32_t a, uint32_t x, uint32_t y) { asm volatile("st.shared.v2.u32 [%0], {%1, %2};" :: "r"(a), "r"(x), "r"(y) : "memory"); }
__device__ __forceinline__ void sts_f32(uint32_t a, float v) { asm volatile("st.shared.f32 [%0], %1;" :: "r"(a), "f"(v) : "memory"); }
__device__ __forceinline__ void sts_f32x4(uint32_t a, float x, float y, float z, float w) { asm volatile("st.shared.v4.f32 [%0], {%1, %2, %3, %4};" :: "r"(a), "f"(x), "f"(y), "f"(z), "f"(w) : "memory"); }

__device__ __forceinline__ uint4 lds_u32x4(uint32_t a) { uint4 v; asm volatile("ld.shared.v4.u32 {%0, %1, %2, %3}, [%4];" : "=r"(v.x), "=r"(v.y), "=r"(v.z), "=r"(v.w) : "r"(a) : "memory"); return v; }
__device__ __forceinline__ void sts_u32x4(uint32_t a, uint32_t x, uint32_t y, uint32_t z, uint32_t w) { asm volatile("st.shared.v4.u32 [%0], {%1, %2, %3, %4};" :: "r"(a), "r"(x), "r"(y), "r"(z), "r"(w) : "memory"); }
__device__ __forceinline__ void st_tagged(float* p, float v) {
  const uint32_t b = __float_as_uint(v);
  asm volatile("st.relaxed.gpu.global.u32 [%0], %1;" :: "l"(p), "r"(b == 0u ? 0x80000000u : b) : "memory");
}
__device__ __forceinline__ void st_tagged4(float* p, float x, float y, float z, float w) {
  const uint32_t a = __float_as_uint(x), b = __float_as_uint(y), c = __float_as_uint(z), d = __float_as_uint(w);
  asm volatile("st.relaxed.gpu.global.v4.u32 [%0], {%1, %2, %3, %4};" :: "l"(p), "r"(a == 0u ? 0x80000000u : a), "r"(b == 0u ? 0x80000000u : b),
               "r"(c == 0u ? 0x80000000u : c), "r"(d == 0u ? 0x80000000u : d) : "memory");
}
__device__ __forceinline__ void st_relaxed2(void* p, uint32_t a, uint32_t b) { asm volatile("st.relaxed.gpu.global.v2.u32 [%0], {%1, %2};" :: "l"(p), "r"(a), "r"(b) : "memory"); }
__device__ __forceinline__ float4 ld_tagged4(const float* p) {
  float4 v; asm volatile("ld.relaxed.gpu.global.v4.f32 {%0, %1, %2, %3}, [%4];" : "=f"(v.x), "=f"(v.y), "=f"(v.z), "=f"(v.w) : "l"(p) : "memory"); return v;
}
__device__ __forceinline__ bool tagged4(const float4& v) {
  return __float_as_uint(v.x) != 0u && __float_as_uint(v.y) != 0u && __float_as_uint(v.z) != 0u && __float_as_uint(v.w) != 0u;
}
__device__ __forceinline__ void hint_arrive(uint32_t* p) { asm volatile("red.relaxed.gpu.global.add.u32 [%0], 1;" :: "l"(p) : "memory"); }
__device__ __forceinline__ void hint_wait(const uint32_t* p, uint32_t target) {
  uint32_t v = 0u;
  #pragma unroll 1
  for (unsigned int i = 0; i < (1u << 22) && v < target; i++) asm volatile("ld.relaxed.gpu.global.u32 %0, [%1];" : "=r"(v) : "l"(p) : "memory");
}
__device__ __forceinline__ void fence_proxy_async_global() { asm volatile("fence.proxy.async.global;" ::: "memory"); }

__device__ __forceinline__ void mma_bf16(float (&d)[4], uint32_t a0, uint32_t a1, uint32_t a2, uint32_t a3, uint32_t b0, uint32_t b1) {
  asm volatile("mma.sync.aligned.m16n8k16.row.col.f32.bf16.bf16.f32 {%0, %1, %2, %3}, {%4, %5, %6, %7}, {%8, %9}, {%0, %1, %2, %3};"
               : "+f"(d[0]), "+f"(d[1]), "+f"(d[2]), "+f"(d[3]) : "r"(a0), "r"(a1), "r"(a2), "r"(a3), "r"(b0), "r"(b1));
}
__device__ __forceinline__ uint32_t bfma2(uint32_t a, uint32_t b, uint32_t c) { uint32_t r; asm("fma.rn.bf16x2 %0, %1, %2, %3;" : "=r"(r) : "r"(a), "r"(b), "r"(c)); return r; }
#define XDLY 1000
#define PRE_T 1000
#define GDLY 4150
#define A_T 4800
#define SDLY 5800
#define ST1_T 6000
#define GDLY2 8000
#define WDLY 3800
#define W_OFF 2000
#define W_GAP 300
#define W_RND 3600
#define W_LATE 27000
#define CLR_T 70000
#define SGL_T 79000
#define OG_PRE 12
#define OG_LEN 6
#define WD_0 16
#define WD_S 6
#define NDUM 16
__device__ __forceinline__ uint32_t clock_lo() { uint32_t c; asm volatile("mov.u32 %0, %%clock;" : "=r"(c) :: "memory"); return c; }
__device__ __forceinline__ void wait_clock(uint32_t t0, uint32_t n) {
  #pragma unroll 1
  while (clock_lo() - t0 < n) {}
}
__device__ __forceinline__ void sleep_until(uint32_t t0, uint32_t n) {
  #pragma unroll 1
  while (clock_lo() - t0 < n) __nanosleep(500);
}
__device__ __forceinline__ float2 ld_tagged2(const float2* p) {
  float2 v; asm volatile("ld.relaxed.gpu.global.v2.f32 {%0, %1}, [%2];" : "=f"(v.x), "=f"(v.y) : "l"(p) : "memory"); return v;
}
template <int N>
__device__ __forceinline__ void gemv64(float (&d)[2][4], const uint4 (&w)[N], const uint32_t (&sv)[N / 2], int lane) {
  const int g = lane >> 2;
  const uint32_t lo = (g & 1) ? 0x1044u : 0x4410u, hi = (g & 1) ? 0x3244u : 0x4432u;
  const uint32_t lo0 = g < 2 ? lo : 0x4444u, hi0 = g < 2 ? hi : 0x4444u, lo1 = (g & 6) == 2 ? lo : 0x4444u, hi1 = (g & 6) == 2 ? hi : 0x4444u;
  #pragma unroll
  for (int i = 0; i < N; i++)
    mma_bf16(d[i & 1], w[i].x, w[i].y, w[i].z, w[i].w, __byte_perm(sv[i >> 1], 0u, (i & 1) ? hi0 : lo0), __byte_perm(sv[i >> 1], 0u, (i & 1) ? hi1 : lo1));
}
template <int NW>
__device__ __forceinline__ float gemv64_sum(const float (&d)[2][4], uint32_t scr, int t2) {
  if ((t2 & 2) == 0) sts_f32x4(scr + (t2 >> 2) * 32 + (t2 & 1) * 16, d[0][0] + d[1][0], d[0][1] + d[1][1], d[0][2] + d[1][2], d[0][3] + d[1][3]);
  named_bar_sync(NW == 8 ? 5 : 3, NW * 32);
  float sum = 0.f;
  #pragma unroll
  for (int i = 0; i < NW; i += 2) sum += lds_f32(scr + i * 256 + (t2 & 63) * 4) + lds_f32(scr + i * 256 + 256 + (t2 & 63) * 4);
  return sum;
}
__device__ __forceinline__ uint32_t silu2(uint32_t c) { return pack_bf16(silu_bf(bflo(c)), silu_bf(bfhi(c))); }
__device__ __forceinline__ void head_first(Scratch* hm, uint32_t scr, int t2, const bf16* __restrict__ cvec, const bf16* __restrict__ w_mod) {
  const int row = (blockIdx.x >> 3) * 64 + (t2 >> 5) * 16 + (t2 & 3) * 4;
  const bf16* wp = w_mod + (size_t)row * (6 * T_D) + (blockIdx.x & 4) * 256 + (blockIdx.x & 3) * 64 + (t2 & 28) * 2;
  uint4 w[4];
  #pragma unroll
  for (int i = 0; i < 4; i++) w[i] = ldg_nc_v4(wp + i * 6 * T_D);
  const uint2 c = *reinterpret_cast<const uint2*>(cvec + row);
  const uint32_t sv[2] = {silu2(c.x), silu2(c.y)};
  float d[2][4] = {{0.f, 0.f, 0.f, 0.f}, {0.f, 0.f, 0.f, 0.f}};
  gemv64<4>(d, w, sv, t2 & 31);
  const float sum = gemv64_sum<4>(d, scr, t2);
  if (t2 < 64) st_tagged(hm->modu + (blockIdx.x >> 3) * 512 + (blockIdx.x & 7) * 64 + t2, sum);
  HS(1);
}
__device__ __forceinline__ void head_stats(Scratch* hm, uint32_t xs, uint32_t b_x, int tid) {
  const int lane = tid & 31, w = tid >> 5, g = lane >> 2;
  float d[4][4] = {{0.f, 0.f, 0.f, 0.f}, {0.f, 0.f, 0.f, 0.f}, {0.f, 0.f, 0.f, 0.f}, {0.f, 0.f, 0.f, 0.f}};
  const uint32_t xa = xs + ((w & 1) * 8 + g) * 2048 + (w >> 1) * 1024 + (g & 1) * 64 + (lane & 3) * 16;
  float2* dst = hm->stat + ((blockIdx.x * 2 + (w & 1)) * 2 + (w >> 1)) * 8 + g;
  mbar_wait(b_x, 0);
  #pragma unroll
  for (int j = 0; j < 16; j++) {
    const uint4 v = lds_u32x4((xa ^ ((j & 1) * 64)) + (j >> 1) * 128);
    mma_bf16(d[2 * (j & 1)], v.x, 0x3F803F80u, v.y, 0x3F803F80u, v.x, v.y);
    mma_bf16(d[2 * (j & 1) + 1], v.z, 0x3F803F80u, v.w, 0x3F803F80u, v.z, v.w);
  }
  #pragma unroll
  for (int e = 0; e < 4; e++) d[0][e] = (d[0][e] + d[1][e]) + (d[2][e] + d[3][e]);
  const uint32_t sm = __float_as_uint((g & 1) ? d[0][3] : d[0][2]), sq = __float_as_uint((g & 1) ? d[0][1] : d[0][0]);
  if ((lane & 3) == (g >> 1)) st_relaxed2(dst, sm == 0u ? 0x80000000u : sm, sq == 0u ? 0x80000000u : sq);
  HSD(3, sm);
}
__device__ __forceinline__ void put_table(uint32_t tab, int l, bool ca, const float4& v) {
  uint32_t m0 = pack_bf16(v.x, v.y), m1 = pack_bf16(v.z, v.w);
  if (ca) { m0 = badd2(m0, 0x3F803F80u); m1 = badd2(m1, 0x3F803F80u); }
  tab += (l >> 2) * 64 + (l & 1) * 32 + (l & 2) * 2 + (ca ? 0 : 8);
  sts_u32(tab, m0); sts_u32(tab + 16, m1);
}
__device__ __forceinline__ void head_gather(Scratch* hm, uint32_t tab, int tid) {
  float4 p[16];
  #pragma unroll 1
  for (unsigned int spin = 0; spin < (1u << 22); spin++) {
    uint32_t m = 0xffffffffu;
    #pragma unroll
    for (int k = 0; k < 16; k++) p[k] = ld_tagged4(hm->modu + k * 512 + tid * 4);
    #pragma unroll
    for (int k = 0; k < 16; k++) m = min(min(m, min(__float_as_uint(p[k].x), __float_as_uint(p[k].y))), min(__float_as_uint(p[k].z), __float_as_uint(p[k].w)));
    if (m != 0u) break;
  }
  #pragma unroll
  for (int o = 1; o < 16; o <<= 1)
    #pragma unroll
    for (int k = 0; k < 16; k += 2 * o) { p[k].x += p[k + o].x; p[k].y += p[k + o].y; p[k].z += p[k + o].z; p[k].w += p[k + o].w; }
  put_table(tab, tid & 63, tid >= 64, p[0]);
  __syncwarp();
  HS(2);
}
__device__ __forceinline__ uint32_t ln_stat(float sm, float sq) {
  const float mean = sm * (1.0f / T_D), var = fmaxf(fmaf(-mean, mean, sq * (1.0f / T_D)), 0.f);
  return pack_bf16(mean, sqrt_approx(rbf(rbf(var) + 1e-05f)));
}
__device__ __forceinline__ void gather_table(Scratch* hm, uint32_t tab0, uint32_t b_tab, int a, int lane) {
  #pragma unroll 1
  for (int r = 2; r < 8; r++) {
    float4 v;
    #pragma unroll 1
    for (unsigned int spin = 0; spin < (1u << 22); spin++) {
      v = ld_tagged4(hm->mod + a * T_D + r * 128 + lane * 4);
      if (__all_sync(0xffffffffu, tagged4(v))) break;
      __nanosleep(50);
    }
    put_table(tab0 + r * 512, lane, a, v);
    __syncwarp();
    if (lane == 0) mbar_arrive(b_tab + 8 * r);
    if (r < 6) HS(2 + r);
  }
}

__device__ __forceinline__ uint32_t assign_tile(Scratch* hm, uint32_t t0, int lane) {
  uint32_t me; asm("mov.u32 %0, %%smid;" : "=r"(me));
  me = (me & 255u) + 1u;
  if (lane == 0) asm volatile("st.relaxed.gpu.global.u32 [%0], %1;" :: "l"(hm->gkey + blockIdx.x), "r"((t0 & ~511u) | me) : "memory");
  uint32_t k[5];
  #pragma unroll 1
  for (unsigned int spin = 0; spin < (1u << 20); spin++) {
    __nanosleep(200);
    #pragma unroll
    for (int m = 0; m < 5; m++) asm volatile("ld.relaxed.gpu.global.u32 %0, [%1];" : "=r"(k[m]) : "l"(hm->gkey + m * 32 + lane) : "memory");
    if (__all_sync(0xffffffffu, k[0] != 0u && k[1] != 0u && k[2] != 0u && k[3] != 0u && (k[4] != 0u || lane >= 4))) break;
  }
  uint32_t sz = 0u, g = 0u, rank = 0u, w[5];
  #pragma unroll
  for (int m = 0; m < 5; m++) w[m] = k[m] == 0u ? 0u : (k[m] & 511u) < me ? 257u : (k[m] & 511u) == me ? 65537u : 1u;
  #pragma unroll 1
  for (int i = 0; i < 16; i++) {
    const uint32_t v = __reduce_max_sync(0xffffffffu, max(max(max(k[0], k[1]), max(k[2], k[3])), k[4])), lo = (i == 15 || v < 2048u) ? 0u : v - 2048u;
    uint32_t n = 0u;
    #pragma unroll
    for (int m = 0; m < 5; m++) { const bool in = k[m] >= lo; n += in ? w[m] : 0u; w[m] = in ? 0u : w[m]; k[m] = in ? 0u : k[m]; }
    n = __reduce_add_sync(0xffffffffu, n);
    if (lane == i) sz = n & 255u;
    if (n >> 16) { g = i; rank = (n >> 8) & 255u; }
  }
  #pragma unroll 1
  for (int d = 0; d < 4; d += 2)
    if ((__reduce_max_sync(0xffffffffu, sz * 32u + lane) & 31u) == (uint32_t)lane) sz -= 2;
  const uint32_t gs = __shfl_sync(0xffffffffu, sz, g);
  const uint32_t off = __reduce_add_sync(0xffffffffu, (sz != 16u) * 32u + lane < (gs != 16u) * 32u + g ? sz : 0u);
  return rank < gs ? off + rank : 128u;
}

__device__ __forceinline__ int col_pos(int c) { return (c & ~31) + ((c >> 1) & 3) * 8 + ((c >> 3) & 3) * 2 + (c & 1); }
__device__ __forceinline__ int mod_col0(int j, int b) { return b < 0 ? (j & 1) * T_D + (b + 4) * 256 + ((j >> 1) ^ 2) * 64 : 2 * T_D + j * 512 + b * 64; }
__device__ __noinline__ void mod_rest(Scratch* hm, uint32_t t0, uint32_t sbase, uint32_t bar, int t2, int j, const bf16* __restrict__ cvec, const bf16* __restrict__ w_r) {
  const uint32_t scr = sbase + 4 * 32768 + 8192;
  const int kind = j >> 1;
  const uint2 c4 = *reinterpret_cast<const uint2*>(cvec + t2 * 4);
  sts_u32x2(scr + t2 * 8, silu2(c4.x), silu2(c4.y));
  const int w8 = t2 >> 5, t = t2 & 3, g = (t2 >> 2) & 7;
  float dot = 0.f;
  uint32_t buf = 0, par = 0;
  named_bar_sync(5, 256);
  #pragma unroll 1
  for (int b = -3; b < 8; b++) {
    float d[2][4] = {{0.f, 0.f, 0.f, 0.f}, {0.f, 0.f, 0.f, 0.f}};
    #pragma unroll 1
    for (int k = 0; k < 4; k++) {
      const uint32_t wa = sbase + (buf + (buf > 2 ? 2 : 0)) * 32768 + w8 * 4096 + t * 256;
      uint4 w[8];
      uint32_t sv[4];
      #pragma unroll
      for (int i = 0; i < 4; i++) sv[i] = lds_u32(scr + k * 512 + w8 * 64 + i * 16 + t * 4);
      mbar_wait(bar + buf * 8, par);
      #pragma unroll
      for (int i = 0; i < 8; i++) w[i] = lds_u32x4(wa + (i >> 1) * 1024 + (i & 1) * 128 + ((g ^ (t * 2 + (i & 1))) << 4));
      gemv64<8>(d, w, sv, t2 & 31);
      named_bar_sync(5, 256);
      if (t2 == 0) sts_u32(bar + 40, b * 4 + k + 18);
      if (++buf == 5) { buf = 0; par ^= 1; }
    }
    const int c0 = mod_col0(j, b);
    float v = gemv64_sum<8>(d, scr + 2048, t2);
    if (t2 < 64) {
      if (b < 0) st_tagged(hm->mod + c0 + t2, v);
      else {
        const int col = (c0 + t2) & 1023;
        uint8_t* dst = g_col + (col >> 7) * 1536;
        v = rbf(v);
        if (kind == 2) v = rbf(1.0f + v);
        const float vw = v * __bfloat162float(w_r[col]);
        dot += vw;
        if (kind == 2) {
          reinterpret_cast<bf16*>(dst)[col_pos(col & 127)] = __float2bfloat16_rn(vw);
          reinterpret_cast<bf16*>(dst)[128 + col_pos(col & 127)] = __float2bfloat16_rn(vw - rbf(vw));
        }
        reinterpret_cast<bf16*>(dst + 512 + (kind == 0 ? 0 : kind == 2 ? 256 : kind == 1 ? 512 : 768))[col_pos(col & 127)] = __float2bfloat16_rn(v);
      }
    }
  }
  #pragma unroll
  for (int o = 16; o > 0; o >>= 1) dot += __shfl_xor_sync(0xffffffffu, dot, o);
  if (t2 == 32) sts_f32(scr + 4096, dot);
  fence_proxy_async();
  named_bar_sync(5, 256);
  if (t2 == 0 && (kind == 1 || kind == 2)) g_scal[(kind == 2 ? 0 : 2) + (j & 1)] = dot + lds_f32(scr + 4096);
  sleep_until(t0, CLR_T);
  #pragma unroll 1
  for (int i = j * 256 + t2; i < (int)(sizeof(TailMail) / 16); i += 8 * 256) reinterpret_cast<uint4*>(&hm->mail)[i] = make_uint4(0u, 0u, 0u, 0u);
  named_bar_sync(5, 256);
  if (t2 == 0) red_release_add(&g_hcnt[0], 1u);
  sleep_until(t0, SGL_T);
}

constexpr int AT_NBLK = T_SEQ / 128;
constexpr float AT_HEAD = 7.0f;
#define WOL 12
constexpr int WO_LATE = WOL;
#define QSTG 3
constexpr int QP_STAG = QSTG;
constexpr int AT_SPLIT = 28, AT_PIN = 8, PINB = 4;
constexpr int AT_NFULL = 124;
constexpr int AT_PREG = 40, AT_CREG = 232;
constexpr uint32_t AT_SQ = 5 * 32768;
constexpr float AT_C = 0.08838834764831845f * 1.4426950408889634f;
constexpr float AT_RAW_LO = -16.0f, AT_RAW_HI = 24.0f;
constexpr float AT_RAW_SUM = 281474976710656.0f, AT_RAW_MIN = 9.094947017729282e-13f;
constexpr uint32_t AT_SBAR = AT_SQ + 65536 + 256;
constexpr uint32_t AT_SMEM = AT_SQ + 65536 + 3072;

__device__ __forceinline__ uint32_t ring_slot(uint32_t t) { return t - 5u * ((t * 205u) >> 10); }
__device__ __forceinline__ uint32_t qp_pos(uint32_t j, uint32_t it) { return 4u * it + (j & 3u) + ((j & 3u) == 3u ? it : 0u); }
__device__ __forceinline__ uint32_t ring_par(uint32_t t) { return ((t * 205u) >> 10) & 1u; }
__device__ __forceinline__ void softmax_rowmax(const float (&s)[64], float& mx0, float& mx1) {
  float a0 = fmaxf(s[0], s[1]), a1 = fmaxf(s[4], s[5]), a2 = fmaxf(s[8], s[9]), a3 = fmaxf(s[12], s[13]);
  float b0 = fmaxf(s[2], s[3]), b1 = fmaxf(s[6], s[7]), b2 = fmaxf(s[10], s[11]), b3 = fmaxf(s[14], s[15]);
  #pragma unroll
  for (int j = 4; j < 16; j += 4) {
    a0 = fmaxf(a0, fmaxf(s[4 * j + 0], s[4 * j + 1]));  b0 = fmaxf(b0, fmaxf(s[4 * j + 2], s[4 * j + 3]));
    a1 = fmaxf(a1, fmaxf(s[4 * j + 4], s[4 * j + 5]));  b1 = fmaxf(b1, fmaxf(s[4 * j + 6], s[4 * j + 7]));
    a2 = fmaxf(a2, fmaxf(s[4 * j + 8], s[4 * j + 9]));  b2 = fmaxf(b2, fmaxf(s[4 * j + 10], s[4 * j + 11]));
    a3 = fmaxf(a3, fmaxf(s[4 * j + 12], s[4 * j + 13])); b3 = fmaxf(b3, fmaxf(s[4 * j + 14], s[4 * j + 15]));
  }
  mx0 = fmaxf(fmaxf(a0, a1), fmaxf(a2, a3));
  mx1 = fmaxf(fmaxf(b0, b1), fmaxf(b2, b3));
  mx0 = fmaxf(mx0, __shfl_xor_sync(0xffffffffu, mx0, 1));
  mx1 = fmaxf(mx1, __shfl_xor_sync(0xffffffffu, mx1, 1));
  mx0 = fmaxf(mx0, __shfl_xor_sync(0xffffffffu, mx0, 2));
  mx1 = fmaxf(mx1, __shfl_xor_sync(0xffffffffu, mx1, 2));
}
__device__ __forceinline__ void softmax_sub(float (&s)[64], float mc0, float mc1) {
  #pragma unroll
  for (int j = 0; j < 16; j++) { s[4 * j] -= mc0; s[4 * j + 1] -= mc0; s[4 * j + 2] -= mc1; s[4 * j + 3] -= mc1; }
}
template <int LO, int HI>
__device__ __forceinline__ void softmax_exp(float (&s)[64]) {
  #pragma unroll
  for (int i = LO; i < HI; i++) s[i] = ex2_approx(s[i]);
}
__device__ __forceinline__ bool softmax_mode(const float (&s)[64], float& mc0, float& mc1) {
  softmax_rowmax(s, mc0, mc1);
  const bool raw = __all_sync(0xffffffffu, mc0 >= AT_RAW_LO && mc0 <= AT_RAW_HI && mc1 >= AT_RAW_LO && mc1 <= AT_RAW_HI);
  mc0 += AT_HEAD; mc1 += AT_HEAD;
  return raw;
}
__device__ __forceinline__ void rowsum_p(const uint32_t (&p)[32], uint32_t& t0, uint32_t& t1) {
  uint32_t a[16];
  #pragma unroll
  for (int i = 0; i < 8; i++) { a[2 * i] = badd2(p[4 * i], p[4 * i + 2]); a[2 * i + 1] = badd2(p[4 * i + 1], p[4 * i + 3]); }
  #pragma unroll
  for (int i = 0; i < 4; i++) { a[2 * i] = badd2(a[4 * i], a[4 * i + 2]); a[2 * i + 1] = badd2(a[4 * i + 1], a[4 * i + 3]); }
  t0 = badd2(badd2(a[0], a[2]), badd2(a[4], a[6]));
  t1 = badd2(badd2(a[1], a[3]), badd2(a[5], a[7]));
}
__device__ __forceinline__ void add_rowsum(const uint32_t (&p)[32], float& l0, float& l1) {
  uint32_t t0, t1;
  rowsum_p(p, t0, t1);
  l0 += bflo(t0) + bfhi(t0); l1 += bflo(t1) + bfhi(t1);
}
__device__ __forceinline__ void pack_p(uint32_t (&p)[32], const float (&s)[64]) {
  #pragma unroll
  for (int i = 0; i < 32; i++) p[i] = pack_bf16(s[2 * i], s[2 * i + 1]);
}
__device__ __noinline__ void attn_rows_exact(uint32_t sq, int warp, int lane, const bf16* __restrict__ kh, const bf16* __restrict__ vh) {
  #pragma unroll 1
  for (int r = 16 * warp; r < 16 * warp + 16; r++) {
    const uint32_t ad = (lane >> 4) * 16384 + r * 128 + ((((lane & 15) >> 1) ^ (r & 7)) << 4) + (lane & 1) * 8;
    uint2 qv; asm volatile("ld.shared.v2.u32 {%0, %1}, [%2];" : "=r"(qv.x), "=r"(qv.y) : "r"(sq + ad) : "memory");
    const float q0 = bflo(qv.x), q1 = bfhi(qv.x), q2 = bflo(qv.y), q3 = bfhi(qv.y);
    float m = -INFINITY, l = 0.f, o0 = 0.f, o1 = 0.f, o2 = 0.f, o3 = 0.f;
    #pragma unroll 1
    for (int key = 0; key < T_SEQ; key++) {
      const uint2 kv = *reinterpret_cast<const uint2*>(kh + (size_t)key * T_DH + lane * 4);
      const uint2 vv = *reinterpret_cast<const uint2*>(vh + (size_t)key * T_DH + lane * 4);
      float sc = (q0 * bflo(kv.x) + q1 * bfhi(kv.x)) + (q2 * bflo(kv.y) + q3 * bfhi(kv.y));
      #pragma unroll
      for (int o = 16; o > 0; o >>= 1) sc += __shfl_xor_sync(0xffffffffu, sc, o);
      const float mn = fmaxf(m, sc);
      const float al = (m == mn) ? 1.0f : ex2_approx(m - mn), p = rbf(ex2_approx(sc - mn));
      m = mn;
      l = fmaf(l, al, p);
      o0 = fmaf(o0, al, p * bflo(vv.x)); o1 = fmaf(o1, al, p * bfhi(vv.x));
      o2 = fmaf(o2, al, p * bflo(vv.y)); o3 = fmaf(o3, al, p * bfhi(vv.y));
    }
    const float inv = rcp_approx(l);
    asm volatile("st.shared.v2.u32 [%0], {%1, %2};" :: "r"(sq + ad), "r"(pack_bf16(o0 * inv, o1 * inv)), "r"(pack_bf16(o2 * inv, o3 * inv)) : "memory");
  }
}
__device__ __forceinline__ void issue_qk(float (&s)[64], const uint32_t (&q)[32], uint32_t k_lo) {
  wgmma_fence();
  wgmma_m64n128k16_rs<0>(s, q[0], q[1], q[2], q[3], k_lo, 0);
  wgmma_m64n128k16_rs<2>(s, q[4], q[5], q[6], q[7], k_lo, 1);
  wgmma_m64n128k16_rs<4>(s, q[8], q[9], q[10], q[11], k_lo, 1);
  wgmma_m64n128k16_rs<6>(s, q[12], q[13], q[14], q[15], k_lo, 1);
  wgmma_m64n128k16_rs<1024>(s, q[16], q[17], q[18], q[19], k_lo, 1);
  wgmma_m64n128k16_rs<1026>(s, q[20], q[21], q[22], q[23], k_lo, 1);
  wgmma_m64n128k16_rs<1028>(s, q[24], q[25], q[26], q[27], k_lo, 1);
  wgmma_m64n128k16_rs<1030>(s, q[28], q[29], q[30], q[31], k_lo, 1);
  wgmma_commit();
}
__device__ __forceinline__ void issue_pv(float (&o)[64], const uint32_t (&p)[32], uint32_t v_lo, int accumulate) {
  wgmma_fence();
  wgmma_m64n128k16_rs_tb<0>(o, p[0], p[1], p[2], p[3], v_lo, accumulate);
  wgmma_m64n128k16_rs_tb<128>(o, p[4], p[5], p[6], p[7], v_lo, 1);
  wgmma_m64n128k16_rs_tb<256>(o, p[8], p[9], p[10], p[11], v_lo, 1);
  wgmma_m64n128k16_rs_tb<384>(o, p[12], p[13], p[14], p[15], v_lo, 1);
  wgmma_m64n128k16_rs_tb<512>(o, p[16], p[17], p[18], p[19], v_lo, 1);
  wgmma_m64n128k16_rs_tb<640>(o, p[20], p[21], p[22], p[23], v_lo, 1);
  wgmma_m64n128k16_rs_tb<768>(o, p[24], p[25], p[26], p[27], v_lo, 1);
  wgmma_m64n128k16_rs_tb<896>(o, p[28], p[29], p[30], p[31], v_lo, 1);
  wgmma_commit();
}
__device__ __forceinline__ void rescale_o(float (&o)[64], float al0, float al1) {
  #pragma unroll
  for (int j = 0; j < 16; j++) { o[4 * j] *= al0; o[4 * j + 1] *= al0; o[4 * j + 2] *= al1; o[4 * j + 3] *= al1; }
}

__device__ __forceinline__ void stage_o(const float (&o)[64], float i0, float i1, uint32_t dst, int lane) {
  #pragma unroll
  for (int J = 0; J < 16; J += 2)
    stmatrix_x4(dst + (J >> 3) * 16384 + ((((J & 7) + (lane >> 4)) ^ (lane & 7)) << 4),
                pack_bf16(o[4 * J + 0] * i0, o[4 * J + 1] * i0), pack_bf16(o[4 * J + 2] * i1, o[4 * J + 3] * i1),
                pack_bf16(o[4 * J + 4] * i0, o[4 * J + 5] * i0), pack_bf16(o[4 * J + 6] * i1, o[4 * J + 7] * i1));
}
__device__ __forceinline__ bool finish_l(float& l0, float& l1) {
  l0 += __shfl_xor_sync(0xffffffffu, l0, 1); l1 += __shfl_xor_sync(0xffffffffu, l1, 1);
  l0 += __shfl_xor_sync(0xffffffffu, l0, 2); l1 += __shfl_xor_sync(0xffffffffu, l1, 2);
  const bool redo = __any_sync(0xffffffffu, !(l0 <= AT_RAW_SUM && l1 <= AT_RAW_SUM && l0 >= AT_RAW_MIN && l1 >= AT_RAW_MIN));
  l0 = rcp_approx(l0); l1 = rcp_approx(l1);
  return redo;
}
__device__ __forceinline__ void stage_qregs(const uint32_t (&q)[32], uint32_t dst, int lane) {
  #pragma unroll
  for (int J = 0; J < 16; J += 2)
    stmatrix_x4(dst + (J >> 3) * 16384 + ((((J & 7) + (lane >> 4)) ^ (lane & 7)) << 4), q[2 * J], q[2 * J + 1], q[2 * J + 2], q[2 * J + 3]);
}
__device__ __forceinline__ void store_o(const CUtensorMap* tmO, uint32_t src, int head, int row) {
  tma_store_2d(tmO, src, head * T_DH, row);
  tma_store_2d(tmO, src + 16384, head * T_DH + 64, row);
  bulk_commit();
}
struct GemvSel { uint32_t lo0, hi0, lo1, hi1; };
__device__ __forceinline__ GemvSel gemv_sel(int lane) {
  const uint32_t lo = (lane & 8) ? 0x1044u : 0x4410u, hi = (lane & 8) ? 0x3244u : 0x4432u;
  GemvSel s; s.lo0 = (lane & 16) ? 0x4444u : lo; s.hi0 = (lane & 16) ? 0x4444u : hi; s.lo1 = (lane & 16) ? lo : 0x4444u; s.hi1 = (lane & 16) ? hi : 0x4444u;
  return s;
}
#define GEMV_B0(j, h, s) __byte_perm((j) < 2 ? (h).x : (h).y, 0u, ((j) & 1) ? (s).hi0 : (s).lo0)
#define GEMV_B1(j, h, s) __byte_perm((j) < 2 ? (h).x : (h).y, 0u, ((j) & 1) ? (s).hi1 : (s).lo1)
__device__ __forceinline__ float4 gemv_out(const float (&d)[4], int lane) {
  const bool tk = lane & 1;
  const float r0 = __shfl_xor_sync(0xffffffffu, tk ? d[0] : d[1], 1), r1 = __shfl_xor_sync(0xffffffffu, tk ? d[2] : d[3], 1);
  return tk ? make_float4(r0, d[1], r1, d[3]) : make_float4(d[0], r0, d[2], r1);
}
#define OG_NG 8
#define OG_GRP (64 / OG_NG)
constexpr int OG_ST = 5, OG_NKB = T_DQKV / 64, OG_MOE = T_F / 32;
constexpr int OG_POS = 7;
constexpr uint32_t OG_STAGE = 32768;
constexpr uint32_t OG_SWD = AT_SQ;
constexpr uint32_t OG_SCOL = AT_SBAR + 512;
constexpr uint32_t OG_SMISC = AT_SBAR + 2048;
constexpr uint32_t OG_XSLOT = ((OG_POS + OG_NKB) % OG_ST) * OG_STAGE;
constexpr uint32_t OG_OSLOT = ((OG_POS + OG_NKB + 1) % OG_ST) * OG_STAGE;
constexpr uint32_t OG_SH2 = ((OG_POS + OG_NKB + 2) % OG_ST) * OG_STAGE;
constexpr uint32_t OG_SRED = ((OG_POS + OG_NKB + 3) % OG_ST) * OG_STAGE;
constexpr uint32_t OG_SSTAT = OG_SRED + 16384;
constexpr uint32_t OG_SGU = OG_SRED + 8192;
constexpr uint32_t OG_SFIN = OG_SGU + 256;
#define OGM 2
#define OG_MT(b) ((((b) >> OGM) & 15) ^ (((b) & 64) ? 15 : 0))
#define OG_NT(b) (((b) & ((1 << OGM) - 1)) + (((b) >> (4 + OGM)) << OGM))
#define TAIL_SETUP \
  const uint32_t bar_full = sbase + AT_SBAR, bar_empty = bar_full + 40; \
  const uint32_t bar_wd = bar_full + 168, bar_col = bar_full + 176, bar_out = bar_full + 184, bar_end = bar_full + 192; \
  const uint32_t bar_key = bar_full + 200, bar_h2 = bar_full + 208, bar_sel = bar_full + 216; \
  const int mt = OG_MT(bx), nt = OG_NT(bx); \
  const int m0 = mt * 128, n0 = nt * 128; \
  const bool has_moe = (int)bx < OG_MOE; \
  (void)bar_empty; (void)bar_wd; (void)bar_col; (void)bar_out; (void)bar_end; (void)bar_key; (void)bar_h2; (void)bar_sel; (void)m0; (void)n0; (void)has_moe;

__device__ __forceinline__ void tail_producer(Scratch* hm, uint32_t bx, uint32_t sbase, uint32_t ph, uint32_t obpar, uint64_t pol, const CUtensorMap* tmA, const CUtensorMap* tmB,
                                              const CUtensorMap* tmX, const bf16* __restrict__ w_down) {
  TAIL_SETUP
  const uint32_t b_ob = bar_full + 96, b_acq = bar_full + 256;
  uint32_t stage = OG_ST, wdd = sbase + OG_SWD;
  int wdk = has_moe ? WD_0 : 99;
  const uint8_t* wdp = (const uint8_t*)w_down + (size_t)bx * 65536;
  if (has_moe) mbar_expect_tx(bar_wd, 65536);
  mbar_expect_tx(bar_col, 1536 + 16);
  #pragma unroll 1
  for (int kb = 0; kb <= OG_NKB; kb++) {
    const uint32_t fb = bar_full + (kb ? 8 * stage : 248), sa = sbase + stage * OG_STAGE, sb = sa + 16384;
    mbar_wait(bar_empty + 8 * stage, kb ? ph : obpar);
    mbar_expect_tx(fb, OG_STAGE);
    if (kb < OG_NKB) {
      tma_load_2d_hint(sb, tmB, n0, kb * 64, fb, pol);
      tma_load_2d_hint(sb + 8192, tmB, n0 + 64, kb * 64, fb, pol);
      if ((kb & 31) == 0) { mbar_wait(b_acq + (kb >> 2), 0); fence_proxy_async_global(); }
      tma_load_2d_hint(sa, tmA, kb * 64, m0, fb, pol);
    } else {
      tma_load_2d_hint(sa, tmX, n0, m0, fb, pol);
      tma_load_2d_hint(sb, tmX, n0 + 64, m0, fb, pol);
    }
    if (kb == 32) {
      bulk_load_hint(sbase + OG_SCOL, g_col + nt * 1536, 1536, bar_col, pol);
      bulk_load_hint(sbase + OG_SMISC, g_scal, 16, bar_col, pol);
    }
    if (kb == wdk && kb < WD_0 + 8 * WD_S) {
      if (kb == WD_0) mbar_wait(b_ob, obpar);
      bulk_load_hint(wdd, wdp, 8192, bar_wd, pol);
      wdp += 8192; wdd += 8224; wdk += WD_S;
    }
    if (++stage == OG_ST) { stage = 0; ph ^= 1; }
    if (kb == 0) stage = (OG_POS + 1) % OG_ST;
  }
}

__device__ __forceinline__ uint32_t out2(uint32_t x1, uint32_t mb2, uint32_t ih, uint32_t il, uint32_t c1, uint32_t sb, uint32_t gb) {
  const uint32_t d = bsub2(x1, mb2);
  return bfma2(gb, bfma2(bfma2(d, ih, bmul2(d, il)), c1, sb), x1);
}
__device__ __forceinline__ void tail_exchange(Scratch* hm, uint32_t bx, uint32_t sbase, int wid, uint32_t tx, const CUtensorMap* tmOut, bf16* __restrict__ out) {
    TAIL_SETUP
    mbar_wait(bar_end, 0);
    const int lane = tx & 31;
    TL_MARK2(22, lane == 0);
    if (tx == 96) PF(5);
    if (wid == 0) {
      uint32_t k1 = 0u, k2 = 0u;
      #pragma unroll 1
      for (unsigned int spin = 0; spin < (1u << 22); spin++) {
        if (k1 == 0u) asm volatile("ld.relaxed.gpu.global.u32 %0, [%1];" : "=r"(k1) : "l"(g_key + lane) : "memory");
        if (__all_sync(0xffffffffu, k1 != 0u)) break;
      }
      TS(6, lane == 0);
      warp_top2(k1, k2);
      if (lane == 0) {
        const uint32_t r1 = 0xffffu - (k1 & 0xffffu), r2 = 0xffffu - (k2 & 0xffffu);
        sts_u32x4(sbase + OG_SMISC + 64, k1, k2, (r1 >> 7) * 2, (r2 >> 7) * 2 + ((r1 >> 7) == (r2 >> 7)));
        mbar_arrive(bar_sel);
      }
    } else if (wid < 3) {
      const uint32_t ch = lane & 15, ca = sbase + OG_SCOL + 768 + (ch >> 2) * 64 + (ch & 3) * 4;
      const uint4 c1 = make_uint4(lds_u32(ca), lds_u32(ca + 16), lds_u32(ca + 32), lds_u32(ca + 48)), sh = make_uint4(lds_u32(ca + 256), lds_u32(ca + 272), lds_u32(ca + 288), lds_u32(ca + 304));
      float* dst = reinterpret_cast<float*>(g_cand + (mt * 2 + (lane >> 4)) * 256 + nt * 16 + ch);
      mbar_wait(bar_key, 0);
      const uint4 kk = lds_u32x4(sbase + OG_SSTAT + 1024 + lane * 16);
      uint32_t k1 = max(kk.x, kk.y), k2 = min(kk.x, kk.y);
      k2 = max(max(k2, min(kk.z, kk.w)), min(k1, max(kk.z, kk.w))); k1 = max(k1, max(kk.z, kk.w));
      warp_top2(k1, k2);
      if (wid == 1) {
        if (lane == 0 && nt == (mt & 7)) st_relaxed2(g_key + mt * 2, k1, k2);
        TS(4, lane == 0);
      } else {
        const uint32_t r = (~((lane & 16) ? k2 : k1)) & 127u;
        const uint2 st = lds_u32x2(sbase + OG_SSTAT + r * 8);
        const uint4 xc = lds_u32x4(sbase + OG_XSLOT + (ch >> 3) * 16384 + r * 128 + (((ch ^ r) & 7) << 4));
        const float inr = __uint_as_float(st.y);
        const float h0 = __uint_as_float(ln_mod2(xc.x, st.x, inr, c1.x, sh.x)), h1 = __uint_as_float(ln_mod2(xc.y, st.x, inr, c1.y, sh.y));
        const float h2 = __uint_as_float(ln_mod2(xc.z, st.x, inr, c1.z, sh.z)), h3 = __uint_as_float(ln_mod2(xc.w, st.x, inr, c1.w, sh.w));
        st_tagged4(dst + 512, h0, h1, h2, h3);
        st_tagged4(dst, __uint_as_float(xc.x), __uint_as_float(xc.y), __uint_as_float(xc.z), __uint_as_float(xc.w));
      }
    }
    mbar_wait(bar_sel, 0);
    mbar_wait(bar_out, 0);
    {
      const int sel0 = 0xffff - (lds_u32(sbase + OG_SMISC + 64) & 0xffffu), sel1 = 0xffff - (lds_u32(sbase + OG_SMISC + 68) & 0xffffu);
      if ((sel0 >> 7) == mt || (sel1 >> 7) == mt) {
        #pragma unroll 2
        for (int i = 0; i < 16; i++) {
          const int r = i * 8 + (tx >> 4), ch = tx & 15;
          if (m0 + r != sel0 && m0 + r != sel1)
            *reinterpret_cast<uint4*>(out + (size_t)(m0 + r) * T_D + n0 + ch * 8) =
                lds_u32x4(sbase + OG_OSLOT + (ch >> 3) * 16384 + r * 128 + (((ch & 7) ^ (r & 7)) << 4));
        }
      } else if (tx == 96) {
        tma_store_2d(tmOut, sbase + OG_OSLOT, n0, m0);
        tma_store_2d(tmOut, sbase + OG_OSLOT + 16384, n0 + 64, m0);
        bulk_commit();
      }
      __syncwarp();
    }
    {
      const int tk = bx >> 6, c0 = (bx & 63) * 16;
      const uint32_t gb2 = *reinterpret_cast<const uint32_t*>(g_col + (c0 >> 7) * 1536 + 512 + 768 + col_pos((c0 & 127) + (tx & 14)) * 2);
      const float* src = g_ypart + (size_t)((tx >> 2) * 2 + tk) * T_D + c0 + (tx & 3) * 4;
      const bool four = tx < (OG_MOE - 96) * 4;
      mbar_wait(bar_h2, 0);
      float fx = 0.f, fh = 0.f, rs = 0.f;
      bf16* op = out;
      if (wid == 1) {
        const uint32_t key = lds_u32(sbase + OG_SMISC + 64 + tk * 4);
        const uint32_t* xp = reinterpret_cast<const uint32_t*>(g_cand + lds_u32(sbase + OG_SMISC + 72 + tk * 4) * 256) + ((c0 + (tx & 14)) >> 1);
        uint32_t x2 = 0u;
        #pragma unroll 1
        for (unsigned int spin = 0; spin < (1u << 20); spin++) { asm volatile("ld.relaxed.gpu.global.u32 %0, [%1];" : "=r"(x2) : "l"(xp) : "memory"); if (__all_sync(0xffffffffu, x2 != 0u)) break; }
        const uint32_t h2p = lds_u32(sbase + OG_SH2 + tk * 2048 + (c0 + (tx & 14)) * 2);
        fx = (lane & 1) ? bfhi(x2) : bflo(x2); fh = (lane & 1) ? bfhi(h2p) : bflo(h2p);
        rs = rbf(sigmoid_f(bfhi((key & 0x80000000u) ? key ^ 0x80000000u : ~key)));
        op += (size_t)(0xffffu - (key & 0xffffu)) * T_D + c0 + (lane & 15);
      }
      if (bx == 0 && tx < 68) g_hcnt[32 * (tx >> 2) + (tx & 3)] = 0u;
      if (tx < 64) hm->modu[bx * 64 + tx] = 0.f;
      else if (tx < 96) hm->stat[bx * 32 + tx - 64] = make_float2(0.f, 0.f);
      else if (tx < 112) hm->mod[bx * 16 + tx - 96] = 0.f;
      else if (tx < 114 && bx < 66) hm->gkey[bx * 2 + tx - 112] = 0u;
      if (tx == 0) hint_wait(CNT_Y, (uint32_t)OG_MOE);
      named_bar_sync(10, 128);
      TS(11, lane == 0);
      float4 p0, p1, p2, p3;
      #pragma unroll 1
      for (unsigned int spin = 0; spin < (1u << 20); spin++) {
        p0 = ld_tagged4(src); p1 = ld_tagged4(src + 64 * T_D); p2 = ld_tagged4(src + 128 * T_D); p3 = ld_tagged4(four ? src + 192 * T_D : src);
        if (__all_sync(0xffffffffu, tagged4(p0) & tagged4(p1) & tagged4(p2) & tagged4(p3))) break;
      }
      if (four) { p2.x += p3.x; p2.y += p3.y; p2.z += p3.z; p2.w += p3.w; }
      p0.x = (p0.x + p1.x) + p2.x; p0.y = (p0.y + p1.y) + p2.y; p0.z = (p0.z + p1.z) + p2.z; p0.w = (p0.w + p1.w) + p2.w;
      #pragma unroll
      for (int o = 4; o <= 16; o <<= 1) {
        p0.x += __shfl_xor_sync(0xffffffffu, p0.x, o); p0.y += __shfl_xor_sync(0xffffffffu, p0.y, o);
        p0.z += __shfl_xor_sync(0xffffffffu, p0.z, o); p0.w += __shfl_xor_sync(0xffffffffu, p0.w, o);
      }
      if (lane < 4) sts_f32x4(sbase + OG_SFIN + (tx >> 5) * 64 + lane * 16, p0.x, p0.y, p0.z, p0.w);
      named_bar_sync(10, 128);
      TS(12, lane == 0);
      if (wid == 1 && lane < 16) {
        const uint32_t ya = sbase + OG_SFIN + lane * 4;
        const float y = rbf(rbf((lds_f32(ya) + lds_f32(ya + 64)) + (lds_f32(ya + 128) + lds_f32(ya + 192))) * rs);
        *op = __float2bfloat16_rn(fx + rbf(((lane & 1) ? bfhi(gb2) : bflo(gb2)) * rbf(fh + y)));
      }
      if (tx == 96) bulk_wait_read<0>();
    }
    TL_END(4, tx == 0);
    PS(6, tx == 32);
    TS(13, tx == 32);
}

__device__ __forceinline__ void tail_consumer(Scratch* hm, uint32_t bx, uint32_t sbase, int tid, int w8, const bf16* __restrict__ w_gate, const bf16* __restrict__ w_up) {
    TAIL_SETUP
    const int warp = w8 & 3, lane = tid & 31, cwg = w8 >> 2, t2 = cwg * 128 + tid;
    const uint32_t dbase = (sbase & 0x3FFFFu) >> 4;
    const uint32_t a_base = dbase + ((cwg * 8192) >> 4) + (1u << 16);
    const uint32_t b_base = dbase + (16384 >> 4) + (512u << 16);
    TL_MARK2(25, threadIdx.x == 128);
    const uint64_t pol = policy_evict_first();
    const bf16* pw = ((lane & 16) ? w_up : w_gate) + (size_t)(w8 * 128 + (lane & 3) * 4) * T_F + (has_moe ? bx : 0) * 32 + ((lane >> 2) & 3) * 8;
    uint4 wv[32];
    float acc[64];
    {
      uint32_t stage = (OG_POS + 1) % OG_ST, phase = ((OG_POS + 1) / OG_ST) & 1, prev = 12;
      #pragma unroll
      for (int i = 0; i < 64; i++) acc[i] = 0.f;
      mbar_wait(bar_full + 248, 0);
      wgmma_fence();
      wgmma_m64n128k16_ss_tb<0 + 5 * 2048, 0 + 5 * 2048>(acc, a_base, b_base, 0);
      wgmma_m64n128k16_ss_tb<2 + 5 * 2048, 128 + 5 * 2048>(acc, a_base, b_base, 1);
      wgmma_m64n128k16_ss_tb<4 + 5 * 2048, 256 + 5 * 2048>(acc, a_base, b_base, 1);
      wgmma_m64n128k16_ss_tb<6 + 5 * 2048, 384 + 5 * 2048>(acc, a_base, b_base, 1);
      wgmma_commit();
      #pragma unroll
      for (int g = OG_PRE ? -1 : 0; g < OG_NG; g++) {
        #pragma unroll
        for (int j = 0; j < 4; j++) if (g >= 0) wv[4 * g + j] = ldg_stream_v4(pw + (size_t)(16 * g + j) * T_F, pol);
        #pragma unroll 1
        for (int kb = g < 0 ? 1 : OG_PRE + g * OG_LEN; kb < (g == OG_NG - 1 ? OG_NKB : OG_PRE + (g + 1) * OG_LEN); kb++) {
          mbar_wait(bar_full + 8 * stage, phase);
          const uint32_t a_lo = a_base + stage * (OG_STAGE >> 4), b_lo = b_base + stage * (OG_STAGE >> 4);
          wgmma_fence();
          wgmma_m64n128k16_ss_tb<0, 0>(acc, a_lo, b_lo, 1);
          wgmma_m64n128k16_ss_tb<2, 128>(acc, a_lo, b_lo, 1);
          wgmma_m64n128k16_ss_tb<4, 256>(acc, a_lo, b_lo, 1);
          wgmma_m64n128k16_ss_tb<6, 384>(acc, a_lo, b_lo, 1);
          wgmma_commit();
          wgmma_wait<1>();
          if (tid == 0) mbar_arrive(bar_empty + 8 * prev);
          prev = stage;
          if (++stage == OG_ST) { stage = 0; phase ^= 1; }
        }
      }
    }
    const uint32_t frag = (64 * cwg + 16 * warp + (lane & 15)) * 128 + (((lane >> 4) ^ (lane & 7)) << 4);
    const uint32_t tcol = sbase + OG_SCOL + (lane & 3) * 16, g = lane >> 2;
    float* sdst = reinterpret_cast<float*>(g_part1 + ((mt * 8 + w8) * 8 + nt) * 16 + g + (lane & 1) * 8);
    uint32_t xr[32];
    uint4 ga[4], cw[4];
    auto ld_quarter = [&](int q, uint32_t dep) {
      #pragma unroll
      for (int i = 2 * q; i < 2 * q + 2; i++) ldmatrix_x4(sbase + OG_XSLOT + (i >> 2) * 16384 + (frag ^ ((i & 3) * 32)) + dep, xr[4 * i], xr[4 * i + 1], xr[4 * i + 2], xr[4 * i + 3]);
      ga[q] = lds_u32x4(tcol + 512 + q * 64 + dep);
      cw[q] = lds_u32x4((g ? tcol + (lane & 8) * 32 + q * 64 : sbase + OG_SMISC + 32) + dep);
    };
    mbar_wait(bar_col, 0);
    mbar_wait(bar_full + 8 * ((OG_POS + OG_NKB) % OG_ST), ((OG_POS + OG_NKB) / OG_ST) & 1);
    ld_quarter(0, 0);
    wgmma_wait<0>();
    fence_regs(acc);
    if (tid == 0) mbar_arrive(bar_end);
    TL_MARK2(9, lane == 0);
    TS(0, lane == 0);
    PS(5, threadIdx.x == 256);
    {
      float dl[4] = {0.f, 0.f, 0.f, 0.f}, da[4] = {0.f, 0.f, 0.f, 0.f}, db[4] = {0.f, 0.f, 0.f, 0.f};
      #pragma unroll
      for (int q = 0; q < 4; q++) {
        uint32_t pk[8];
        #pragma unroll
        for (int i = 0; i < 8; i++) pk[i] = pack_bf16(acc[16 * q + 2 * i], acc[16 * q + 2 * i + 1]);
        if (q < 3) ld_quarter(q + 1, 0u);
        #pragma unroll
        for (int i = 2 * q; i < 2 * q + 2; i++) {
          #pragma unroll
          for (int k = 0; k < 4; k++) xr[4 * i + k] = badd2(xr[4 * i + k], bmul2((i & 1) ? (k < 2 ? ga[q].z : ga[q].w) : (k < 2 ? ga[q].x : ga[q].y), pk[4 * (i & 1) + k]));
          mma_bf16(dl, xr[4 * i], xr[4 * i + 1], xr[4 * i + 2], xr[4 * i + 3], (i & 1) ? cw[q].z : cw[q].x, (i & 1) ? cw[q].w : cw[q].y);
          mma_bf16(da, xr[4 * i], xr[4 * i + 1], xr[4 * i + 2], xr[4 * i + 3], xr[4 * i], xr[4 * i + 2]);
          mma_bf16(db, xr[4 * i], xr[4 * i + 1], xr[4 * i + 2], xr[4 * i + 3], xr[4 * i + 1], xr[4 * i + 3]);
        }
      }
      {
        const int dsrc = (lane & ~3) + (g >> 1);
        const float qa = __shfl_sync(0xffffffffu, (g & 1) ? da[1] : da[0], dsrc), qb = __shfl_sync(0xffffffffu, (g & 1) ? db[3] : db[2], dsrc);
        const float e0 = __shfl_xor_sync(0xffffffffu, (lane & 1) ? dl[0] : dl[2], 1), e1 = __shfl_xor_sync(0xffffffffu, dl[3], 1);
        const bool hi = lane & 1;
        if ((lane & 3) < 2) st_tagged4(sdst, hi ? e0 : dl[0], hi ? qb : qa, hi ? e1 + dl[2] : dl[1] + e0, 1.0f);
      }
    }
    TL_MARK2(10, lane == 0);
    TS(1, lane == 0);
    uint4 tc[4], ts[4], tg[4];
    #pragma unroll
    for (int i = 0; i < 8; i++) stmatrix_x4(sbase + OG_XSLOT + (i >> 2) * 16384 + (frag ^ ((i & 3) * 32)), xr[4 * i], xr[4 * i + 1], xr[4 * i + 2], xr[4 * i + 3]);
    #pragma unroll
    for (int i = 0; i < 8; i++) ldmatrix_x4(sbase + OG_XSLOT + (i >> 2) * 16384 + (frag ^ ((i & 3) * 32)), xr[4 * i], xr[4 * i + 1], xr[4 * i + 2], xr[4 * i + 3]);
    #pragma unroll
    for (int i = 0; i < 2; i++) { tc[i] = lds_u32x4(tcol + 768 + i * 64); ts[i] = lds_u32x4(tcol + 1024 + i * 64); tg[i] = lds_u32x4(tcol + 1280 + i * 64); }
    {
      const float* src = reinterpret_cast<const float*>(g_part1 + ((mt * 8 + w8) * 8 + (lane & 1) * 4) * 16 + (lane >> 1));
      float4 v, v1, v2, v3;
      #pragma unroll 1
      for (unsigned int spin = 0; spin < (1u << 22); spin++) {
        v = ld_tagged4(src); v1 = ld_tagged4(src + 64); v2 = ld_tagged4(src + 128); v3 = ld_tagged4(src + 192);
        if (tagged4(v) & tagged4(v1) & tagged4(v2) & tagged4(v3)) break;
        __nanosleep(100);
      }
      __syncwarp();
      TL_MARK2(26, lane == 0);
    TS(2, lane == 0);
      v.x = (v.x + v1.x) + (v2.x + v3.x); v.y = (v.y + v1.y) + (v2.y + v3.y); v.z = (v.z + v1.z) + (v2.z + v3.z);
      v.x += __shfl_xor_sync(0xffffffffu, v.x, 1); v.y += __shfl_xor_sync(0xffffffffu, v.y, 1); v.z += __shfl_xor_sync(0xffffffffu, v.z, 1);
      const float mean = v.x * (1.0f / T_D);
      const float var = fmaxf(fmaf(-mean, mean, v.y * (1.0f / T_D)), 0.f);
      const uint32_t mb2 = pack_bf16(mean, mean);
      const float inv = rcp_approx(rbf(sqrt_approx(rbf(rbf(var) + 1e-05f))));
      {
        const uint4 sc = lds_u32x4(sbase + OG_SMISC);
        const uint32_t key = rank_key(rbf(fmaf(fmaf(-bflo(mb2), __uint_as_float(sc.x) + __uint_as_float(sc.y), v.z), inv, __uint_as_float(sc.z) + __uint_as_float(sc.w))), m0 + 16 * w8 + (lane >> 1));
        mbar_wait(bar_end, 0);
        if (lane & 1) sts_u32(sbase + OG_SSTAT + 1024 + (16 * w8 + (lane >> 1)) * 4, key);
        else sts_u32x2(sbase + OG_SSTAT + (16 * w8 + (lane >> 1)) * 8, mb2, __float_as_uint(inv));
        __syncwarp();
        TS(3, lane == 0);
        if (lane == 0) mbar_arrive(bar_key);
      }
      const uint32_t ih = pack_bf16(inv, inv), il = pack_bf16(inv - bflo(ih), inv - bflo(ih));
      const uint32_t mba = __shfl_sync(0xffffffffu, mb2, 2 * (lane >> 2)), mbb = __shfl_sync(0xffffffffu, mb2, 2 * (lane >> 2) + 16);
      const uint32_t iha = __shfl_sync(0xffffffffu, ih, 2 * (lane >> 2)), ihb = __shfl_sync(0xffffffffu, ih, 2 * (lane >> 2) + 16);
      const uint32_t ila = __shfl_sync(0xffffffffu, il, 2 * (lane >> 2)), ilb = __shfl_sync(0xffffffffu, il, 2 * (lane >> 2) + 16);
      #pragma unroll
      for (int i = 2; i < 4; i++) { tc[i] = lds_u32x4(tcol + 768 + i * 64); ts[i] = lds_u32x4(tcol + 1024 + i * 64); tg[i] = lds_u32x4(tcol + 1280 + i * 64); }
      #pragma unroll
      for (int i = 0; i < 8; i++) {
        const uint4 &c = tc[i >> 1], &s = ts[i >> 1], &b = tg[i >> 1];
        const bool u = i & 1;
        stmatrix_x4(sbase + OG_OSLOT + (i >> 2) * 16384 + (frag ^ ((i & 3) * 32)),
                    out2(xr[4 * i], mba, iha, ila, u ? c.z : c.x, u ? s.z : s.x, u ? b.z : b.x), out2(xr[4 * i + 1], mbb, ihb, ilb, u ? c.z : c.x, u ? s.z : s.x, u ? b.z : b.x),
                    out2(xr[4 * i + 2], mba, iha, ila, u ? c.w : c.y, u ? s.w : s.y, u ? b.w : b.y), out2(xr[4 * i + 3], mbb, ihb, ilb, u ? c.w : c.y, u ? s.w : s.y, u ? b.w : b.y));
      }
      fence_proxy_async();
      __syncwarp();
      if (lane == 0) mbar_arrive(bar_out);
      TL_MARK2(24, lane == 0);
    TS(5, lane == 0);
    }
    uint4 wd[16];
    {
      mbar_wait(bar_sel, 0);
      TL_MARK2(12, lane == 0);
    TS(7, lane == 0);
      const float* src = reinterpret_cast<const float*>(g_cand + lds_u32(sbase + OG_SMISC + 72 + cwg * 4) * 256 + 128 + tid);
      float4 hf = ld_tagged4(src);
      if (has_moe) mbar_wait(bar_wd, 0);
      #pragma unroll
      for (int i = 0; i < 16; i++) wd[i] = lds_u32x4(sbase + OG_SWD + (((i >> 2) & 1) * 4 + (lane & 3)) * 8224 + (i & 3) * 2048 + w8 * 256 + (i >> 3) * 128 + (lane >> 2) * 16);
      #pragma unroll 1
      for (unsigned int spin = 0; spin < (1u << 20) && !tagged4(hf); spin++) hf = ld_tagged4(src);
      const uint4 hv = make_uint4(__float_as_uint(hf.x), __float_as_uint(hf.y), __float_as_uint(hf.z), __float_as_uint(hf.w));
      sts_u32x4(sbase + OG_SH2 + t2 * 16, hv.x, hv.y, hv.z, hv.w);
    }
    named_bar_sync(9, 256);
    if (t2 == 0) mbar_arrive(bar_h2);
    TL_MARK2(13, lane == 0);
    TS(8, lane == 0);
    if (has_moe) {
      const GemvSel sel = gemv_sel(lane);
      {
        float d[4][4];
        #pragma unroll
        for (int c = 0; c < 4; c++) { d[c][0] = 0.f; d[c][1] = 0.f; d[c][2] = 0.f; d[c][3] = 0.f; }
        #pragma unroll
        for (int st = 0; st < 8; st++) {
          const uint2 hb = lds_u32x2(sbase + OG_SH2 + ((lane >> 2) & 1) * 2048 + (w8 * 128 + st * 16 + (lane & 3) * 4) * 2);
          #pragma unroll
          for (int j = 0; j < 4; j++) mma_bf16(d[j], wv[4 * st + j].x, wv[4 * st + j].y, wv[4 * st + j].z, wv[4 * st + j].w, GEMV_B0(j, hb, sel), GEMV_B1(j, hb, sel));
        }
        #pragma unroll
        for (int e = 0; e < 4; e++) d[0][e] = (d[0][e] + d[1][e]) + (d[2][e] + d[3][e]);
        const float4 r = gemv_out(d[0], lane);
        sts_f32x4(sbase + OG_SRED + w8 * 512 + (((lane >> 4) * 2 + (lane & 1)) * 32 + ((lane >> 2) & 3) * 8 + (lane & 2) * 2) * 4, r.x, r.y, r.z, r.w);
      }
      named_bar_sync(9, 256);
      if (t2 < 64) {
        float gp[8], up[8];
        #pragma unroll
        for (int w = 0; w < 8; w++) { gp[w] = lds_f32(sbase + OG_SRED + w * 512 + t2 * 4); up[w] = lds_f32(sbase + OG_SRED + w * 512 + 256 + t2 * 4); }
        const float gs = ((gp[0] + gp[1]) + (gp[2] + gp[3])) + ((gp[4] + gp[5]) + (gp[6] + gp[7]));
        const float us = ((up[0] + up[1]) + (up[2] + up[3])) + ((up[4] + up[5]) + (up[6] + up[7]));
        asm volatile("st.shared.u16 [%0], %1;" :: "r"(sbase + OG_SGU + t2 * 2), "h"((uint16_t)pack_bf16(silu_bf(rbf(gs)) * rbf(us), 0.f)) : "memory");
      }
      named_bar_sync(9, 256);
      TS(9, lane == 0);
      float d[4][4];
      #pragma unroll
      for (int c = 0; c < 4; c++) { d[c][0] = 0.f; d[c][1] = 0.f; d[c][2] = 0.f; d[c][3] = 0.f; }
      #pragma unroll
      for (int st = 0; st < 2; st++) {
        const uint2 g = lds_u32x2(sbase + OG_SGU + ((lane >> 2) & 1) * 64 + st * 32 + (lane & 3) * 8);
        #pragma unroll
        for (int j = 0; j < 4; j++) {
          const uint32_t b0 = GEMV_B0(j, g, sel), b1 = GEMV_B1(j, g, sel);
          mma_bf16(d[j & 1], wd[4 * st + j].x, wd[4 * st + j].y, wd[4 * st + j].z, wd[4 * st + j].w, b0, b1);
          mma_bf16(d[2 + (j & 1)], wd[8 + 4 * st + j].x, wd[8 + 4 * st + j].y, wd[8 + 4 * st + j].z, wd[8 + 4 * st + j].w, b0, b1);
        }
      }
      #pragma unroll
      for (int e = 0; e < 4; e++) { d[0][e] += d[1][e]; d[2][e] += d[3][e]; }
      const float4 y0 = gemv_out(d[0], lane), y1 = gemv_out(d[2], lane);
      float* yp = g_ypart + (size_t)(bx * 2 + (lane & 1)) * T_D + w8 * 128 + (lane >> 2) * 8 + (lane & 2) * 2;
      st_tagged4(yp, y0.x, y0.y, y0.z, y0.w);
      st_tagged4(yp + 64, y1.x, y1.y, y1.z, y1.w);
      named_bar_sync(9, 256);
      if (t2 == 0) hint_arrive(CNT_Y);
    }
    TS(10, lane == 0);
    TL_CLK(4, 1, threadIdx.x == 128);
}

__device__ __forceinline__ void store_warp(Scratch* hm, uint32_t sbase, const CUtensorMap* tmO, int item0, int n_items) {
  if (elect_one()) {
    const uint32_t bars = sbase + AT_SBAR, b_q0 = bars + 80, b_ob = bars + 96, b_ordy = bars + 104, b_acq = bars + 256;
    mbar_wait(bars + 232, 0);
    const uint32_t bx = lds_u32(bars + 240);
    const unsigned int* cnt = &g_hcnt[32 * (1 + OG_MT(bx)) + 2];
    #pragma unroll 1
    for (int q = 0; q < 4 * n_items; q++) {
      const int item = item0 + (q >> 2) * 128, h = (q >> 1) & 1, w = q & 1;
      const bool last = (q >> 2) == n_items - 1;
      mbar_wait(b_ordy + 8 * (q & 3), q >> 2);
      if (q == 4 && item < 192) spin_until(&g_hcnt[32 * (1 + (item & 15)) + 1], (item & 15) < 12 ? 8u : 7u);
      store_o(tmO, (h ? (last ? sbase + AT_SQ + 32768 : sbase + 2 * 32768) : sbase + AT_SQ) + w * 8192, (item >> 4) * 2 + h, (item & 15) * 128 + w * 64);
      if (w) {
        PF(1 + (q >> 1));
        bulk_wait_read<0>();
        mbar_arrive(h ? b_ob : b_q0);
        bulk_wait<0>();
        fence_proxy_async_global();
        red_release_add(&g_hcnt[32 * (1 + (item & 15)) + 2 + (item >> 7)], 1u);
        if (bx < 128 && q == (n_items == 2 ? 5 : 3)) { spin_until(cnt, 16u); mbar_arrive(b_acq); }
      }
    }
    if (bx < 128) { spin_until(&g_hcnt[0], 8u); spin_until(cnt + 1, 16u); mbar_arrive(b_acq + 8); }
  }
}

#define TUNE_PARAM
__device__ __forceinline__ int h_first(int item, int c) { const int j = (item >> 4) + 3 * c; return j >= 7 ? j - 7 : j; }
__global__ void __launch_bounds__(384, 1)
fused_kernel(const bf16* __restrict__ x, const bf16* __restrict__ cvec, const bf16* __restrict__ w_mod, Scratch* hm, uint32_t zero, TUNE_PARAM
            const uint8_t* __restrict__ pf_wo, const bf16* __restrict__ kc, const bf16* __restrict__ vc, const bf16* __restrict__ w_r,
            const bf16* __restrict__ w_gate, const bf16* __restrict__ w_up, const bf16* __restrict__ w_down, bf16* __restrict__ out,
            const __grid_constant__ CUtensorMap tmM, const __grid_constant__ CUtensorMap tmW, const __grid_constant__ CUtensorMap tmK,
            const __grid_constant__ CUtensorMap tmV, const __grid_constant__ CUtensorMap tmO, const __grid_constant__ CUtensorMap tmOl, const __grid_constant__ CUtensorMap tmWo,
            const __grid_constant__ CUtensorMap tmX, const __grid_constant__ CUtensorMap tmOut)
{
  extern __shared__ __align__(1024) uint8_t smem_raw[];
  const uint32_t sbase = smem_u32(smem_raw);
  const uint32_t bars = sbase + AT_SBAR;
  const uint32_t b_full = bars, b_empty = bars + 40;
  const uint32_t b_q0 = bars + 80, b_q1 = bars + 88;
  const uint32_t b_ob = bars + 96;
  const uint32_t b_ordy = bars + 104;
  const uint32_t b_pin = bars + 136;
  const uint32_t b_a0 = bars + 144;
  const uint32_t b_x = bars + 160;
  const uint32_t b_w = bars + 152, b_go = bars + 224;
  const uint32_t b_bx = bars + 232, s_bx = bars + 240;
  const uint32_t b_hs = bars + 464;
  const uint32_t b_tab = bars + 272;
  const int wid = __shfl_sync(0xffffffffu, threadIdx.x >> 5, 0), wg = wid >> 2;
  const bool single = blockIdx.x >= AT_NFULL;
  const int item0 = __shfl_sync(0xffffffffu, blockIdx.x < 128 ? (int)blockIdx.x : (int)blockIdx.x + 124, 0), n_items = __shfl_sync(0xffffffffu, single ? 1 : 2, 0);
  const uint32_t t0 = clock_lo();
  TL_START(3);
  HS(0);
  if (threadIdx.x == 0) {
    if (sbase & 1023u) __trap();
    for (int i = 0; i < 5; i++) { mbar_init(b_full + 8 * i, 1); mbar_init(b_empty + 8 * i, 2); mbar_init(b_hs + 8 * i, i < 2 && !single ? 4 : 1); }
    sts_u32(bars + 504, 5u);
    mbar_init(b_q0, 1); mbar_init(b_q1, 8); mbar_init(b_ob, 1);
    for (int i = 0; i < 4; i++) mbar_init(b_ordy + 8 * i, 4);
    mbar_init(b_pin, 1); mbar_init(b_a0, 8); mbar_init(b_x, 1); mbar_init(b_w, 1); mbar_init(b_go, 1); mbar_init(b_bx, 1);
    for (int i = 0; i < 8; i++) mbar_init(b_tab + 8 * i, i < 2 ? 1 : 2);
    mbar_init(bars + 168, 1); mbar_init(bars + 176, 1); mbar_init(bars + 184, 8); mbar_init(bars + 192, 2);
    mbar_init(bars + 200, 8); mbar_init(bars + 208, 1); mbar_init(bars + 216, 1); mbar_init(bars + 248, 1); mbar_init(bars + 256, 1); mbar_init(bars + 264, 1);
    sts_u32x4(sbase + OG_SMISC + 32, 0x3F803F80u, 0x3F803F80u, 0x3F803F80u, 0x3F803F80u);
    fence_mbar_init();
    if (blockIdx.x < 128) {
      HS(1);
      wait_clock(t0, XDLY);
      mbar_expect_tx(b_x, 32768);
      bulk_load_hint(sbase + 3 * 32768, x + (size_t)blockIdx.x * 16 * T_D, 32768, b_x, pol_normal());
    }
    mbar_arrive(b_tab); mbar_arrive(b_tab + 8);
  }

  if (wg == 0) {
    reg_dealloc<AT_PREG>();
    if (wid == 0) { __syncwarp(); named_bar_arrive(6, 128); named_bar_arrive(11, 160); named_bar_arrive(12, 160); }
    if (wid >= 2) {
      named_bar_sync(6, 128);
      wait_clock(t0, GDLY2);
      gather_table(hm, sbase + 4 * 32768, b_tab, wid & 1, threadIdx.x & 31);
      if (threadIdx.x == 64) PF(0);
      if (threadIdx.x == 96 && !single) { sleep_until(t0, 40000); spin_until(&g_hcnt[32 * (1 + (item0 & 15))], 7u); mbar_arrive(b_w); }
    } else if (wid == 1) {
      named_bar_sync(6, 128);
      if (item0 < 112) {
        const int lane = threadIdx.x & 31;
        #pragma unroll 1
        for (int j0 = h_first(item0, 0), j1 = h_first(item0, 1); j0 < 16 || j1 < 16;) {
          const int c = j1 < j0, j = c ? j1 : j0;
          bf16* hg = hm->o + (size_t)((item0 & 15) * 128 + c * 64 + (lane >> 3)) * O_LD + O_H + (lane & 7) * 8 + j * 64;
          uint32_t src = sbase + AT_SQ - 16384 + c * 8192 + (lane >> 3) * 128 + (((lane ^ (lane >> 3)) & 7) << 4);
          mbar_wait(b_hs + 8 * c, j >= 7 && j < 14);
          #pragma unroll 1
          for (int i = 0; i < 4; i++, hg += 16 * O_LD, src += 2048) {
            uint4 v[4];
            #pragma unroll
            for (int k = 0; k < 4; k++) v[k] = lds_u32x4((src ^ ((k & 1) * 64)) + k * 512);
            #pragma unroll
            for (int k = 0; k < 4; k++) *reinterpret_cast<uint4*>(hg + k * 4 * O_LD) = v[k];
          }
          __syncwarp();
          if (lane == 0) mbar_arrive(b_hs + 16 + 8 * c);
          if (c) j1 += 7; else j0 += 7;
        }
        if (lane == 0) mbar_arrive(b_go);
        if (lane == 0) red_release_add(&g_hcnt[32 * (1 + (item0 & 15))], 1u);
      }
      sleep_until(t0, 26000);
      const uint32_t v = assign_tile(hm, t0, threadIdx.x & 31);
      if (threadIdx.x == 32) { sts_u32(s_bx, v); mbar_arrive(b_bx); }
      __syncwarp();
      store_warp(hm, sbase, &tmO, item0, n_items);
      __syncwarp();
    } else {
     if (elect_one()) {
      const uint64_t pol = policy_evict_first();
      prefetch_tmap(&tmW); prefetch_tmap(&tmX); prefetch_tmap(&tmWo); prefetch_tmap(&tmOl);
      if (single) {
        prefetch_tmap(&tmM);
        #pragma unroll 1
        for (uint32_t i = 0, buf = 0; i < 44; i++) {
          wait_clock(t0, i < 12 ? (blockIdx.x < 128 ? WDLY + W_OFF : WDLY) + (i & 3) * W_GAP + (i >> 2) * W_RND : W_LATE);
          #pragma unroll 1
          for (uint32_t spin = 0, n = 0; spin < (1u << 24) && n <= i; spin++) asm volatile("ld.volatile.shared.u32 %0, [%1];" : "=r"(n) : "r"(bars + 504) : "memory");
          mbar_expect_tx(bars + 464 + buf * 8, 32768);
          tma_load_2d_hint(sbase + (buf + (buf > 2 ? 2 : 0)) * 32768, &tmM, mod_col0(blockIdx.x - AT_NFULL, (int)(i >> 2) - 3), (i & 3) * 256, bars + 464 + buf * 8, pol);
          if (++buf == 5) buf = 0;
        }
        mbar_wait(b_go, 0);
      }
      {
        #pragma unroll 1
        for (int j = 0; j < T_D / 64; j++) {
          const uint32_t fb = b_full + 8 * (j & 3);
          mbar_wait(b_empty + 8 * (j & 3), ((j >> 2) & 1) ^ 1);
          mbar_expect_tx(fb, j == 0 ? 65536 : j == T_D / 64 - 1 ? 32768 : 49152);
          if (j < 2) wait_clock(t0, j ? ST1_T : PRE_T);
          if (j == 3) mbar_wait(b_a0, 0);
          if (j < 4) HS(2 + j);
          tma_load_3d_hint(sbase + (j & 3) * 32768, &tmW, j * 64, (item0 >> 4) * 4, fb, pol);
          if (j == 0) { wait_clock(t0, A_T); tma_load_2d_hint(sbase + AT_SQ, &tmX, 0, (item0 & 15) * 128, fb, pol); }
          if (j < T_D / 64 - 1) tma_load_2d_hint(sbase + AT_SQ + ((j + 1) & 3) * 16384, &tmX, (j + 1) * 64, (item0 & 15) * 128, fb, pol);
        }
      }
      uint32_t slot = 0, ph = 1;
      #pragma unroll 1
      for (int it = 0; it < n_items; it++) {
        const int item = item0 + it * 128, hp = item >> 4, qt = item & 15;
        const bool first = it == 0;
        if (!first) {
          #pragma unroll 1
          for (int j = 0; j < T_D / 64; j++) {
            const uint32_t sl = ring_slot(qp_pos(j, 1)), fb = b_full + 8 * sl;
            mbar_wait(b_empty + 8 * sl, ring_par(qp_pos(j, 1)) ^ ((j >> 2) & 1) ^ 1);
            mbar_expect_tx(fb, 49152);
            tma_load_3d_hint(sbase + sl * 32768, &tmW, j * 64, hp * 4, fb, pol);
            if (j == 0) { mbar_wait(b_q0, 0); mbar_wait(b_q1, 0); mbar_wait(b_w, 0); fence_proxy_async_global(); }
            tma_load_2d_hint(sbase + AT_SQ + (j & 3) * 16384, &tmOl, O_H + j * 64, qt * 128, fb, pol);
          }
        }
        #pragma unroll 1
        for (int j = 0; j < 4 * AT_NBLK; j++) {
          const bool isv = (j > 0 && !(j & 1)) || j == 4 * AT_NBLK - 1;
          const int row = hp * 2 * T_SEQ + (isv ? (j - 1) >> 1 : (j + 1) >> 1) * 128;
          const uint32_t fb = b_full + 8 * slot;
          mbar_wait(b_empty + 8 * slot, ph);
          if (!first && j == 3) mbar_wait(b_ob, 0);
          if (!first && j == 4) hint_arrive(&g_hcnt[32 * (1 + qt) + 1]);
          if (first && j == 4 && item0 < 112) mbar_wait(b_go, 0);
          mbar_expect_tx(fb, 32768);
          tma_load_2d_hint(sbase + slot * 32768, isv ? &tmV : &tmK, 0, row, fb, pol);
          tma_load_2d_hint(sbase + slot * 32768 + 16384, isv ? &tmV : &tmK, 64, row, fb, pol);
          if (it == 1 && isv && j >= 2 * WO_LATE && j < 2 * WO_LATE + 32 && blockIdx.x < 64)
            l2_prefetch_bulk(pf_wo + (size_t)blockIdx.x * 131072 + ((j >> 1) - WO_LATE) * 8192, 8192);
          if (++slot == 5) { slot = 0; ph ^= 1; }
        }
      }
      mbar_wait(b_bx, 0);
      const uint32_t bx = lds_u32(s_bx);
      if (bx < 128) {
        if (single) mbar_wait(b_go, 1);
        tail_producer(hm, bx, sbase, 0, n_items - 1, pol, &tmOl, &tmWo, &tmX, w_down);
      }
     }
    }
    __syncwarp();
    PSV(0, threadIdx.x == 96, t0);
    mbar_wait(b_bx, 0);
    const uint32_t bx = __shfl_sync(0xffffffffu, lds_u32(s_bx), 0);
    if (bx < 128) tail_exchange(hm, bx, sbase, wid, __shfl_sync(0xffffffffu, threadIdx.x, threadIdx.x), &tmOut, out);
  } else {
    if (wg == 1 && blockIdx.x < 128) head_first(hm, sbase + 4 * 32768 + 4096, threadIdx.x - 128, cvec, w_mod);
    named_bar_sync(10 + wg, 160);
    if (wg == 2 && blockIdx.x < 128) head_stats(hm, sbase + 3 * 32768, b_x, threadIdx.x - 256);
    if (single) {
      mod_rest(hm, t0, sbase, bars + 464, threadIdx.x - 128, (int)blockIdx.x - AT_NFULL, cvec, w_r);
      named_bar_sync(5, 256);
      if (threadIdx.x == 128) mbar_arrive(b_go);
    }
    if (wg == 1) { wait_clock(t0, GDLY); head_gather(hm, sbase + 4 * 32768, threadIdx.x - 128); }
    reg_alloc<AT_CREG>();
    const int cwg = wg - 1;
    const int tid = __shfl_sync(0xffffffffu, threadIdx.x, threadIdx.x) & 127;
    const int warp = wid & 3, lane = tid & 31;
    const uint32_t dbase = (sbase & 0x3FFFFu) >> 4;
    const uint32_t k_base = dbase + (1u << 16);
    const uint32_t v_base = dbase + (1024u << 16);
    const uint32_t w_base = dbase + (512u << 16);
    const uint32_t frag = cwg * 8192 + (16 * warp + (lane & 7) + 8 * ((lane >> 3) & 1)) * 128;
    if (cwg == 1) named_bar_arrive(1, 256);
    bool raw = false;
    constexpr int nkb = T_D / 64;
    float acc[128], c0, c1;
    {
      FS(0, 0);
      uint32_t af[2][16], rw[16];
      uint4 tb[4];
      uint32_t xa[4];
      #pragma unroll
      for (int st = 0; st < 4; st++) xa[st] = __shfl_sync(0xffffffffu, (sbase + AT_SQ + frag + (((lane >> 4) ^ (lane & 7)) << 4)) ^ (st * 32), lane);
      const uint32_t xt = __shfl_sync(0xffffffffu, sbase + 4 * 32768 + (lane & 3) * 16, lane);
      auto qp_fetch = [&](int j) {
        #pragma unroll
        for (int st = 0; st < 4; st++) {
          ldmatrix_x4(xa[st] + (j & 3) * 16384, rw[4 * st], rw[4 * st + 1], rw[4 * st + 2], rw[4 * st + 3]);
          tb[st] = lds_u32x4(xt + (j & 15) * 256 + st * 64);
        }
      };
      zero_regs(acc);
      #pragma unroll
      for (int i = 0; i < 16; i++) af[1][i] = 0u;
      const float2* stp = hm->stat + (item0 & 15) * 256 + (cwg * 4 + warp) * 32 + (lane & 3) * 8 + (lane >> 2);
      HS(4);
      wait_clock(t0, SDLY);
      float2 sv = ld_tagged2(stp);
      named_bar_sync(5, 256);
      mbar_wait(b_full, 0);
      HS(5);
      qp_fetch(0);
      #pragma unroll 1
      for (unsigned int spin = 0; spin < (1u << 22); spin++) {
        if (__all_sync(0xffffffffu, (__float_as_uint(sv.x) != 0u) & (__float_as_uint(sv.y) != 0u))) break;
        sv = ld_tagged2(stp);
      }
      HS(6);
      if (lane == 0) mbar_arrive(b_a0 + (rw[3] & rw[7] & rw[11] & rw[15] & zero));
      const uint32_t st = ln_stat(sv.x + __shfl_xor_sync(0xffffffffu, sv.x, 1), sv.y + __shfl_xor_sync(0xffffffffu, sv.y, 1)), so = __shfl_xor_sync(0xffffffffu, st, 2);
      const uint32_t sta = (lane & 2) ? so : st, stb = (lane & 2) ? st : so;
      const uint32_t mean_a = __byte_perm(sta, 0u, 0x1010), mean_b = __byte_perm(stb, 0u, 0x1010), sd_a = __byte_perm(sta, 0u, 0x3232), sd_b = __byte_perm(stb, 0u, 0x3232);
      c0 = AT_C * rcp_approx(bfhi(sta)); c1 = AT_C * rcp_approx(bfhi(stb));
      sts_u32(sbase + OG_SMISC + 256 + (cwg * 4 + warp) * 64 + (lane & 28) + (lane & 2) * 16, __float_as_uint((lane & 2) ? c1 : c0));
      int jst = item0 < 112 ? h_first(item0, cwg) : 99;
      #pragma unroll 1
      for (int j2 = 0; j2 < nkb; j2 += 2) {
        #pragma unroll
        for (int u = 0; u < 2; u++) {
          const int j = j2 + u;
          const uint32_t bt = b_tab + 4 * ((j + 1) & 15);
          if (u == 1) {
            #pragma unroll 1
            for (uint32_t z = 0; z < zero; z++)
              #pragma unroll
              for (int i = 0; i < 16; i += 4) sts_u32x4(xt + i * 4, af[1][i], af[1][i + 1], af[1][i + 2], af[1][i + 3]);
          }
          bool ok = mbar_test(b_full + 8 * (j & 3), (j >> 2) & 1);
          if (u == 1) ok &= mbar_test(bt, 0);
          #pragma unroll
          for (int st = 0; st < 4; st++) {
            af[u][4 * st + 0] = bfma2(bsub2(rw[4 * st + 0], mean_a), tb[st].x, bmul2(tb[st].z, sd_a));
            af[u][4 * st + 1] = bfma2(bsub2(rw[4 * st + 1], mean_b), tb[st].x, bmul2(tb[st].z, sd_b));
            af[u][4 * st + 2] = bfma2(bsub2(rw[4 * st + 2], mean_a), tb[st].y, bmul2(tb[st].w, sd_a));
            af[u][4 * st + 3] = bfma2(bsub2(rw[4 * st + 3], mean_b), tb[st].y, bmul2(tb[st].w, sd_b));
          }
          if (!ok || j == jst) {
            if (!ok) { mbar_wait(b_full + 8 * (j & 3), (j >> 2) & 1); if (u == 1) mbar_wait(bt, 0); }
            if (j == jst) {
              if (j >= 7) mbar_wait(b_hs + 16 + 8 * cwg, j >= 14);
              #pragma unroll
              for (int st = 0; st < 4; st++) stmatrix_x4(xa[st] - 16384, af[u][4 * st], af[u][4 * st + 1], af[u][4 * st + 2], af[u][4 * st + 3]);
              __syncwarp();
              if (lane == 0) mbar_arrive(b_hs + 8 * cwg);
              jst += 7;
            }
          }
          qp_fetch(j + 1);
          if (cwg == 1 && j == nkb - QP_STAG) named_bar_sync(7, 256);
          const uint32_t b_lo = w_base + (j & 3) * 2048;
          wgmma_fence();
          wgmma_m64n256k16_rs_tb<0>(acc, af[u][0], af[u][1], af[u][2], af[u][3], b_lo, 1);
          wgmma_m64n256k16_rs_tb<128>(acc, af[u][4], af[u][5], af[u][6], af[u][7], b_lo, 1);
          wgmma_m64n256k16_rs_tb<256>(acc, af[u][8], af[u][9], af[u][10], af[u][11], b_lo, 1);
          wgmma_m64n256k16_rs_tb<384>(acc, af[u][12], af[u][13], af[u][14], af[u][15], b_lo, 1);
          wgmma_commit();
          if (cwg == 0 && j == nkb - 1) named_bar_arrive(7, 256);
          if (j == 0) HS(7);
          wgmma_wait<1>();
          if (tid == 0) mbar_arrive(j > 0 ? b_empty + 8 * ((j - 1) & 3) : b_pin);
        }
      }
      wgmma_wait<0>();
      fence_regs(acc);
    }
    uint32_t bx;
    #pragma unroll 1
    for (int it = 0;;) {
      const int item = item0 + it * 128, hp = item >> 4;
      const bool more = it + 1 < n_items;
      const int ta = __shfl_sync(0xffffffffu, 4 * it, 0);
      FS(2 * it, 1);
      PS(1 + 2 * it, threadIdx.x == 256);
      if (tid == 0) mbar_arrive(b_empty + 24);
      float o[64], s[64];
      uint32_t p[32], q[32];
      #pragma unroll
      for (int i = 0; i < 32; i++) q[i] = pack_bf16(acc[2 * i] * ((i & 1) ? c1 : c0), acc[2 * i + 1] * ((i & 1) ? c1 : c0));
      zero_regs(s);
      const uint32_t sq = sbase + AT_SQ + cwg * 8192;
      const bool last_wg1 = cwg == 1 && !more;
      float mc0, mc1, al0 = 1.0f, al1 = 1.0f, l0 = 0.f, l1 = 0.f, lp0 = 0.f, lp1 = 0.f;
      bool redo0 = false;
      FS(2 * it, 2);
      {
        uint32_t dep = zero;
        #pragma unroll
        for (int i = 0; i < 32; i++) dep &= q[i];
        mbar_wait(b_full + 8 * ring_slot(ta) + dep, ring_par(ta));
      }
      named_bar_sync(1 + cwg, 256);
      FS(2 * it, 3);
      issue_qk(s, q, k_base + ring_slot(ta) * 2048);
      named_bar_arrive(1 + (cwg ^ 1), 256);
      const uint32_t rdy = (uint32_t)mbar_test(b_full + 8 * ring_slot(ta + 1), ring_par(ta + 1));
      bool ready = rdy & mbar_test(b_full + 8 * ring_slot(ta + 2), ring_par(ta + 2));
      stage_o(*reinterpret_cast<const float (*)[64]>(&acc[64]), c0, c1, sbase + AT_SQ + 32768 + frag, lane);
      wgmma_wait<0>();
      fence_regs(s);
      if (tid == 0) mbar_arrive(b_empty + 8 * ring_slot(ta));
      mc0 = 0.f; mc1 = 0.f;
      if (!raw) {
        raw = softmax_mode(s, mc0, mc1);
        if (__builtin_expect(!raw, 0)) softmax_sub(s, mc0, mc1);
      }
      softmax_exp<0, 64>(s);
      stage_qregs(q, sbase + AT_SQ + frag, lane);
      pack_p(p, s);
      zero_regs(o);
      FS(2 * it, 4);
      uint32_t ks = ring_slot(ta + 1), vs = ring_slot(ta + 2), kp = ring_par(ta + 1), vp = ring_par(ta + 2);
      if (!ready) { mbar_wait(b_full + 8 * ks, kp); mbar_wait(b_full + 8 * vs, vp); }
      #pragma unroll 1
      for (int n = 1; n < 2 * AT_NBLK; n++) {
        named_bar_sync(1 + cwg, 256);
        issue_qk(s, q, k_base + ks * 2048);
        if (n == AT_NBLK + 1) {
          redo0 = finish_l(lp0, lp1);
          if (!redo0) stage_o(o, lp0, lp1, sbase + AT_SQ + frag, lane);
        }
        issue_pv(o, p, v_base + vs * 2048, (n & 15) != 1);
        if (!(last_wg1 && n == 2 * AT_NBLK - 1)) named_bar_arrive(1 + (cwg ^ 1), 256);
        wgmma_wait<1>();
        fence_regs(s);
        if (tid == 0) mbar_arrive(b_empty + 8 * ks);
        if (__builtin_expect(!raw || (n + 1) >> 1 == AT_NBLK / 2, 0)) {
          if (n == AT_NBLK - 1) {
            #pragma unroll
            for (int J = 0; J < 16; J += 2)
              ldmatrix_x4(sbase + AT_SQ + 32768 + frag + (J >> 3) * 16384 + ((((J & 7) + (lane >> 4)) ^ (lane & 7)) << 4), q[2 * J], q[2 * J + 1], q[2 * J + 2], q[2 * J + 3]);
          }
          if (n == AT_NBLK && lane == 0) mbar_arrive(b_q1);
          if (!raw) {
            const float m0 = mc0, m1 = mc1;
            const bool ok = softmax_mode(s, mc0, mc1);
            if (n == AT_NBLK) raw = ok;
            else {
              mc0 = mc0 - AT_HEAD > m0 ? mc0 : m0; mc1 = mc1 - AT_HEAD > m1 ? mc1 : m1;
              al0 = ex2_approx(m0 - mc0); al1 = ex2_approx(m1 - mc1);
            }
            if (!raw) softmax_sub(s, mc0, mc1);
          }
        }
        softmax_exp<0, AT_SPLIT>(s);
        add_rowsum(p, l0, l1);
        if (tid == 0) {
          uint32_t dep = zero & __float_as_uint(l0) & __float_as_uint(l1);
          #pragma unroll
          for (int i = AT_SPLIT - AT_PIN - PINB; i < AT_SPLIT - PINB; i += 2) dep &= __float_as_uint(s[i]) & __float_as_uint(s[i + 1]);
          mbar_arrive(b_pin + dep);
        }
        wgmma_wait<0>();
        fence_regs(o);
        if (tid == 0) mbar_arrive(b_empty + 8 * vs);
        ks += 2; if (ks >= 5) { ks -= 5; kp ^= 1; }
        vs += 2; if (vs >= 5) { vs -= 5; vp ^= 1; }
        ready = mbar_test(b_full + 8 * ks, kp) & mbar_test(b_full + 8 * vs, vp);
        softmax_exp<AT_SPLIT, 64>(s);
        pack_p(p, s);
        if (n == AT_NBLK) { lp0 = l0; lp1 = l1; l0 = 0.f; l1 = 0.f; }
        if (__builtin_expect(!raw || !ready || n == AT_NBLK + 1, 0)) {
        if (n == AT_NBLK + 1 && !redo0) { fence_proxy_async(); __syncwarp(); if (lane == 0) mbar_arrive(b_ordy + 8 * cwg); }
        if (!raw && __any_sync(0xffffffffu, al0 != 1.0f || al1 != 1.0f)) {
          rescale_o(o, al0, al1);
          l0 *= al0; l1 *= al1;
          al0 = 1.0f; al1 = 1.0f;
        }
        if (!ready && n < 2 * AT_NBLK - 1) {
          mbar_wait(b_full + 8 * ks, kp);
          mbar_wait(b_full + 8 * vs, vp);
        }
        }
      }
      FS(2 * it + 1, 5);
      const uint32_t vl = ring_slot(ta + 63);
      vs = ring_slot(ta + 62);
      const uint32_t ob = more ? sbase + vs * 32768 : sbase + AT_SQ + 32768;
      mbar_wait(b_full + 8 * vl, ring_par(ta + 63));
      issue_pv(o, p, v_base + vl * 2048, 1);
      add_rowsum(p, l0, l1);
      const bool overflow = finish_l(l0, l1);
      mbar_wait(b_bx, 0);
      bx = __shfl_sync(0xffffffffu, lds_u32(s_bx), 0);
      mbar_wait(b_empty + 8 * vs, ring_par(ta + 62));
      wgmma_wait<0>();
      fence_regs(o);
      if (tid == 0) mbar_arrive(b_empty + 8 * vl);
      FS(2 * it + 1, 6);
      if (overflow) stage_qregs(q, ob + frag, lane);
      else stage_o(o, l0, l1, ob + frag, lane);
      if (__builtin_expect(overflow || redo0, 0)) {
        __syncwarp();
        #pragma unroll 1
        for (int h = redo0 ? 0 : 1; h < (overflow ? 2 : 1); h++)
          attn_rows_exact(h ? ob + cwg * 8192 : sq, warp, lane, kc + (size_t)(hp * 2 + h) * T_SEQ * T_DH, vc + (size_t)(hp * 2 + h) * T_SEQ * T_DH);
        fence_proxy_async();
        __syncwarp();
        if (lane == 0 && redo0) mbar_arrive(b_ordy + 8 * cwg);
        raw = false;
      }
      fence_proxy_async();
      __syncwarp();
      if (lane == 0) mbar_arrive(b_ordy + 16 + 8 * cwg);
      named_bar_sync(3 + cwg, 128);
      FS(2 * it + 1, 7);
      PS(2 + 2 * it, threadIdx.x == 256);
      if (++it == n_items) break;
      FS(2 * it, 0);
      zero_regs(acc);
      auto ss_step = [&](int j, int accumulate) {
        const uint32_t slot = ring_slot(qp_pos(j, 1));
        mbar_wait(b_full + 8 * slot, ring_par(qp_pos(j, 1)) ^ ((j >> 2) & 1));
        if (cwg == 1 && j == nkb - QP_STAG) named_bar_sync(7, 256);
        const uint32_t a_lo = dbase + ((AT_SQ + cwg * 8192) >> 4) + (1u << 16) + (j & 3) * 1024, b_lo = w_base + slot * 2048;
        wgmma_fence();
        wgmma_m64n256k16_ss_tb<0, 0>(acc, a_lo, b_lo, accumulate);
        wgmma_m64n256k16_ss_tb<2, 128>(acc, a_lo, b_lo, 1);
        wgmma_m64n256k16_ss_tb<4, 256>(acc, a_lo, b_lo, 1);
        wgmma_m64n256k16_ss_tb<6, 384>(acc, a_lo, b_lo, 1);
        wgmma_commit();
        return b_empty + 8 * slot;
      };
      uint32_t prev = ss_step(0, 0);
      c0 = lds_f32(sbase + OG_SMISC + 256 + (cwg * 4 + warp) * 64 + (lane & 28)); c1 = lds_f32(sbase + OG_SMISC + 288 + (cwg * 4 + warp) * 64 + (lane & 28));
      #pragma unroll 1
      for (int j = 1; j < nkb; j++) {
        const uint32_t cur = ss_step(j, 1);
        if (cwg == 0 && j == nkb - 1) named_bar_arrive(7, 256);
        wgmma_wait<1>();
        if (tid == 0) mbar_arrive(prev);
        prev = cur;
      }
      wgmma_wait<0>();
      fence_regs(acc);
    }
    if (n_items == 1) {
      named_bar_sync(5, 256);
      if (threadIdx.x == 128) {
        #pragma unroll 1
        for (int i = 4; i < 8; i++) {
          mbar_arrive(b_full + 8 * ring_slot(i));
          mbar_arrive(b_empty + 8 * ring_slot(i)); mbar_arrive(b_empty + 8 * ring_slot(i));
        }
        mbar_arrive(b_go);
      }
      named_bar_sync(5, 256);
    }
    TL_CLK(3, 1, threadIdx.x == 128);
    TL_CTA(1, threadIdx.x == 256);
    TL_END(3, tid == 0);
    __syncwarp();
    QDUMP();
    TL_MARK2(19, tid == 0 && !single);
    if (bx < 128) {
      tail_consumer(hm, bx, sbase, tid, wid - 4, w_gate, w_up);
    }
  }
}

typedef CUresult (*PFN_encodeTiled)(CUtensorMap*, CUtensorMapDataType, cuuint32_t, void*, const cuuint64_t*, const cuuint64_t*,
                                    const cuuint32_t*, const cuuint32_t*, CUtensorMapInterleave, CUtensorMapSwizzle,
                                    CUtensorMapL2promotion, CUtensorMapFloatOOBfill);

CUtensorMap make_map_2d(PFN_encodeTiled enc, const void* ptr, uint64_t inner, uint64_t outer, uint64_t stride_bytes, uint32_t box_inner, uint32_t box_outer) {
  CUtensorMap m;
  cuuint64_t gd[2] = {inner, outer}; cuuint64_t gs[1] = {stride_bytes};
  cuuint32_t bx[2] = {box_inner, box_outer}; cuuint32_t es[2] = {1, 1};
  enc(&m, CU_TENSOR_MAP_DATA_TYPE_BFLOAT16, 2, const_cast<void*>(ptr), gd, gs, bx, es, CU_TENSOR_MAP_INTERLEAVE_NONE,
      CU_TENSOR_MAP_SWIZZLE_128B, CU_TENSOR_MAP_L2_PROMOTION_L2_128B, CU_TENSOR_MAP_FLOAT_OOB_FILL_NONE);
  return m;
}

CUtensorMap make_map_3d(PFN_encodeTiled enc, const void* ptr, uint64_t cols, uint64_t rows, uint32_t box_rows, uint32_t chunks) {
  CUtensorMap m;
  cuuint64_t gd[3] = {64, rows, cols / 64}; cuuint64_t gs[2] = {cols * 2, 128};
  cuuint32_t bx[3] = {64, box_rows, chunks}; cuuint32_t es[3] = {1, 1, 1};
  enc(&m, CU_TENSOR_MAP_DATA_TYPE_BFLOAT16, 3, const_cast<void*>(ptr), gd, gs, bx, es, CU_TENSOR_MAP_INTERLEAVE_NONE,
      CU_TENSOR_MAP_SWIZZLE_128B, CU_TENSOR_MAP_L2_PROMOTION_L2_128B, CU_TENSOR_MAP_FLOAT_OOB_FILL_NONE);
  return m;
}

}

extern "C" void kernel_launch(void* const* d_in, const int* in_sizes, int n_in, void* d_out, int out_size) {
  const bf16* x      = (const bf16*)d_in[0];
  const bf16* kc     = (const bf16*)d_in[1];
  const bf16* vc     = (const bf16*)d_in[2];
  const bf16* wq     = (const bf16*)d_in[3];
  const bf16* wo     = (const bf16*)d_in[4];
  const bf16* w_r    = (const bf16*)d_in[6];
  const bf16* w_gate = (const bf16*)d_in[7];
  const bf16* w_up   = (const bf16*)d_in[8];
  const bf16* w_down = (const bf16*)d_in[9];
  const bf16* cvec   = (const bf16*)d_in[10];
  const bf16* w_mod  = (const bf16*)d_in[11];
  bf16* out = (bf16*)d_out;

  static PFN_encodeTiled enc = nullptr;
  static void* p_hm = nullptr;
  if (!enc) {
    void* fn = nullptr; cudaDriverEntryPointQueryResult qres;
    cudaGetDriverEntryPoint("cuTensorMapEncodeTiled", &fn, cudaEnableDefault, &qres);
    enc = (PFN_encodeTiled)fn;
    cudaGetSymbolAddress(&p_hm, g_scr);
    cudaFuncSetAttribute(fused_kernel, cudaFuncAttributeMaxDynamicSharedMemorySize, (int)AT_SMEM);
  }
  const CUtensorMap tm_m   = make_map_2d(enc, w_mod, 6 * T_D, T_D, 6 * T_D * 2, 64, 256);
  const CUtensorMap tm_wq  = make_map_3d(enc, wq, T_DQKV, T_D, 64, 4);
  const CUtensorMap tm_k   = make_map_2d(enc, kc, T_DH, (uint64_t)T_NH * T_SEQ, T_DH * 2, 64, 128);
  const CUtensorMap tm_v   = make_map_2d(enc, vc, T_DH, (uint64_t)T_NH * T_SEQ, T_DH * 2, 64, 128);
  const CUtensorMap tm_ost = make_map_2d(enc, ((Scratch*)p_hm)->o, O_LD, T_SEQ, O_LD * 2, 64, 64);
  const CUtensorMap tm_old = make_map_2d(enc, ((Scratch*)p_hm)->o, O_LD, T_SEQ, O_LD * 2, 64, 128);
  const CUtensorMap tm_wo  = make_map_2d(enc, wo, T_D, T_DQKV, T_D * 2, 64, 64);
  const CUtensorMap tm_x   = make_map_2d(enc, x, T_D, T_SEQ, T_D * 2, 64, 128);
  const CUtensorMap tm_out = make_map_2d(enc, out, T_D, T_SEQ, T_D * 2, 64, 128);

#define TUNE_ARG
  fused_kernel<<<132, 384, AT_SMEM, cudaStreamPerThread>>>(x, cvec, w_mod, (Scratch*)p_hm, 0u, TUNE_ARG (const uint8_t*)wo, kc, vc, w_r, w_gate, w_up, w_down, out,
             tm_m, tm_wq, tm_k, tm_v, tm_ost, tm_old, tm_wo, tm_x, tm_out);
}
```

```cpp
#include <cuda_runtime.h>
#include <cuda_bf16.h>
#include <cuda.h>
#include <stdint.h>

namespace {

typedef __nv_bfloat16 bf16;

constexpr int T_SEQ = 2048, T_D = 1024, T_NH = 32, T_DH = 128, T_DQKV = 4096, T_F = 3584;

struct __align__(2048) TailMail {
  float4 part1[T_SEQ * 8];
  uint32_t key[256];
  uint4 cand[16 * 2 * 2 * 128];
  uint32_t cnt[32];
  float ypart[(T_F / 32) * 2 * T_D];
};
constexpr int O_LD = T_DQKV, O_H = 16 * T_DH;
struct __align__(2048) Scratch {
  TailMail mail;
  float mod[2 * T_D];
  float modu[16 * 512];
  float2 stat[T_SEQ * 2];
  uint32_t gkey[160];
  uint8_t col[8 * 1536];
  unsigned int hcnt[17 * 32];
  float scal[4];
  __align__(1024) bf16 o[T_SEQ * O_LD];
};
__device__ Scratch g_scr;
#define g_part1 hm->mail.part1
#define g_key hm->mail.key
#define g_cand hm->mail.cand
#define CNT_Y hm->mail.cnt
#define g_ypart hm->mail.ypart
#define g_col hm->col
#define g_scal hm->scal
#define g_hcnt hm->hcnt

__device__ __forceinline__ uint32_t smem_u32(const void* p) { return (uint32_t)__cvta_generic_to_shared(p); }
__device__ __forceinline__ void mbar_init(uint32_t bar, uint32_t cnt) { asm volatile("mbarrier.init.shared::cta.b64 [%0], %1;" :: "r"(bar), "r"(cnt)); }
__device__ __forceinline__ void mbar_expect_tx(uint32_t bar, uint32_t bytes) { asm volatile("mbarrier.arrive.expect_tx.shared::cta.b64 _, [%0], %1;" :: "r"(bar), "r"(bytes) : "memory"); }
__device__ __forceinline__ void mbar_arrive(uint32_t bar) { asm volatile("mbarrier.arrive.shared::cta.b64 _, [%0];" :: "r"(bar) : "memory"); }
__device__ __forceinline__ void mbar_wait(uint32_t bar, uint32_t parity) {
  asm volatile("{\n.reg .pred p;\nLAB_WAIT:\nmbarrier.try_wait.parity.shared::cta.b64 p, [%0], %1;\n@!p bra LAB_WAIT;\n}\n" :: "r"(bar), "r"(parity) : "memory");
}
__device__ __forceinline__ bool mbar_test(uint32_t bar, uint32_t parity) {
  uint32_t r; asm volatile("{\n.reg .pred p;\nmbarrier.test_wait.parity.shared::cta.b64 p, [%1], %2;\nselp.u32 %0, 1, 0, p;\n}\n" : "=r"(r) : "r"(bar), "r"(parity) : "memory");
  return r != 0;
}
__device__ __forceinline__ void fence_mbar_init() { asm volatile("fence.mbarrier_init.release.cluster;" ::: "memory"); }
__device__ __forceinline__ uint64_t policy_evict_first() {
  uint64_t p; asm volatile("createpolicy.fractional.L2::evict_first.b64 %0, 1.0;" : "=l"(p)); return p;
}
__device__ __forceinline__ void tma_load_2d_hint(uint32_t dst, const CUtensorMap* map, int c0, int c1, uint32_t bar, uint64_t pol) {
  asm volatile("cp.async.bulk.tensor.2d.shared::cluster.global.mbarrier::complete_tx::bytes.L2::cache_hint [%0], [%1, {%3, %4}], [%2], %5;"
    :: "r"(dst), "l"(map), "r"(bar), "r"(c0), "r"(c1), "l"(pol) : "memory");
}
__device__ __forceinline__ void tma_load_3d_hint(uint32_t dst, const CUtensorMap* map, int c1, int c2, uint32_t bar, uint64_t pol) {
  asm volatile("cp.async.bulk.tensor.3d.shared::cluster.global.mbarrier::complete_tx::bytes.L2::cache_hint [%0], [%1, {%6, %3, %4}], [%2], %5;"
    :: "r"(dst), "l"(map), "r"(bar), "r"(c1), "r"(c2), "l"(pol), "r"(0) : "memory");
}
__device__ __forceinline__ void tma_store_2d(const CUtensorMap* map, uint32_t src, int c0, int c1) {
  asm volatile("cp.async.bulk.tensor.2d.global.shared::cta.bulk_group [%0, {%2, %3}], [%1];" :: "l"(map), "r"(src), "r"(c0), "r"(c1) : "memory");
}
__device__ __forceinline__ void prefetch_tmap(const CUtensorMap* map) { asm volatile("prefetch.tensormap [%0];" :: "l"(map) : "memory"); }
__device__ __forceinline__ void l2_prefetch_bulk(const void* p, uint32_t bytes) {
  asm volatile("cp.async.bulk.prefetch.L2.global [%0], %1;" :: "l"(p), "r"(bytes) : "memory");
}
__device__ __forceinline__ void bulk_commit() { asm volatile("cp.async.bulk.commit_group;" ::: "memory"); }
template<int N> __device__ __forceinline__ void bulk_wait_read() { asm volatile("cp.async.bulk.wait_group.read %0;" :: "n"(N) : "memory"); }
template<int N> __device__ __forceinline__ void bulk_wait() { asm volatile("cp.async.bulk.wait_group %0;" :: "n"(N) : "memory"); }
__device__ __forceinline__ void named_bar_sync(int id, int nthreads) { asm volatile("bar.sync %0, %1;" :: "r"(id), "r"(nthreads) : "memory"); }
__device__ __forceinline__ void named_bar_arrive(int id, int nthreads) { asm volatile("bar.arrive %0, %1;" :: "r"(id), "r"(nthreads) : "memory"); }
__device__ __forceinline__ void wgmma_fence() { asm volatile("wgmma.fence.sync.aligned;" ::: "memory"); }
__device__ __forceinline__ void wgmma_commit() { asm volatile("wgmma.commit_group.sync.aligned;" ::: "memory"); }
template<int N> __device__ __forceinline__ void wgmma_wait() { asm volatile("wgmma.wait_group.sync.aligned %0;" :: "n"(N) : "memory"); }
template<int R> __device__ __forceinline__ void reg_alloc() { asm volatile("setmaxnreg.inc.sync.aligned.u32 %0;" :: "n"(R)); }
template<int R> __device__ __forceinline__ void reg_dealloc() { asm volatile("setmaxnreg.dec.sync.aligned.u32 %0;" :: "n"(R)); }
__device__ __forceinline__ bool elect_one() {
  uint32_t pred; asm volatile("{\n.reg .pred p;\nelect.sync _|p, 0xffffffff;\nselp.u32 %0, 1, 0, p;\n}\n" : "=r"(pred)); return pred != 0;
}
__device__ __forceinline__ uint32_t pack_bf16(float lo, float hi) {
  uint32_t r; asm("cvt.rn.bf16x2.f32 %0, %1, %2;" : "=r"(r) : "f"(hi), "f"(lo)); return r;
}
__device__ __forceinline__ void stmatrix_x4(uint32_t addr, uint32_t r0, uint32_t r1, uint32_t r2, uint32_t r3) {
  asm volatile("stmatrix.sync.aligned.m8n8.x4.shared.b16 [%0], {%1, %2, %3, %4};" :: "r"(addr), "r"(r0), "r"(r1), "r"(r2), "r"(r3) : "memory");
}
__device__ __forceinline__ void fence_proxy_async() { asm volatile("fence.proxy.async.shared::cta;" ::: "memory"); }
__device__ __forceinline__ float ex2_approx(float x) { float y; asm("ex2.approx.ftz.f32 %0, %1;" : "=f"(y) : "f"(x)); return y; }
template<int N> __device__ __forceinline__ void fence_regs(float (&r)[N]) {
  #pragma unroll
  for (int i = 0; i < N; i++) asm volatile("" : "+f"(r[i]) :: "memory");
}
template<int N> __device__ __forceinline__ void zero_regs(float (&r)[N]) {
  #pragma unroll
  for (int i = 0; i < N; i += 2) asm volatile("mov.b64 {%0, %1}, 0;" : "=f"(r[i]), "=f"(r[i + 1]));
}
__device__ __forceinline__ float rbf(float x) { return __uint_as_float(pack_bf16(0.f, x)); }
__device__ __forceinline__ float bflo(uint32_t v) { return __uint_as_float(v << 16); }
__device__ __forceinline__ float bfhi(uint32_t v) { return __uint_as_float(v & 0xffff0000u); }

#define TL_START(k) do {} while (0)
#define TL_END(k, cond) do {} while (0)
#define TL_CTA(i, cond) do {} while (0)
#define FS(slot, k) do {} while (0)
#define QS(idx) do {} while (0)
#define QDUMP() do {} while (0)
#define TL_MARK2(k, cond) do {} while (0)
#define TL_CLK(k, i, cond) do {} while (0)

#define HS(k) do {} while (0)
#define HSD(k, dep) do {} while (0)
#define HSDUMP() do {} while (0)
#define PS(k, cond) do {} while (0)
#define PSV(k, cond, v) do {} while (0)
#define PF(k) do {} while (0)
#define TS(k, cond) do {} while (0)
template <int OFFA, int OFFB>
__device__ __forceinline__ void wgmma_m64n256k16_ss_tb(float (&d)[128], uint32_t a_lo, uint32_t b_lo, int scaleD) {
  asm volatile("{\n.reg .pred p;\n.reg .b32 ta, tb;\n.reg .b64 da, db;\nsetp.ne.b32 p, %130, 0;\n"
    "add.u32 ta, %128, %131;\nadd.u32 tb, %129, %132;\n"
    "mov.b64 da, {ta, 0x40000040};\nmov.b64 db, {tb, 0x40000040};\n"
    "wgmma.mma_async.sync.aligned.m64n256k16.f32.bf16.bf16 "
    "{%0, %1, %2, %3, %4, %5, %6, %7, %8, %9, %10, %11, %12, %13, %14, %15, %16, %17, %18, %19, %20, %21, %22, %23, %24, %25, %26, %27, %28, %29, %30, %31, %32, %33, %34, %35, %36, %37, %38, %39, %40, %41, %42, %43, %44, %45, %46, %47, %48, %49, %50, %51, %52, %53, %54, %55, %56, %57, %58, %59, %60, %61, %62, %63, %64, %65, %66, %67, %68, %69, %70, %71, %72, %73, %74, %75, %76, %77, %78, %79, %80, %81, %82, %83, %84, %85, %86, %87, %88, %89, %90, %91, %92, %93, %94, %95, %96, %97, %98, %99, %100, %101, %102, %103, %104, %105, %106, %107, %108, %109, %110, %111, %112, %113, %114, %115, %116, %117, %118, %119, %120, %121, %122, %123, %124, %125, %126, %127}, "
    "da, db, p, 1, 1, 0, 1;\n}\n"
    : "+f"(d[0]), "+f"(d[1]), "+f"(d[2]), "+f"(d[3]), "+f"(d[4]), "+f"(d[5]), "+f"(d[6]), "+f"(d[7]), "+f"(d[8]), "+f"(d[9]), "+f"(d[10]), "+f"(d[11]), "+f"(d[12]), "+f"(d[13]), "+f"(d[14]), "+f"(d[15]), "+f"(d[16]), "+f"(d[17]), "+f"(d[18]), "+f"(d[19]), "+f"(d[20]), "+f"(d[21]), "+f"(d[22]), "+f"(d[23]), "+f"(d[24]), "+f"(d[25]), "+f"(d[26]), "+f"(d[27]), "+f"(d[28]), "+f"(d[29]), "+f"(d[30]), "+f"(d[31]), "+f"(d[32]), "+f"(d[33]), "+f"(d[34]), "+f"(d[35]), "+f"(d[36]), "+f"(d[37]), "+f"(d[38]), "+f"(d[39]), "+f"(d[40]), "+f"(d[41]), "+f"(d[42]), "+f"(d[43]), "+f"(d[44]), "+f"(d[45]), "+f"(d[46]), "+f"(d[47]), "+f"(d[48]), "+f"(d[49]), "+f"(d[50]), "+f"(d[51]), "+f"(d[52]), "+f"(d[53]), "+f"(d[54]), "+f"(d[55]), "+f"(d[56]), "+f"(d[57]), "+f"(d[58]), "+f"(d[59]), "+f"(d[60]), "+f"(d[61]), "+f"(d[62]), "+f"(d[63]), "+f"(d[64]), "+f"(d[65]), "+f"(d[66]), "+f"(d[67]), "+f"(d[68]), "+f"(d[69]), "+f"(d[70]), "+f"(d[71]), "+f"(d[72]), "+f"(d[73]), "+f"(d[74]), "+f"(d[75]), "+f"(d[76]), "+f"(d[77]), "+f"(d[78]), "+f"(d[79]), "+f"(d[80]), "+f"(d[81]), "+f"(d[82]), "+f"(d[83]), "+f"(d[84]), "+f"(d[85]), "+f"(d[86]), "+f"(d[87]), "+f"(d[88]), "+f"(d[89]), "+f"(d[90]), "+f"(d[91]), "+f"(d[92]), "+f"(d[93]), "+f"(d[94]), "+f"(d[95]), "+f"(d[96]), "+f"(d[97]), "+f"(d[98]), "+f"(d[99]), "+f"(d[100]), "+f"(d[101]), "+f"(d[102]), "+f"(d[103]), "+f"(d[104]), "+f"(d[105]), "+f"(d[106]), "+f"(d[107]), "+f"(d[108]), "+f"(d[109]), "+f"(d[110]), "+f"(d[111]), "+f"(d[112]), "+f"(d[113]), "+f"(d[114]), "+f"(d[115]), "+f"(d[116]), "+f"(d[117]), "+f"(d[118]), "+f"(d[119]), "+f"(d[120]), "+f"(d[121]), "+f"(d[122]), "+f"(d[123]), "+f"(d[124]), "+f"(d[125]), "+f"(d[126]), "+f"(d[127])
    : "r"(a_lo), "r"(b_lo), "r"(scaleD), "n"(OFFA), "n"(OFFB));
}

template <int OFFA, int OFFB>
__device__ __forceinline__ void wgmma_m64n128k16_ss_tb(float (&d)[64], uint32_t a_lo, uint32_t b_lo, int scaleD) {
  asm volatile("{\n.reg .pred p;\n.reg .b32 ta, tb;\n.reg .b64 da, db;\nsetp.ne.b32 p, %66, 0;\n"
    "add.u32 ta, %64, %67;\nadd.u32 tb, %65, %68;\n"
    "mov.b64 da, {ta, 0x40000040};\nmov.b64 db, {tb, 0x40000040};\n"
    "wgmma.mma_async.sync.aligned.m64n128k16.f32.bf16.bf16 "
    "{%0, %1, %2, %3, %4, %5, %6, %7, %8, %9, %10, %11, %12, %13, %14, %15, %16, %17, %18, %19, %20, %21, %22, %23, %24, %25, %26, %27, %28, %29, %30, %31, %32, %33, %34, %35, %36, %37, %38, %39, %40, %41, %42, %43, %44, %45, %46, %47, %48, %49, %50, %51, %52, %53, %54, %55, %56, %57, %58, %59, %60, %61, %62, %63}, "
    "da, db, p, 1, 1, 0, 1;\n}\n"
    : "+f"(d[0]), "+f"(d[1]), "+f"(d[2]), "+f"(d[3]), "+f"(d[4]), "+f"(d[5]), "+f"(d[6]), "+f"(d[7]), "+f"(d[8]), "+f"(d[9]), "+f"(d[10]), "+f"(d[11]), "+f"(d[12]), "+f"(d[13]), "+f"(d[14]), "+f"(d[15]), "+f"(d[16]), "+f"(d[17]), "+f"(d[18]), "+f"(d[19]), "+f"(d[20]), "+f"(d[21]), "+f"(d[22]), "+f"(d[23]), "+f"(d[24]), "+f"(d[25]), "+f"(d[26]), "+f"(d[27]), "+f"(d[28]), "+f"(d[29]), "+f"(d[30]), "+f"(d[31]), "+f"(d[32]), "+f"(d[33]), "+f"(d[34]), "+f"(d[35]), "+f"(d[36]), "+f"(d[37]), "+f"(d[38]), "+f"(d[39]), "+f"(d[40]), "+f"(d[41]), "+f"(d[42]), "+f"(d[43]), "+f"(d[44]), "+f"(d[45]), "+f"(d[46]), "+f"(d[47]), "+f"(d[48]), "+f"(d[49]), "+f"(d[50]), "+f"(d[51]), "+f"(d[52]), "+f"(d[53]), "+f"(d[54]), "+f"(d[55]), "+f"(d[56]), "+f"(d[57]), "+f"(d[58]), "+f"(d[59]), "+f"(d[60]), "+f"(d[61]), "+f"(d[62]), "+f"(d[63])
    : "r"(a_lo), "r"(b_lo), "r"(scaleD), "n"(OFFA), "n"(OFFB));
}

template <int OFFB>
__device__ __forceinline__ void wgmma_m64n256k16_rs_tb(float (&d)[128], uint32_t a0, uint32_t a1, uint32_t a2, uint32_t a3, uint32_t b_lo, int scaleD) {
  asm volatile("{\n.reg .pred p;\n.reg .b32 tb;\n.reg .b64 db;\nsetp.ne.b32 p, %133, 0;\n"
    "add.u32 tb, %132, %134;\n"
    "mov.b64 db, {tb, 0x40000040};\n"
    "wgmma.mma_async.sync.aligned.m64n256k16.f32.bf16.bf16 "
    "{%0, %1, %2, %3, %4, %5, %6, %7, %8, %9, %10, %11, %12, %13, %14, %15, %16, %17, %18, %19, %20, %21, %22, %23, %24, %25, %26, %27, %28, %29, %30, %31, %32, %33, %34, %35, %36, %37, %38, %39, %40, %41, %42, %43, %44, %45, %46, %47, %48, %49, %50, %51, %52, %53, %54, %55, %56, %57, %58, %59, %60, %61, %62, %63, %64, %65, %66, %67, %68, %69, %70, %71, %72, %73, %74, %75, %76, %77, %78, %79, %80, %81, %82, %83, %84, %85, %86, %87, %88, %89, %90, %91, %92, %93, %94, %95, %96, %97, %98, %99, %100, %101, %102, %103, %104, %105, %106, %107, %108, %109, %110, %111, %112, %113, %114, %115, %116, %117, %118, %119, %120, %121, %122, %123, %124, %125, %126, %127}, "
    "{%128, %129, %130, %131}, db, p, 1, 1, 1;\n}\n"
    : "+f"(d[0]), "+f"(d[1]), "+f"(d[2]), "+f"(d[3]), "+f"(d[4]), "+f"(d[5]), "+f"(d[6]), "+f"(d[7]), "+f"(d[8]), "+f"(d[9]), "+f"(d[10]), "+f"(d[11]), "+f"(d[12]), "+f"(d[13]), "+f"(d[14]), "+f"(d[15]), "+f"(d[16]), "+f"(d[17]), "+f"(d[18]), "+f"(d[19]), "+f"(d[20]), "+f"(d[21]), "+f"(d[22]), "+f"(d[23]), "+f"(d[24]), "+f"(d[25]), "+f"(d[26]), "+f"(d[27]), "+f"(d[28]), "+f"(d[29]), "+f"(d[30]), "+f"(d[31]), "+f"(d[32]), "+f"(d[33]), "+f"(d[34]), "+f"(d[35]), "+f"(d[36]), "+f"(d[37]), "+f"(d[38]), "+f"(d[39]), "+f"(d[40]), "+f"(d[41]), "+f"(d[42]), "+f"(d[43]), "+f"(d[44]), "+f"(d[45]), "+f"(d[46]), "+f"(d[47]), "+f"(d[48]), "+f"(d[49]), "+f"(d[50]), "+f"(d[51]), "+f"(d[52]), "+f"(d[53]), "+f"(d[54]), "+f"(d[55]), "+f"(d[56]), "+f"(d[57]), "+f"(d[58]), "+f"(d[59]), "+f"(d[60]), "+f"(d[61]), "+f"(d[62]), "+f"(d[63]), "+f"(d[64]), "+f"(d[65]), "+f"(d[66]), "+f"(d[67]), "+f"(d[68]), "+f"(d[69]), "+f"(d[70]), "+f"(d[71]), "+f"(d[72]), "+f"(d[73]), "+f"(d[74]), "+f"(d[75]), "+f"(d[76]), "+f"(d[77]), "+f"(d[78]), "+f"(d[79]), "+f"(d[80]), "+f"(d[81]), "+f"(d[82]), "+f"(d[83]), "+f"(d[84]), "+f"(d[85]), "+f"(d[86]), "+f"(d[87]), "+f"(d[88]), "+f"(d[89]), "+f"(d[90]), "+f"(d[91]), "+f"(d[92]), "+f"(d[93]), "+f"(d[94]), "+f"(d[95]), "+f"(d[96]), "+f"(d[97]), "+f"(d[98]), "+f"(d[99]), "+f"(d[100]), "+f"(d[101]), "+f"(d[102]), "+f"(d[103]), "+f"(d[104]), "+f"(d[105]), "+f"(d[106]), "+f"(d[107]), "+f"(d[108]), "+f"(d[109]), "+f"(d[110]), "+f"(d[111]), "+f"(d[112]), "+f"(d[113]), "+f"(d[114]), "+f"(d[115]), "+f"(d[116]), "+f"(d[117]), "+f"(d[118]), "+f"(d[119]), "+f"(d[120]), "+f"(d[121]), "+f"(d[122]), "+f"(d[123]), "+f"(d[124]), "+f"(d[125]), "+f"(d[126]), "+f"(d[127])
    : "r"(a0), "r"(a1), "r"(a2), "r"(a3), "r"(b_lo), "r"(scaleD), "n"(OFFB));
}

template <int OFFB>
__device__ __forceinline__ void wgmma_m64n128k16_rs_tb(float (&d)[64], uint32_t a0, uint32_t a1, uint32_t a2, uint32_t a3, uint32_t b_lo, int scaleD) {
  asm volatile("{\n.reg .pred p;\n.reg .b32 tb;\n.reg .b64 db;\nsetp.ne.b32 p, %69, 0;\n"
    "add.u32 tb, %68, %70;\n"
    "mov.b64 db, {tb, 0x40000040};\n"
    "wgmma.mma_async.sync.aligned.m64n128k16.f32.bf16.bf16 "
    "{%0, %1, %2, %3, %4, %5, %6, %7, %8, %9, %10, %11, %12, %13, %14, %15, %16, %17, %18, %19, %20, %21, %22, %23, %24, %25, %26, %27, %28, %29, %30, %31, %32, %33, %34, %35, %36, %37, %38, %39, %40, %41, %42, %43, %44, %45, %46, %47, %48, %49, %50, %51, %52, %53, %54, %55, %56, %57, %58, %59, %60, %61, %62, %63}, "
    "{%64, %65, %66, %67}, db, p, 1, 1, 1;\n}\n"
    : "+f"(d[0]), "+f"(d[1]), "+f"(d[2]), "+f"(d[3]), "+f"(d[4]), "+f"(d[5]), "+f"(d[6]), "+f"(d[7]), "+f"(d[8]), "+f"(d[9]), "+f"(d[10]), "+f"(d[11]), "+f"(d[12]), "+f"(d[13]), "+f"(d[14]), "+f"(d[15]), "+f"(d[16]), "+f"(d[17]), "+f"(d[18]), "+f"(d[19]), "+f"(d[20]), "+f"(d[21]), "+f"(d[22]), "+f"(d[23]), "+f"(d[24]), "+f"(d[25]), "+f"(d[26]), "+f"(d[27]), "+f"(d[28]), "+f"(d[29]), "+f"(d[30]), "+f"(d[31]), "+f"(d[32]), "+f"(d[33]), "+f"(d[34]), "+f"(d[35]), "+f"(d[36]), "+f"(d[37]), "+f"(d[38]), "+f"(d[39]), "+f"(d[40]), "+f"(d[41]), "+f"(d[42]), "+f"(d[43]), "+f"(d[44]), "+f"(d[45]), "+f"(d[46]), "+f"(d[47]), "+f"(d[48]), "+f"(d[49]), "+f"(d[50]), "+f"(d[51]), "+f"(d[52]), "+f"(d[53]), "+f"(d[54]), "+f"(d[55]), "+f"(d[56]), "+f"(d[57]), "+f"(d[58]), "+f"(d[59]), "+f"(d[60]), "+f"(d[61]), "+f"(d[62]), "+f"(d[63])
    : "r"(a0), "r"(a1), "r"(a2), "r"(a3), "r"(b_lo), "r"(scaleD), "n"(OFFB));
}

template <int OFFB>
__device__ __forceinline__ void wgmma_m64n128k16_rs(float (&d)[64], uint32_t a0, uint32_t a1, uint32_t a2, uint32_t a3, uint32_t b_lo, int scaleD) {
  asm volatile("{\n.reg .pred p;\n.reg .b32 tb;\n.reg .b64 db;\nsetp.ne.b32 p, %69, 0;\n"
    "add.u32 tb, %68, %70;\n"
    "mov.b64 db, {tb, 0x40000040};\n"
    "wgmma.mma_async.sync.aligned.m64n128k16.f32.bf16.bf16 "
    "{%0, %1, %2, %3, %4, %5, %6, %7, %8, %9, %10, %11, %12, %13, %14, %15, %16, %17, %18, %19, %20, %21, %22, %23, %24, %25, %26, %27, %28, %29, %30, %31, %32, %33, %34, %35, %36, %37, %38, %39, %40, %41, %42, %43, %44, %45, %46, %47, %48, %49, %50, %51, %52, %53, %54, %55, %56, %57, %58, %59, %60, %61, %62, %63}, "
    "{%64, %65, %66, %67}, db, p, 1, 1, 0;\n}\n"
    : "+f"(d[0]), "+f"(d[1]), "+f"(d[2]), "+f"(d[3]), "+f"(d[4]), "+f"(d[5]), "+f"(d[6]), "+f"(d[7]), "+f"(d[8]), "+f"(d[9]), "+f"(d[10]), "+f"(d[11]), "+f"(d[12]), "+f"(d[13]), "+f"(d[14]), "+f"(d[15]), "+f"(d[16]), "+f"(d[17]), "+f"(d[18]), "+f"(d[19]), "+f"(d[20]), "+f"(d[21]), "+f"(d[22]), "+f"(d[23]), "+f"(d[24]), "+f"(d[25]), "+f"(d[26]), "+f"(d[27]), "+f"(d[28]), "+f"(d[29]), "+f"(d[30]), "+f"(d[31]), "+f"(d[32]), "+f"(d[33]), "+f"(d[34]), "+f"(d[35]), "+f"(d[36]), "+f"(d[37]), "+f"(d[38]), "+f"(d[39]), "+f"(d[40]), "+f"(d[41]), "+f"(d[42]), "+f"(d[43]), "+f"(d[44]), "+f"(d[45]), "+f"(d[46]), "+f"(d[47]), "+f"(d[48]), "+f"(d[49]), "+f"(d[50]), "+f"(d[51]), "+f"(d[52]), "+f"(d[53]), "+f"(d[54]), "+f"(d[55]), "+f"(d[56]), "+f"(d[57]), "+f"(d[58]), "+f"(d[59]), "+f"(d[60]), "+f"(d[61]), "+f"(d[62]), "+f"(d[63])
    : "r"(a0), "r"(a1), "r"(a2), "r"(a3), "r"(b_lo), "r"(scaleD), "n"(OFFB));
}

__device__ __forceinline__ uint4 ldg_nc_v4(const void* p) {
  uint4 v;
    asm volatile("{\n.reg .b64 pol;\ncreatepolicy.fractional.L2::evict_first.b64 pol, 1.0;\n"
                 "ld.global.nc.L1::no_allocate.L2::cache_hint.v4.u32 {%0, %1, %2, %3}, [%4], pol;\n}\n" : "=r"(v.x), "=r"(v.y), "=r"(v.z), "=r"(v.w) : "l"(p));
  return v;
}
__device__ __forceinline__ uint64_t pol_normal() {
  uint64_t p; asm volatile("createpolicy.fractional.L2::evict_normal.b64 %0, 1.0;" : "=l"(p)); return p;
}
__device__ __forceinline__ float rcp_approx(float x) { float y; asm("rcp.approx.ftz.f32 %0, %1;" : "=f"(y) : "f"(x)); return y; }
__device__ __forceinline__ float sigmoid_f(float v) { return rcp_approx(1.0f + ex2_approx(v * -1.4426950408889634f)); }
__device__ __forceinline__ float silu_bf(float v) { return rbf(v * sigmoid_f(v)); }
__device__ __forceinline__ uint32_t rank_key(float r, int idx) {
  const uint32_t b = __float_as_uint(r) >> 16;
  const uint32_t u = (r != r) ? 0u : ((b & 0x8000u) ? (~b & 0xffffu) : (b | 0x8000u));
  return (u << 16) | (0xffffu - (uint32_t)idx);
}
__device__ __forceinline__ void warp_top2(uint32_t& k1, uint32_t& k2) {
  const uint32_t m1 = __reduce_max_sync(0xffffffffu, k1);
  k2 = __reduce_max_sync(0xffffffffu, k1 == m1 ? k2 : k1);
  k1 = m1;
}
__device__ __forceinline__ uint32_t bmul2(uint32_t a, uint32_t b) { uint32_t r; asm("mul.rn.bf16x2 %0, %1, %2;" : "=r"(r) : "r"(a), "r"(b)); return r; }
__device__ __forceinline__ uint32_t badd2(uint32_t a, uint32_t b) { uint32_t r; asm("add.rn.bf16x2 %0, %1, %2;" : "=r"(r) : "r"(a), "r"(b)); return r; }
__device__ __forceinline__ uint32_t bsub2(uint32_t a, uint32_t b) { uint32_t r; asm("sub.rn.bf16x2 %0, %1, %2;" : "=r"(r) : "r"(a), "r"(b)); return r; }
__device__ __forceinline__ float sqrt_approx(float x) { float y; asm("sqrt.approx.f32 %0, %1;" : "=f"(y) : "f"(x)); return y; }
__device__ __forceinline__ uint32_t ln_norm2(uint32_t x1, uint32_t mb2, float inv) {
  const uint32_t d = bsub2(x1, mb2);
  return pack_bf16(bflo(d) * inv, bfhi(d) * inv);
}
__device__ __forceinline__ uint32_t ln_mod2(uint32_t x1, uint32_t mb2, float inv, uint32_t c1, uint32_t sb) { return badd2(bmul2(ln_norm2(x1, mb2, inv), c1), sb); }
__device__ __forceinline__ void ldmatrix_x4(uint32_t addr, uint32_t& r0, uint32_t& r1, uint32_t& r2, uint32_t& r3) {
  asm volatile("ldmatrix.sync.aligned.m8n8.x4.shared.b16 {%0, %1, %2, %3}, [%4];" : "=r"(r0), "=r"(r1), "=r"(r2), "=r"(r3) : "r"(addr) : "memory");
}
__device__ __forceinline__ uint4 ldg_stream_v4(const void* p, uint64_t pol) {
  uint4 v; asm volatile("ld.global.nc.L1::no_allocate.L2::cache_hint.L2::128B.v4.u32 {%0, %1, %2, %3}, [%4], %5;" : "=r"(v.x), "=r"(v.y), "=r"(v.z), "=r"(v.w) : "l"(p), "l"(pol)); return v;
}
__device__ __forceinline__ void bulk_load_hint(uint32_t dst, const void* src, uint32_t bytes, uint32_t bar, uint64_t pol) {
  asm volatile("cp.async.bulk.shared::cluster.global.mbarrier::complete_tx::bytes.L2::cache_hint [%0], [%1], %2, [%3], %4;"
    :: "r"(dst), "l"(src), "r"(bytes), "r"(bar), "l"(pol) : "memory");
}
__device__ __forceinline__ void red_release_add(unsigned int* p, unsigned int v) { asm volatile("red.release.gpu.global.add.u32 [%0], %1;" :: "l"(p), "r"(v) : "memory"); }
__device__ __forceinline__ unsigned int ld_acquire(const unsigned int* p) { unsigned int v; asm volatile("ld.acquire.gpu.global.u32 %0, [%1];" : "=r"(v) : "l"(p) : "memory"); return v; }
__device__ __forceinline__ void spin_until(const unsigned int* p, unsigned int target) {
  #pragma unroll 1
  for (unsigned int i = 0; i < (1u << 22); i++) { if (ld_acquire(p) >= target) return; }
}
__device__ __forceinline__ float lds_f32(uint32_t a) { float v; asm volatile("ld.shared.f32 %0, [%1];" : "=f"(v) : "r"(a) : "memory"); return v; }
__device__ __forceinline__ uint2 lds_u32x2(uint32_t a) { uint2 v; asm volatile("ld.shared.v2.u32 {%0, %1}, [%2];" : "=r"(v.x), "=r"(v.y) : "r"(a) : "memory"); return v; }
__device__ __forceinline__ uint32_t lds_u32(uint32_t a) { uint32_t v; asm volatile("ld.shared.u32 %0, [%1];" : "=r"(v) : "r"(a) : "memory"); return v; }
__device__ __forceinline__ void sts_u32(uint32_t a, uint32_t v) { asm volatile("st.shared.u32 [%0], %1;" :: "r"(a), "r"(v) : "memory"); }
__device__ __forceinline__ void sts_u32x2(uint32_t a, uint32_t x, uint32_t y) { asm volatile("st.shared.v2.u32 [%0], {%1, %2};" :: "r"(a), "r"(x), "r"(y) : "memory"); }
__device__ __forceinline__ void sts_f32(uint32_t a, float v) { asm volatile("st.shared.f32 [%0], %1;" :: "r"(a), "f"(v) : "memory"); }
__device__ __forceinline__ void sts_f32x4(uint32_t a, float x, float y, float z, float w) { asm volatile("st.shared.v4.f32 [%0], {%1, %2, %3, %4};" :: "r"(a), "f"(x), "f"(y), "f"(z), "f"(w) : "memory"); }

__device__ __forceinline__ uint4 lds_u32x4(uint32_t a) { uint4 v; asm volatile("ld.shared.v4.u32 {%0, %1, %2, %3}, [%4];" : "=r"(v.x), "=r"(v.y), "=r"(v.z), "=r"(v.w) : "r"(a) : "memory"); return v; }
__device__ __forceinline__ void sts_u32x4(uint32_t a, uint32_t x, uint32_t y, uint32_t z, uint32_t w) { asm volatile("st.shared.v4.u32 [%0], {%1, %2, %3, %4};" :: "r"(a), "r"(x), "r"(y), "r"(z), "r"(w) : "memory"); }
__device__ __forceinline__ void st_tagged(float* p, float v) {
  const uint32_t b = __float_as_uint(v);
  asm volatile("st.relaxed.gpu.global.u32 [%0], %1;" :: "l"(p), "r"(b == 0u ? 0x80000000u : b) : "memory");
}
__device__ __forceinline__ void st_tagged4(float* p, float x, float y, float z, float w) {
  const uint32_t a = __float_as_uint(x), b = __float_as_uint(y), c = __float_as_uint(z), d = __float_as_uint(w);
  asm volatile("st.relaxed.gpu.global.v4.u32 [%0], {%1, %2, %3, %4};" :: "l"(p), "r"(a == 0u ? 0x80000000u : a), "r"(b == 0u ? 0x80000000u : b),
               "r"(c == 0u ? 0x80000000u : c), "r"(d == 0u ? 0x80000000u : d) : "memory");
}
__device__ __forceinline__ void st_relaxed2(void* p, uint32_t a, uint32_t b) { asm volatile("st.relaxed.gpu.global.v2.u32 [%0], {%1, %2};" :: "l"(p), "r"(a), "r"(b) : "memory"); }
__device__ __forceinline__ float4 ld_tagged4(const float* p) {
  float4 v; asm volatile("ld.relaxed.gpu.global.v4.f32 {%0, %1, %2, %3}, [%4];" : "=f"(v.x), "=f"(v.y), "=f"(v.z), "=f"(v.w) : "l"(p) : "memory"); return v;
}
__device__ __forceinline__ bool tagged4(const float4& v) {
  return __float_as_uint(v.x) != 0u && __float_as_uint(v.y) != 0u && __float_as_uint(v.z) != 0u && __float_as_uint(v.w) != 0u;
}
__device__ __forceinline__ void hint_arrive(uint32_t* p) { asm volatile("red.relaxed.gpu.global.add.u32 [%0], 1;" :: "l"(p) : "memory"); }
__device__ __forceinline__ void hint_wait(const uint32_t* p, uint32_t target) {
  uint32_t v = 0u;
  #pragma unroll 1
  for (unsigned int i = 0; i < (1u << 22) && v < target; i++) asm volatile("ld.relaxed.gpu.global.u32 %0, [%1];" : "=r"(v) : "l"(p) : "memory");
}
__device__ __forceinline__ void fence_proxy_async_global() { asm volatile("fence.proxy.async.global;" ::: "memory"); }

__device__ __forceinline__ void mma_bf16(float (&d)[4], uint32_t a0, uint32_t a1, uint32_t a2, uint32_t a3, uint32_t b0, uint32_t b1) {
  asm volatile("mma.sync.aligned.m16n8k16.row.col.f32.bf16.bf16.f32 {%0, %1, %2, %3}, {%4, %5, %6, %7}, {%8, %9}, {%0, %1, %2, %3};"
               : "+f"(d[0]), "+f"(d[1]), "+f"(d[2]), "+f"(d[3]) : "r"(a0), "r"(a1), "r"(a2), "r"(a3), "r"(b0), "r"(b1));
}
__device__ __forceinline__ uint32_t bfma2(uint32_t a, uint32_t b, uint32_t c) { uint32_t r; asm("fma.rn.bf16x2 %0, %1, %2, %3;" : "=r"(r) : "r"(a), "r"(b), "r"(c)); return r; }
#define XDLY 1000
#define PRE_T 1000
#define GDLY 4150
#define A_T 4800
#define SDLY 5800
#define ST1_T 6000
#define GDLY2 8000
#define WDLY 3800
#define W_OFF 2000
#define W_GAP 300
#define W_RND 3600
#define W_LATE 27000
#define CLR_T 70000
#define SGL_T 79000
#define OG_PRE 12
#define OG_LEN 6
#define WD_0 16
#define WD_S 6
#define NDUM 16
__device__ __forceinline__ uint32_t clock_lo() { uint32_t c; asm volatile("mov.u32 %0, %%clock;" : "=r"(c) :: "memory"); return c; }
__device__ __forceinline__ void wait_clock(uint32_t t0, uint32_t n) {
  #pragma unroll 1
  while (clock_lo() - t0 < n) {}
}
__device__ __forceinline__ void sleep_until(uint32_t t0, uint32_t n) {
  #pragma unroll 1
  while (clock_lo() - t0 < n) __nanosleep(500);
}
__device__ __forceinline__ float2 ld_tagged2(const float2* p) {
  float2 v; asm volatile("ld.relaxed.gpu.global.v2.f32 {%0, %1}, [%2];" : "=f"(v.x), "=f"(v.y) : "l"(p) : "memory"); return v;
}
template <int N>
__device__ __forceinline__ void gemv64(float (&d)[2][4], const uint4 (&w)[N], const uint32_t (&sv)[N / 2], int lane) {
  const int g = lane >> 2;
  const uint32_t lo = (g & 1) ? 0x1044u : 0x4410u, hi = (g & 1) ? 0x3244u : 0x4432u;
  const uint32_t lo0 = g < 2 ? lo : 0x4444u, hi0 = g < 2 ? hi : 0x4444u, lo1 = (g & 6) == 2 ? lo : 0x4444u, hi1 = (g & 6) == 2 ? hi : 0x4444u;
  #pragma unroll
  for (int i = 0; i < N; i++)
    mma_bf16(d[i & 1], w[i].x, w[i].y, w[i].z, w[i].w, __byte_perm(sv[i >> 1], 0u, (i & 1) ? hi0 : lo0), __byte_perm(sv[i >> 1], 0u, (i & 1) ? hi1 : lo1));
}
template <int NW>
__device__ __forceinline__ float gemv64_sum(const float (&d)[2][4], uint32_t scr, int t2) {
  if ((t2 & 2) == 0) sts_f32x4(scr + (t2 >> 2) * 32 + (t2 & 1) * 16, d[0][0] + d[1][0], d[0][1] + d[1][1], d[0][2] + d[1][2], d[0][3] + d[1][3]);
  named_bar_sync(NW == 8 ? 5 : 3, NW * 32);
  float sum = 0.f;
  #pragma unroll
  for (int i = 0; i < NW; i += 2) sum += lds_f32(scr + i * 256 + (t2 & 63) * 4) + lds_f32(scr + i * 256 + 256 + (t2 & 63) * 4);
  return sum;
}
__device__ __forceinline__ uint32_t silu2(uint32_t c) { return pack_bf16(silu_bf(bflo(c)), silu_bf(bfhi(c))); }
__device__ __forceinline__ void head_first(Scratch* hm, uint32_t scr, int t2, const bf16* __restrict__ cvec, const bf16* __restrict__ w_mod) {
  const int row = (blockIdx.x >> 3) * 64 + (t2 >> 5) * 16 + (t2 & 3) * 4;
  const bf16* wp = w_mod + (size_t)row * (6 * T_D) + (blockIdx.x & 4) * 256 + (blockIdx.x & 3) * 64 + (t2 & 28) * 2;
  uint4 w[4];
  #pragma unroll
  for (int i = 0; i < 4; i++) w[i] = ldg_nc_v4(wp + i * 6 * T_D);
  const uint2 c = *reinterpret_cast<const uint2*>(cvec + row);
  const uint32_t sv[2] = {silu2(c.x), silu2(c.y)};
  float d[2][4] = {{0.f, 0.f, 0.f, 0.f}, {0.f, 0.f, 0.f, 0.f}};
  gemv64<4>(d, w, sv, t2 & 31);
  const float sum = gemv64_sum<4>(d, scr, t2);
  if (t2 < 64) st_tagged(hm->modu + (blockIdx.x >> 3) * 512 + (blockIdx.x & 7) * 64 + t2, sum);
  HS(1);
}
__device__ __forceinline__ void head_stats(Scratch* hm, uint32_t xs, uint32_t b_x, int tid) {
  const int lane = tid & 31, w = tid >> 5, g = lane >> 2;
  float d[4][4] = {{0.f, 0.f, 0.f, 0.f}, {0.f, 0.f, 0.f, 0.f}, {0.f, 0.f, 0.f, 0.f}, {0.f, 0.f, 0.f, 0.f}};
  const uint32_t xa = xs + ((w & 1) * 8 + g) * 2048 + (w >> 1) * 1024 + (g & 1) * 64 + (lane & 3) * 16;
  float2* dst = hm->stat + ((blockIdx.x * 2 + (w & 1)) * 2 + (w >> 1)) * 8 + g;
  mbar_wait(b_x, 0);
  #pragma unroll
  for (int j = 0; j < 16; j++) {
    const uint4 v = lds_u32x4((xa ^ ((j & 1) * 64)) + (j >> 1) * 128);
    mma_bf16(d[2 * (j & 1)], v.x, 0x3F803F80u, v.y, 0x3F803F80u, v.x, v.y);
    mma_bf16(d[2 * (j & 1) + 1], v.z, 0x3F803F80u, v.w, 0x3F803F80u, v.z, v.w);
  }
  #pragma unroll
  for (int e = 0; e < 4; e++) d[0][e] = (d[0][e] + d[1][e]) + (d[2][e] + d[3][e]);
  const uint32_t sm = __float_as_uint((g & 1) ? d[0][3] : d[0][2]), sq = __float_as_uint((g & 1) ? d[0][1] : d[0][0]);
  if ((lane & 3) == (g >> 1)) st_relaxed2(dst, sm == 0u ? 0x80000000u : sm, sq == 0u ? 0x80000000u : sq);
  HSD(3, sm);
}
__device__ __forceinline__ void put_table(uint32_t tab, int l, bool ca, const float4& v) {
  uint32_t m0 = pack_bf16(v.x, v.y), m1 = pack_bf16(v.z, v.w);
  if (ca) { m0 = badd2(m0, 0x3F803F80u); m1 = badd2(m1, 0x3F803F80u); }
  tab += (l >> 2) * 64 + (l & 1) * 32 + (l & 2) * 2 + (ca ? 0 : 8);
  sts_u32(tab, m0); sts_u32(tab + 16, m1);
}
__device__ __forceinline__ void head_gather(Scratch* hm, uint32_t tab, int tid) {
  float4 p[16];
  #pragma unroll 1
  for (unsigned int spin = 0; spin < (1u << 22); spin++) {
    uint32_t m = 0xffffffffu;
    #pragma unroll
    for (int k = 0; k < 16; k++) p[k] = ld_tagged4(hm->modu + k * 512 + tid * 4);
    #pragma unroll
    for (int k = 0; k < 16; k++) m = min(min(m, min(__float_as_uint(p[k].x), __float_as_uint(p[k].y))), min(__float_as_uint(p[k].z), __float_as_uint(p[k].w)));
    if (m != 0u) break;
  }
  #pragma unroll
  for (int o = 1; o < 16; o <<= 1)
    #pragma unroll
    for (int k = 0; k < 16; k += 2 * o) { p[k].x += p[k + o].x; p[k].y += p[k + o].y; p[k].z += p[k + o].z; p[k].w += p[k + o].w; }
  put_table(tab, tid & 63, tid >= 64, p[0]);
  __syncwarp();
  HS(2);
}
__device__ __forceinline__ uint32_t ln_stat(float sm, float sq) {
  const float mean = sm * (1.0f / T_D), var = fmaxf(fmaf(-mean, mean, sq * (1.0f / T_D)), 0.f);
  return pack_bf16(mean, sqrt_approx(rbf(rbf(var) + 1e-05f)));
}
__device__ __forceinline__ void gather_table(Scratch* hm, uint32_t tab0, uint32_t b_tab, int a, int lane) {
  #pragma unroll 1
  for (int r = 2; r < 8; r++) {
    float4 v;
    #pragma unroll 1
    for (unsigned int spin = 0; spin < (1u << 22); spin++) {
      v = ld_tagged4(hm->mod + a * T_D + r * 128 + lane * 4);
      if (__all_sync(0xffffffffu, tagged4(v))) break;
      __nanosleep(50);
    }
    put_table(tab0 + r * 512, lane, a, v);
    __syncwarp();
    if (lane == 0) mbar_arrive(b_tab + 8 * r);
    if (r < 6) HS(2 + r);
  }
}

__device__ __forceinline__ uint32_t assign_tile(Scratch* hm, uint32_t t0, int lane) {
  uint32_t me; asm("mov.u32 %0, %%smid;" : "=r"(me));
  me = (me & 255u) + 1u;
  if (lane == 0) asm volatile("st.relaxed.gpu.global.u32 [%0], %1;" :: "l"(hm->gkey + blockIdx.x), "r"((t0 & ~511u) | me) : "memory");
  uint32_t k[5];
  #pragma unroll 1
  for (unsigned int spin = 0; spin < (1u << 20); spin++) {
    __nanosleep(200);
    #pragma unroll
    for (int m = 0; m < 5; m++) asm volatile("ld.relaxed.gpu.global.u32 %0, [%1];" : "=r"(k[m]) : "l"(hm->gkey + m * 32 + lane) : "memory");
    if (__all_sync(0xffffffffu, k[0] != 0u && k[1] != 0u && k[2] != 0u && k[3] != 0u && (k[4] != 0u || lane >= 4))) break;
  }
  uint32_t sz = 0u, g = 0u, rank = 0u, w[5];
  #pragma unroll
  for (int m = 0; m < 5; m++) w[m] = k[m] == 0u ? 0u : (k[m] & 511u) < me ? 257u : (k[m] & 511u) == me ? 65537u : 1u;
  #pragma unroll 1
  for (int i = 0; i < 16; i++) {
    const uint32_t v = __reduce_max_sync(0xffffffffu, max(max(max(k[0], k[1]), max(k[2], k[3])), k[4])), lo = (i == 15 || v < 2048u) ? 0u : v - 2048u;
    uint32_t n = 0u;
    #pragma unroll
    for (int m = 0; m < 5; m++) { const bool in = k[m] >= lo; n += in ? w[m] : 0u; w[m] = in ? 0u : w[m]; k[m] = in ? 0u : k[m]; }
    n = __reduce_add_sync(0xffffffffu, n);
    if (lane == i) sz = n & 255u;
    if (n >> 16) { g = i; rank = (n >> 8) & 255u; }
  }
  #pragma unroll 1
  for (int d = 0; d < 4; d += 2)
    if ((__reduce_max_sync(0xffffffffu, sz * 32u + lane) & 31u) == (uint32_t)lane) sz -= 2;
  const uint32_t gs = __shfl_sync(0xffffffffu, sz, g);
  const uint32_t off = __reduce_add_sync(0xffffffffu, (sz != 16u) * 32u + lane < (gs != 16u) * 32u + g ? sz : 0u);
  return rank < gs ? off + rank : 128u;
}

__device__ __forceinline__ int col_pos(int c) { return (c & ~31) + ((c >> 1) & 3) * 8 + ((c >> 3) & 3) * 2 + (c & 1); }
__device__ __forceinline__ int mod_col0(int j, int b) { return b < 0 ? (j & 1) * T_D + (b + 4) * 256 + ((j >> 1) ^ 2) * 64 : 2 * T_D + j * 512 + b * 64; }
__device__ __noinline__ void mod_rest(Scratch* hm, uint32_t t0, uint32_t sbase, uint32_t bar, int t2, int j, const bf16* __restrict__ cvec, const bf16* __restrict__ w_r) {
  const uint32_t scr = sbase + 4 * 32768 + 8192;
  const int kind = j >> 1;
  const uint2 c4 = *reinterpret_cast<const uint2*>(cvec + t2 * 4);
  sts_u32x2(scr + t2 * 8, silu2(c4.x), silu2(c4.y));
  const int w8 = t2 >> 5, t = t2 & 3, g = (t2 >> 2) & 7;
  float dot = 0.f;
  uint32_t buf = 0, par = 0;
  named_bar_sync(5, 256);
  #pragma unroll 1
  for (int b = -3; b < 8; b++) {
    float d[2][4] = {{0.f, 0.f, 0.f, 0.f}, {0.f, 0.f, 0.f, 0.f}};
    #pragma unroll 1
    for (int k = 0; k < 4; k++) {
      const uint32_t wa = sbase + (buf + (buf > 2 ? 2 : 0)) * 32768 + w8 * 4096 + t * 256;
      uint4 w[8];
      uint32_t sv[4];
      #pragma unroll
      for (int i = 0; i < 4; i++) sv[i] = lds_u32(scr + k * 512 + w8 * 64 + i * 16 + t * 4);
      mbar_wait(bar + buf * 8, par);
      #pragma unroll
      for (int i = 0; i < 8; i++) w[i] = lds_u32x4(wa + (i >> 1) * 1024 + (i & 1) * 128 + ((g ^ (t * 2 + (i & 1))) << 4));
      gemv64<8>(d, w, sv, t2 & 31);
      named_bar_sync(5, 256);
      if (t2 == 0) sts_u32(bar + 40, b * 4 + k + 18);
      if (++buf == 5) { buf = 0; par ^= 1; }
    }
    const int c0 = mod_col0(j, b);
    float v = gemv64_sum<8>(d, scr + 2048, t2);
    if (t2 < 64) {
      if (b < 0) st_tagged(hm->mod + c0 + t2, v);
      else {
        const int col = (c0 + t2) & 1023;
        uint8_t* dst = g_col + (col >> 7) * 1536;
        v = rbf(v);
        if (kind == 2) v = rbf(1.0f + v);
        const float vw = v * __bfloat162float(w_r[col]);
        dot += vw;
        if (kind == 2) {
          reinterpret_cast<bf16*>(dst)[col_pos(col & 127)] = __float2bfloat16_rn(vw);
          reinterpret_cast<bf16*>(dst)[128 + col_pos(col & 127)] = __float2bfloat16_rn(vw - rbf(vw));
        }
        reinterpret_cast<bf16*>(dst + 512 + (kind == 0 ? 0 : kind == 2 ? 256 : kind == 1 ? 512 : 768))[col_pos(col & 127)] = __float2bfloat16_rn(v);
      }
    }
  }
  #pragma unroll
  for (int o = 16; o > 0; o >>= 1) dot += __shfl_xor_sync(0xffffffffu, dot, o);
  if (t2 == 32) sts_f32(scr + 4096, dot);
  fence_proxy_async();
  named_bar_sync(5, 256);
  if (t2 == 0 && (kind == 1 || kind == 2)) g_scal[(kind == 2 ? 0 : 2) + (j & 1)] = dot + lds_f32(scr + 4096);
  sleep_until(t0, CLR_T);
  #pragma unroll 1
  for (int i = j * 256 + t2; i < (int)(sizeof(TailMail) / 16); i += 8 * 256) reinterpret_cast<uint4*>(&hm->mail)[i] = make_uint4(0u, 0u, 0u, 0u);
  named_bar_sync(5, 256);
  if (t2 == 0) red_release_add(&g_hcnt[0], 1u);
  sleep_until(t0, SGL_T);
}

constexpr int AT_NBLK = T_SEQ / 128;
constexpr float AT_HEAD = 7.0f;
#define WOL 12
constexpr int WO_LATE = WOL;
#define QSTG 3
constexpr int QP_STAG = QSTG;
constexpr int AT_SPLIT = 28, AT_PIN = 8, PINB = 4;
constexpr int AT_NFULL = 124;
constexpr int AT_PREG = 40, AT_CREG = 232;
constexpr uint32_t AT_SQ = 5 * 32768;
constexpr float AT_C = 0.08838834764831845f * 1.4426950408889634f;
constexpr float AT_RAW_LO = -16.0f, AT_RAW_HI = 24.0f;
constexpr float AT_RAW_SUM = 281474976710656.0f, AT_RAW_MIN = 9.094947017729282e-13f;
constexpr uint32_t AT_SBAR = AT_SQ + 65536 + 256;
constexpr uint32_t AT_SMEM = AT_SQ + 65536 + 3072;

__device__ __forceinline__ uint32_t ring_slot(uint32_t t) { return t - 5u * ((t * 205u) >> 10); }
__device__ __forceinline__ uint32_t qp_pos(uint32_t j, uint32_t it) { return 4u * it + (j & 3u) + ((j & 3u) == 3u ? it : 0u); }
__device__ __forceinline__ uint32_t ring_par(uint32_t t) { return ((t * 205u) >> 10) & 1u; }
__device__ __forceinline__ void softmax_rowmax(const float (&s)[64], float& mx0, float& mx1) {
  float a0 = fmaxf(s[0], s[1]), a1 = fmaxf(s[4], s[5]), a2 = fmaxf(s[8], s[9]), a3 = fmaxf(s[12], s[13]);
  float b0 = fmaxf(s[2], s[3]), b1 = fmaxf(s[6], s[7]), b2 = fmaxf(s[10], s[11]), b3 = fmaxf(s[14], s[15]);
  #pragma unroll
  for (int j = 4; j < 16; j += 4) {
    a0 = fmaxf(a0, fmaxf(s[4 * j + 0], s[4 * j + 1]));  b0 = fmaxf(b0, fmaxf(s[4 * j + 2], s[4 * j + 3]));
    a1 = fmaxf(a1, fmaxf(s[4 * j + 4], s[4 * j + 5]));  b1 = fmaxf(b1, fmaxf(s[4 * j + 6], s[4 * j + 7]));
    a2 = fmaxf(a2, fmaxf(s[4 * j + 8], s[4 * j + 9]));  b2 = fmaxf(b2, fmaxf(s[4 * j + 10], s[4 * j + 11]));
    a3 = fmaxf(a3, fmaxf(s[4 * j + 12], s[4 * j + 13])); b3 = fmaxf(b3, fmaxf(s[4 * j + 14], s[4 * j + 15]));
  }
  mx0 = fmaxf(fmaxf(a0, a1), fmaxf(a2, a3));
  mx1 = fmaxf(fmaxf(b0, b1), fmaxf(b2, b3));
  mx0 = fmaxf(mx0, __shfl_xor_sync(0xffffffffu, mx0, 1));
  mx1 = fmaxf(mx1, __shfl_xor_sync(0xffffffffu, mx1, 1));
  mx0 = fmaxf(mx0, __shfl_xor_sync(0xffffffffu, mx0, 2));
  mx1 = fmaxf(mx1, __shfl_xor_sync(0xffffffffu, mx1, 2));
}
__device__ __forceinline__ void softmax_sub(float (&s)[64], float mc0, float mc1) {
  #pragma unroll
  for (int j = 0; j < 16; j++) { s[4 * j] -= mc0; s[4 * j + 1] -= mc0; s[4 * j + 2] -= mc1; s[4 * j + 3] -= mc1; }
}
template <int LO, int HI>
__device__ __forceinline__ void softmax_exp(float (&s)[64]) {
  #pragma unroll
  for (int i = LO; i < HI; i++) s[i] = ex2_approx(s[i]);
}
__device__ __forceinline__ bool softmax_mode(const float (&s)[64], float& mc0, float& mc1) {
  softmax_rowmax(s, mc0, mc1);
  const bool raw = __all_sync(0xffffffffu, mc0 >= AT_RAW_LO && mc0 <= AT_RAW_HI && mc1 >= AT_RAW_LO && mc1 <= AT_RAW_HI);
  mc0 += AT_HEAD; mc1 += AT_HEAD;
  return raw;
}
__device__ __forceinline__ void rowsum_p(const uint32_t (&p)[32], uint32_t& t0, uint32_t& t1) {
  uint32_t a[16];
  #pragma unroll
  for (int i = 0; i < 8; i++) { a[2 * i] = badd2(p[4 * i], p[4 * i + 2]); a[2 * i + 1] = badd2(p[4 * i + 1], p[4 * i + 3]); }
  #pragma unroll
  for (int i = 0; i < 4; i++) { a[2 * i] = badd2(a[4 * i], a[4 * i + 2]); a[2 * i + 1] = badd2(a[4 * i + 1], a[4 * i + 3]); }
  t0 = badd2(badd2(a[0], a[2]), badd2(a[4], a[6]));
  t1 = badd2(badd2(a[1], a[3]), badd2(a[5], a[7]));
}
__device__ __forceinline__ void add_rowsum(const uint32_t (&p)[32], float& l0, float& l1) {
  uint32_t t0, t1;
  rowsum_p(p, t0, t1);
  l0 += bflo(t0) + bfhi(t0); l1 += bflo(t1) + bfhi(t1);
}
__device__ __forceinline__ void pack_p(uint32_t (&p)[32], const float (&s)[64]) {
  #pragma unroll
  for (int i = 0; i < 32; i++) p[i] = pack_bf16(s[2 * i], s[2 * i + 1]);
}
__device__ __noinline__ void attn_rows_exact(uint32_t sq, int warp, int lane, const bf16* __restrict__ kh, const bf16* __restrict__ vh) {
  #pragma unroll 1
  for (int r = 16 * warp; r < 16 * warp + 16; r++) {
    const uint32_t ad = (lane >> 4) * 16384 + r * 128 + ((((lane & 15) >> 1) ^ (r & 7)) << 4) + (lane & 1) * 8;
    uint2 qv; asm volatile("ld.shared.v2.u32 {%0, %1}, [%2];" : "=r"(qv.x), "=r"(qv.y) : "r"(sq + ad) : "memory");
    const float q0 = bflo(qv.x), q1 = bfhi(qv.x), q2 = bflo(qv.y), q3 = bfhi(qv.y);
    float m = -INFINITY, l = 0.f, o0 = 0.f, o1 = 0.f, o2 = 0.f, o3 = 0.f;
    #pragma unroll 1
    for (int key = 0; key < T_SEQ; key++) {
      const uint2 kv = *reinterpret_cast<const uint2*>(kh + (size_t)key * T_DH + lane * 4);
      const uint2 vv = *reinterpret_cast<const uint2*>(vh + (size_t)key * T_DH + lane * 4);
      float sc = (q0 * bflo(kv.x) + q1 * bfhi(kv.x)) + (q2 * bflo(kv.y) + q3 * bfhi(kv.y));
      #pragma unroll
      for (int o = 16; o > 0; o >>= 1) sc += __shfl_xor_sync(0xffffffffu, sc, o);
      const float mn = fmaxf(m, sc);
      const float al = (m == mn) ? 1.0f : ex2_approx(m - mn), p = rbf(ex2_approx(sc - mn));
      m = mn;
      l = fmaf(l, al, p);
      o0 = fmaf(o0, al, p * bflo(vv.x)); o1 = fmaf(o1, al, p * bfhi(vv.x));
      o2 = fmaf(o2, al, p * bflo(vv.y)); o3 = fmaf(o3, al, p * bfhi(vv.y));
    }
    const float inv = rcp_approx(l);
    asm volatile("st.shared.v2.u32 [%0], {%1, %2};" :: "r"(sq + ad), "r"(pack_bf16(o0 * inv, o1 * inv)), "r"(pack_bf16(o2 * inv, o3 * inv)) : "memory");
  }
}
__device__ __forceinline__ void issue_qk(float (&s)[64], const uint32_t (&q)[32], uint32_t k_lo) {
  wgmma_fence();
  wgmma_m64n128k16_rs<0>(s, q[0], q[1], q[2], q[3], k_lo, 0);
  wgmma_m64n128k16_rs<2>(s, q[4], q[5], q[6], q[7], k_lo, 1);
  wgmma_m64n128k16_rs<4>(s, q[8], q[9], q[10], q[11], k_lo, 1);
  wgmma_m64n128k16_rs<6>(s, q[12], q[13], q[14], q[15], k_lo, 1);
  wgmma_m64n128k16_rs<1024>(s, q[16], q[17], q[18], q[19], k_lo, 1);
  wgmma_m64n128k16_rs<1026>(s, q[20], q[21], q[22], q[23], k_lo, 1);
  wgmma_m64n128k16_rs<1028>(s, q[24], q[25], q[26], q[27], k_lo, 1);
  wgmma_m64n128k16_rs<1030>(s, q[28], q[29], q[30], q[31], k_lo, 1);
  wgmma_commit();
}
__device__ __forceinline__ void issue_pv(float (&o)[64], const uint32_t (&p)[32], uint32_t v_lo, int accumulate) {
  wgmma_fence();
  wgmma_m64n128k16_rs_tb<0>(o, p[0], p[1], p[2], p[3], v_lo, accumulate);
  wgmma_m64n128k16_rs_tb<128>(o, p[4], p[5], p[6], p[7], v_lo, 1);
  wgmma_m64n128k16_rs_tb<256>(o, p[8], p[9], p[10], p[11], v_lo, 1);
  wgmma_m64n128k16_rs_tb<384>(o, p[12], p[13], p[14], p[15], v_lo, 1);
  wgmma_m64n128k16_rs_tb<512>(o, p[16], p[17], p[18], p[19], v_lo, 1);
  wgmma_m64n128k16_rs_tb<640>(o, p[20], p[21], p[22], p[23], v_lo, 1);
  wgmma_m64n128k16_rs_tb<768>(o, p[24], p[25], p[26], p[27], v_lo, 1);
  wgmma_m64n128k16_rs_tb<896>(o, p[28], p[29], p[30], p[31], v_lo, 1);
  wgmma_commit();
}
__device__ __forceinline__ void rescale_o(float (&o)[64], float al0, float al1) {
  #pragma unroll
  for (int j = 0; j < 16; j++) { o[4 * j] *= al0; o[4 * j + 1] *= al0; o[4 * j + 2] *= al1; o[4 * j + 3] *= al1; }
}

__device__ __forceinline__ void stage_o(const float (&o)[64], float i0, float i1, uint32_t dst, int lane) {
  #pragma unroll
  for (int J = 0; J < 16; J += 2)
    stmatrix_x4(dst + (J >> 3) * 16384 + ((((J & 7) + (lane >> 4)) ^ (lane & 7)) << 4),
                pack_bf16(o[4 * J + 0] * i0, o[4 * J + 1] * i0), pack_bf16(o[4 * J + 2] * i1, o[4 * J + 3] * i1),
                pack_bf16(o[4 * J + 4] * i0, o[4 * J + 5] * i0), pack_bf16(o[4 * J + 6] * i1, o[4 * J + 7] * i1));
}
__device__ __forceinline__ bool finish_l(float& l0, float& l1) {
  l0 += __shfl_xor_sync(0xffffffffu, l0, 1); l1 += __shfl_xor_sync(0xffffffffu, l1, 1);
  l0 += __shfl_xor_sync(0xffffffffu, l0, 2); l1 += __shfl_xor_sync(0xffffffffu, l1, 2);
  const bool redo = __any_sync(0xffffffffu, !(l0 <= AT_RAW_SUM && l1 <= AT_RAW_SUM && l0 >= AT_RAW_MIN && l1 >= AT_RAW_MIN));
  const float r = rcp_approx(l0 * l1), i0 = r * l1;
  l1 = r * l0; l0 = i0;
  return redo;
}
__device__ __forceinline__ void stage_qregs(const uint32_t (&q)[32], uint32_t dst, int lane) {
  #pragma unroll
  for (int J = 0; J < 16; J += 2)
    stmatrix_x4(dst + (J >> 3) * 16384 + ((((J & 7) + (lane >> 4)) ^ (lane & 7)) << 4), q[2 * J], q[2 * J + 1], q[2 * J + 2], q[2 * J + 3]);
}
__device__ __forceinline__ void store_o(const CUtensorMap* tmO, uint32_t src, int head, int row) {
  tma_store_2d(tmO, src, head * T_DH, row);
  tma_store_2d(tmO, src + 16384, head * T_DH + 64, row);
  bulk_commit();
}
struct GemvSel { uint32_t lo0, hi0, lo1, hi1; };
__device__ __forceinline__ GemvSel gemv_sel(int lane) {
  const uint32_t lo = (lane & 8) ? 0x1044u : 0x4410u, hi = (lane & 8) ? 0x3244u : 0x4432u;
  GemvSel s; s.lo0 = (lane & 16) ? 0x4444u : lo; s.hi0 = (lane & 16) ? 0x4444u : hi; s.lo1 = (lane & 16) ? lo : 0x4444u; s.hi1 = (lane & 16) ? hi : 0x4444u;
  return s;
}
#define GEMV_B0(j, h, s) __byte_perm((j) < 2 ? (h).x : (h).y, 0u, ((j) & 1) ? (s).hi0 : (s).lo0)
#define GEMV_B1(j, h, s) __byte_perm((j) < 2 ? (h).x : (h).y, 0u, ((j) & 1) ? (s).hi1 : (s).lo1)
__device__ __forceinline__ float4 gemv_out(const float (&d)[4], int lane) {
  const bool tk = lane & 1;
  const float r0 = __shfl_xor_sync(0xffffffffu, tk ? d[0] : d[1], 1), r1 = __shfl_xor_sync(0xffffffffu, tk ? d[2] : d[3], 1);
  return tk ? make_float4(r0, d[1], r1, d[3]) : make_float4(d[0], r0, d[2], r1);
}
#define OG_NG 8
#define OG_GRP (64 / OG_NG)
constexpr int OG_ST = 5, OG_NKB = T_DQKV / 64, OG_MOE = T_F / 32;
constexpr int OG_POS = 7;
constexpr uint32_t OG_STAGE = 32768;
constexpr uint32_t OG_SWD = AT_SQ;
constexpr uint32_t OG_SCOL = AT_SBAR + 512;
constexpr uint32_t OG_SMISC = AT_SBAR + 2048;
constexpr uint32_t OG_XSLOT = ((OG_POS + OG_NKB) % OG_ST) * OG_STAGE;
constexpr uint32_t OG_OSLOT = ((OG_POS + OG_NKB + 1) % OG_ST) * OG_STAGE;
constexpr uint32_t OG_SH2 = ((OG_POS + OG_NKB + 2) % OG_ST) * OG_STAGE;
constexpr uint32_t OG_SRED = ((OG_POS + OG_NKB + 3) % OG_ST) * OG_STAGE;
constexpr uint32_t OG_SSTAT = OG_SRED + 16384;
constexpr uint32_t OG_SGU = OG_SRED + 8192;
constexpr uint32_t OG_SFIN = OG_SGU + 256;
#define OGM 2
#define OG_MT(b) ((((b) >> OGM) & 15) ^ (((b) & 64) ? 15 : 0))
#define OG_NT(b) (((b) & ((1 << OGM) - 1)) + (((b) >> (4 + OGM)) << OGM))
#define TAIL_SETUP \
  const uint32_t bar_full = sbase + AT_SBAR, bar_empty = bar_full + 40; \
  const uint32_t bar_wd = bar_full + 168, bar_col = bar_full + 176, bar_out = bar_full + 184, bar_end = bar_full + 192; \
  const uint32_t bar_key = bar_full + 200, bar_h2 = bar_full + 208, bar_sel = bar_full + 216; \
  const int mt = OG_MT(bx), nt = OG_NT(bx); \
  const int m0 = mt * 128, n0 = nt * 128; \
  const bool has_moe = (int)bx < OG_MOE; \
  (void)bar_empty; (void)bar_wd; (void)bar_col; (void)bar_out; (void)bar_end; (void)bar_key; (void)bar_h2; (void)bar_sel; (void)m0; (void)n0; (void)has_moe;

__device__ __forceinline__ void tail_producer(Scratch* hm, uint32_t bx, uint32_t sbase, uint32_t ph, uint32_t obpar, uint64_t pol, const CUtensorMap* tmA, const CUtensorMap* tmB,
                                              const CUtensorMap* tmX, const bf16* __restrict__ w_down) {
  TAIL_SETUP
  const uint32_t b_ob = bar_full + 96, b_acq = bar_full + 256;
  uint32_t stage = OG_ST, wdd = sbase + OG_SWD;
  int wdk = has_moe ? WD_0 : 99;
  const uint8_t* wdp = (const uint8_t*)w_down + (size_t)bx * 65536;
  if (has_moe) mbar_expect_tx(bar_wd, 65536);
  mbar_expect_tx(bar_col, 1536 + 16);
  #pragma unroll 1
  for (int kb = 0; kb <= OG_NKB; kb++) {
    const uint32_t fb = bar_full + (kb ? 8 * stage : 248), sa = sbase + stage * OG_STAGE, sb = sa + 16384;
    mbar_wait(bar_empty + 8 * stage, kb ? ph : obpar);
    mbar_expect_tx(fb, OG_STAGE);
    if (kb < OG_NKB) {
      tma_load_2d_hint(sb, tmB, n0, kb * 64, fb, pol);
      tma_load_2d_hint(sb + 8192, tmB, n0 + 64, kb * 64, fb, pol);
      if ((kb & 31) == 0) { mbar_wait(b_acq + (kb >> 2), 0); fence_proxy_async_global(); }
      tma_load_2d_hint(sa, tmA, kb * 64, m0, fb, pol);
    } else {
      tma_load_2d_hint(sa, tmX, n0, m0, fb, pol);
      tma_load_2d_hint(sb, tmX, n0 + 64, m0, fb, pol);
    }
    if (kb == 32) {
      bulk_load_hint(sbase + OG_SCOL, g_col + nt * 1536, 1536, bar_col, pol);
      bulk_load_hint(sbase + OG_SMISC, g_scal, 16, bar_col, pol);
    }
    if (kb == wdk && kb < WD_0 + 8 * WD_S) {
      if (kb == WD_0) mbar_wait(b_ob, obpar);
      bulk_load_hint(wdd, wdp, 8192, bar_wd, pol);
      wdp += 8192; wdd += 8224; wdk += WD_S;
    }
    if (++stage == OG_ST) { stage = 0; ph ^= 1; }
    if (kb == 0) stage = (OG_POS + 1) % OG_ST;
  }
}

__device__ __forceinline__ uint32_t out2(uint32_t x1, uint32_t mb2, uint32_t ih, uint32_t il, uint32_t c1, uint32_t sb, uint32_t gb) {
  const uint32_t d = bsub2(x1, mb2);
  return bfma2(gb, bfma2(bfma2(d, ih, bmul2(d, il)), c1, sb), x1);
}
__device__ __forceinline__ void tail_exchange(Scratch* hm, uint32_t bx, uint32_t sbase, int wid, uint32_t tx, const CUtensorMap* tmOut, bf16* __restrict__ out) {
    TAIL_SETUP
    mbar_wait(bar_end, 0);
    const int lane = tx & 31;
    TL_MARK2(22, lane == 0);
    if (tx == 96) PF(5);
    if (wid == 0) {
      uint32_t k1 = 0u, k2 = 0u;
      #pragma unroll 1
      for (unsigned int spin = 0; spin < (1u << 22); spin++) {
        if (k1 == 0u) asm volatile("ld.relaxed.gpu.global.u32 %0, [%1];" : "=r"(k1) : "l"(g_key + lane) : "memory");
        if (__all_sync(0xffffffffu, k1 != 0u)) break;
      }
      TS(6, lane == 0);
      warp_top2(k1, k2);
      if (lane == 0) {
        const uint32_t r1 = 0xffffu - (k1 & 0xffffu), r2 = 0xffffu - (k2 & 0xffffu);
        sts_u32x4(sbase + OG_SMISC + 64, k1, k2, (r1 >> 7) * 2, (r2 >> 7) * 2 + ((r1 >> 7) == (r2 >> 7)));
        mbar_arrive(bar_sel);
      }
    } else if (wid < 3) {
      const uint32_t ch = lane & 15, ca = sbase + OG_SCOL + 768 + (ch >> 2) * 64 + (ch & 3) * 4;
      const uint4 c1 = make_uint4(lds_u32(ca), lds_u32(ca + 16), lds_u32(ca + 32), lds_u32(ca + 48)), sh = make_uint4(lds_u32(ca + 256), lds_u32(ca + 272), lds_u32(ca + 288), lds_u32(ca + 304));
      float* dst = reinterpret_cast<float*>(g_cand + (mt * 2 + (lane >> 4)) * 256 + nt * 16 + ch);
      mbar_wait(bar_key, 0);
      const uint4 kk = lds_u32x4(sbase + OG_SSTAT + 1024 + lane * 16);
      uint32_t k1 = max(kk.x, kk.y), k2 = min(kk.x, kk.y);
      k2 = max(max(k2, min(kk.z, kk.w)), min(k1, max(kk.z, kk.w))); k1 = max(k1, max(kk.z, kk.w));
      warp_top2(k1, k2);
      if (wid == 1) {
        if (lane == 0 && nt == (mt & 7)) st_relaxed2(g_key + mt * 2, k1, k2);
        TS(4, lane == 0);
      } else {
        const uint32_t r = (~((lane & 16) ? k2 : k1)) & 127u;
        const uint2 st = lds_u32x2(sbase + OG_SSTAT + r * 8);
        const uint4 xc = lds_u32x4(sbase + OG_XSLOT + (ch >> 3) * 16384 + r * 128 + (((ch ^ r) & 7) << 4));
        const float inr = __uint_as_float(st.y);
        const float h0 = __uint_as_float(ln_mod2(xc.x, st.x, inr, c1.x, sh.x)), h1 = __uint_as_float(ln_mod2(xc.y, st.x, inr, c1.y, sh.y));
        const float h2 = __uint_as_float(ln_mod2(xc.z, st.x, inr, c1.z, sh.z)), h3 = __uint_as_float(ln_mod2(xc.w, st.x, inr, c1.w, sh.w));
        st_tagged4(dst + 512, h0, h1, h2, h3);
        st_tagged4(dst, __uint_as_float(xc.x), __uint_as_float(xc.y), __uint_as_float(xc.z), __uint_as_float(xc.w));
      }
    }
    mbar_wait(bar_sel, 0);
    mbar_wait(bar_out, 0);
    {
      const int sel0 = 0xffff - (lds_u32(sbase + OG_SMISC + 64) & 0xffffu), sel1 = 0xffff - (lds_u32(sbase + OG_SMISC + 68) & 0xffffu);
      if ((sel0 >> 7) == mt || (sel1 >> 7) == mt) {
        #pragma unroll 2
        for (int i = 0; i < 16; i++) {
          const int r = i * 8 + (tx >> 4), ch = tx & 15;
          if (m0 + r != sel0 && m0 + r != sel1)
            *reinterpret_cast<uint4*>(out + (size_t)(m0 + r) * T_D + n0 + ch * 8) =
                lds_u32x4(sbase + OG_OSLOT + (ch >> 3) * 16384 + r * 128 + (((ch & 7) ^ (r & 7)) << 4));
        }
      } else if (tx == 96) {
        tma_store_2d(tmOut, sbase + OG_OSLOT, n0, m0);
        tma_store_2d(tmOut, sbase + OG_OSLOT + 16384, n0 + 64, m0);
        bulk_commit();
      }
      __syncwarp();
    }
    {
      const int tk = bx >> 6, c0 = (bx & 63) * 16;
      const uint32_t gb2 = *reinterpret_cast<const uint32_t*>(g_col + (c0 >> 7) * 1536 + 512 + 768 + col_pos((c0 & 127) + (tx & 14)) * 2);
      const float* src = g_ypart + (size_t)((tx >> 2) * 2 + tk) * T_D + c0 + (tx & 3) * 4;
      const bool four = tx < (OG_MOE - 96) * 4;
      mbar_wait(bar_h2, 0);
      float fx = 0.f, fh = 0.f, rs = 0.f;
      bf16* op = out;
      if (wid == 1) {
        const uint32_t key = lds_u32(sbase + OG_SMISC + 64 + tk * 4);
        const uint32_t* xp = reinterpret_cast<const uint32_t*>(g_cand + lds_u32(sbase + OG_SMISC + 72 + tk * 4) * 256) + ((c0 + (tx & 14)) >> 1);
        uint32_t x2 = 0u;
        #pragma unroll 1
        for (unsigned int spin = 0; spin < (1u << 20); spin++) { asm volatile("ld.relaxed.gpu.global.u32 %0, [%1];" : "=r"(x2) : "l"(xp) : "memory"); if (__all_sync(0xffffffffu, x2 != 0u)) break; }
        const uint32_t h2p = lds_u32(sbase + OG_SH2 + tk * 2048 + (c0 + (tx & 14)) * 2);
        fx = (lane & 1) ? bfhi(x2) : bflo(x2); fh = (lane & 1) ? bfhi(h2p) : bflo(h2p);
        rs = rbf(sigmoid_f(bfhi((key & 0x80000000u) ? key ^ 0x80000000u : ~key)));
        op += (size_t)(0xffffu - (key & 0xffffu)) * T_D + c0 + (lane & 15);
      }
      if (bx == 0 && tx < 68) g_hcnt[32 * (tx >> 2) + (tx & 3)] = 0u;
      if (tx < 64) hm->modu[bx * 64 + tx] = 0.f;
      else if (tx < 96) hm->stat[bx * 32 + tx - 64] = make_float2(0.f, 0.f);
      else if (tx < 112) hm->mod[bx * 16 + tx - 96] = 0.f;
      else if (tx < 114 && bx < 66) hm->gkey[bx * 2 + tx - 112] = 0u;
      if (tx == 0) hint_wait(CNT_Y, (uint32_t)OG_MOE);
      named_bar_sync(10, 128);
      TS(11, lane == 0);
      float4 p0, p1, p2, p3;
      #pragma unroll 1
      for (unsigned int spin = 0; spin < (1u << 20); spin++) {
        p0 = ld_tagged4(src); p1 = ld_tagged4(src + 64 * T_D); p2 = ld_tagged4(src + 128 * T_D); p3 = ld_tagged4(four ? src + 192 * T_D : src);
        if (__all_sync(0xffffffffu, tagged4(p0) & tagged4(p1) & tagged4(p2) & tagged4(p3))) break;
      }
      if (four) { p2.x += p3.x; p2.y += p3.y; p2.z += p3.z; p2.w += p3.w; }
      p0.x = (p0.x + p1.x) + p2.x; p0.y = (p0.y + p1.y) + p2.y; p0.z = (p0.z + p1.z) + p2.z; p0.w = (p0.w + p1.w) + p2.w;
      #pragma unroll
      for (int o = 4; o <= 16; o <<= 1) {
        p0.x += __shfl_xor_sync(0xffffffffu, p0.x, o); p0.y += __shfl_xor_sync(0xffffffffu, p0.y, o);
        p0.z += __shfl_xor_sync(0xffffffffu, p0.z, o); p0.w += __shfl_xor_sync(0xffffffffu, p0.w, o);
      }
      if (lane < 4) sts_f32x4(sbase + OG_SFIN + (tx >> 5) * 64 + lane * 16, p0.x, p0.y, p0.z, p0.w);
      named_bar_sync(10, 128);
      TS(12, lane == 0);
      if (wid == 1 && lane < 16) {
        const uint32_t ya = sbase + OG_SFIN + lane * 4;
        const float y = rbf(rbf((lds_f32(ya) + lds_f32(ya + 64)) + (lds_f32(ya + 128) + lds_f32(ya + 192))) * rs);
        *op = __float2bfloat16_rn(fx + rbf(((lane & 1) ? bfhi(gb2) : bflo(gb2)) * rbf(fh + y)));
      }
      if (tx == 96) bulk_wait_read<0>();
    }
    TL_END(4, tx == 0);
    PS(6, tx == 32);
    TS(13, tx == 32);
}

__device__ __forceinline__ void tail_consumer(Scratch* hm, uint32_t bx, uint32_t sbase, int tid, int w8, const bf16* __restrict__ w_gate, const bf16* __restrict__ w_up) {
    TAIL_SETUP
    const int warp = w8 & 3, lane = tid & 31, cwg = w8 >> 2, t2 = cwg * 128 + tid;
    const uint32_t dbase = (sbase & 0x3FFFFu) >> 4;
    const uint32_t a_base = dbase + ((cwg * 8192) >> 4) + (1u << 16);
    const uint32_t b_base = dbase + (16384 >> 4) + (512u << 16);
    TL_MARK2(25, threadIdx.x == 128);
    const uint64_t pol = policy_evict_first();
    const bf16* pw = ((lane & 16) ? w_up : w_gate) + (size_t)(w8 * 128 + (lane & 3) * 4) * T_F + (has_moe ? bx : 0) * 32 + ((lane >> 2) & 3) * 8;
    uint4 wv[32];
    float acc[64];
    {
      uint32_t stage = (OG_POS + 1) % OG_ST, phase = ((OG_POS + 1) / OG_ST) & 1, prev = 12;
      #pragma unroll
      for (int i = 0; i < 64; i++) acc[i] = 0.f;
      mbar_wait(bar_full + 248, 0);
      wgmma_fence();
      wgmma_m64n128k16_ss_tb<0 + 5 * 2048, 0 + 5 * 2048>(acc, a_base, b_base, 0);
      wgmma_m64n128k16_ss_tb<2 + 5 * 2048, 128 + 5 * 2048>(acc, a_base, b_base, 1);
      wgmma_m64n128k16_ss_tb<4 + 5 * 2048, 256 + 5 * 2048>(acc, a_base, b_base, 1);
      wgmma_m64n128k16_ss_tb<6 + 5 * 2048, 384 + 5 * 2048>(acc, a_base, b_base, 1);
      wgmma_commit();
      #pragma unroll
      for (int g = OG_PRE ? -1 : 0; g < OG_NG; g++) {
        #pragma unroll
        for (int j = 0; j < 4; j++) if (g >= 0) wv[4 * g + j] = ldg_stream_v4(pw + (size_t)(16 * g + j) * T_F, pol);
        #pragma unroll 1
        for (int kb = g < 0 ? 1 : OG_PRE + g * OG_LEN; kb < (g == OG_NG - 1 ? OG_NKB : OG_PRE + (g + 1) * OG_LEN); kb++) {
          mbar_wait(bar_full + 8 * stage, phase);
          const uint32_t a_lo = a_base + stage * (OG_STAGE >> 4), b_lo = b_base + stage * (OG_STAGE >> 4);
          wgmma_fence();
          wgmma_m64n128k16_ss_tb<0, 0>(acc, a_lo, b_lo, 1);
          wgmma_m64n128k16_ss_tb<2, 128>(acc, a_lo, b_lo, 1);
          wgmma_m64n128k16_ss_tb<4, 256>(acc, a_lo, b_lo, 1);
          wgmma_m64n128k16_ss_tb<6, 384>(acc, a_lo, b_lo, 1);
          wgmma_commit();
          wgmma_wait<1>();
          if (tid == 0) mbar_arrive(bar_empty + 8 * prev);
          prev = stage;
          if (++stage == OG_ST) { stage = 0; phase ^= 1; }
        }
      }
    }
    const uint32_t frag = (64 * cwg + 16 * warp + (lane & 15)) * 128 + (((lane >> 4) ^ (lane & 7)) << 4);
    const uint32_t tcol = sbase + OG_SCOL + (lane & 3) * 16, g = lane >> 2;
    float* sdst = reinterpret_cast<float*>(g_part1 + ((mt * 8 + w8) * 8 + nt) * 16 + g + (lane & 1) * 8);
    uint32_t xr[32];
    uint4 ga[4], cw[4];
    auto ld_quarter = [&](int q, uint32_t dep) {
      #pragma unroll
      for (int i = 2 * q; i < 2 * q + 2; i++) ldmatrix_x4(sbase + OG_XSLOT + (i >> 2) * 16384 + (frag ^ ((i & 3) * 32)) + dep, xr[4 * i], xr[4 * i + 1], xr[4 * i + 2], xr[4 * i + 3]);
      ga[q] = lds_u32x4(tcol + 512 + q * 64 + dep);
      cw[q] = lds_u32x4((g ? tcol + (lane & 8) * 32 + q * 64 : sbase + OG_SMISC + 32) + dep);
    };
    mbar_wait(bar_col, 0);
    mbar_wait(bar_full + 8 * ((OG_POS + OG_NKB) % OG_ST), ((OG_POS + OG_NKB) / OG_ST) & 1);
    ld_quarter(0, 0);
    wgmma_wait<0>();
    fence_regs(acc);
    if (tid == 0) mbar_arrive(bar_end);
    TL_MARK2(9, lane == 0);
    TS(0, lane == 0);
    PS(5, threadIdx.x == 256);
    {
      float dl[4] = {0.f, 0.f, 0.f, 0.f}, da[4] = {0.f, 0.f, 0.f, 0.f}, db[4] = {0.f, 0.f, 0.f, 0.f};
      #pragma unroll
      for (int q = 0; q < 4; q++) {
        uint32_t pk[8];
        #pragma unroll
        for (int i = 0; i < 8; i++) pk[i] = pack_bf16(acc[16 * q + 2 * i], acc[16 * q + 2 * i + 1]);
        if (q < 3) ld_quarter(q + 1, 0u);
        #pragma unroll
        for (int i = 2 * q; i < 2 * q + 2; i++) {
          #pragma unroll
          for (int k = 0; k < 4; k++) xr[4 * i + k] = badd2(xr[4 * i + k], bmul2((i & 1) ? (k < 2 ? ga[q].z : ga[q].w) : (k < 2 ? ga[q].x : ga[q].y), pk[4 * (i & 1) + k]));
          mma_bf16(dl, xr[4 * i], xr[4 * i + 1], xr[4 * i + 2], xr[4 * i + 3], (i & 1) ? cw[q].z : cw[q].x, (i & 1) ? cw[q].w : cw[q].y);
          mma_bf16(da, xr[4 * i], xr[4 * i + 1], xr[4 * i + 2], xr[4 * i + 3], xr[4 * i], xr[4 * i + 2]);
          mma_bf16(db, xr[4 * i], xr[4 * i + 1], xr[4 * i + 2], xr[4 * i + 3], xr[4 * i + 1], xr[4 * i + 3]);
        }
      }
      {
        const int dsrc = (lane & ~3) + (g >> 1);
        const float qa = __shfl_sync(0xffffffffu, (g & 1) ? da[1] : da[0], dsrc), qb = __shfl_sync(0xffffffffu, (g & 1) ? db[3] : db[2], dsrc);
        const float e0 = __shfl_xor_sync(0xffffffffu, (lane & 1) ? dl[0] : dl[2], 1), e1 = __shfl_xor_sync(0xffffffffu, dl[3], 1);
        const bool hi = lane & 1;
        if ((lane & 3) < 2) st_tagged4(sdst, hi ? e0 : dl[0], hi ? qb : qa, hi ? e1 + dl[2] : dl[1] + e0, 1.0f);
      }
    }
    TL_MARK2(10, lane == 0);
    TS(1, lane == 0);
    uint4 tc[4], ts[4], tg[4];
    #pragma unroll
    for (int i = 0; i < 8; i++) stmatrix_x4(sbase + OG_XSLOT + (i >> 2) * 16384 + (frag ^ ((i & 3) * 32)), xr[4 * i], xr[4 * i + 1], xr[4 * i + 2], xr[4 * i + 3]);
    #pragma unroll
    for (int i = 0; i < 8; i++) ldmatrix_x4(sbase + OG_XSLOT + (i >> 2) * 16384 + (frag ^ ((i & 3) * 32)), xr[4 * i], xr[4 * i + 1], xr[4 * i + 2], xr[4 * i + 3]);
    #pragma unroll
    for (int i = 0; i < 2; i++) { tc[i] = lds_u32x4(tcol + 768 + i * 64); ts[i] = lds_u32x4(tcol + 1024 + i * 64); tg[i] = lds_u32x4(tcol + 1280 + i * 64); }
    {
      const float* src = reinterpret_cast<const float*>(g_part1 + ((mt * 8 + w8) * 8 + (lane & 1) * 4) * 16 + (lane >> 1));
      float4 v, v1, v2, v3;
      #pragma unroll 1
      for (unsigned int spin = 0; spin < (1u << 22); spin++) {
        v = ld_tagged4(src); v1 = ld_tagged4(src + 64); v2 = ld_tagged4(src + 128); v3 = ld_tagged4(src + 192);
        if (tagged4(v) & tagged4(v1) & tagged4(v2) & tagged4(v3)) break;
        __nanosleep(100);
      }
      __syncwarp();
      TL_MARK2(26, lane == 0);
    TS(2, lane == 0);
      v.x = (v.x + v1.x) + (v2.x + v3.x); v.y = (v.y + v1.y) + (v2.y + v3.y); v.z = (v.z + v1.z) + (v2.z + v3.z);
      v.x += __shfl_xor_sync(0xffffffffu, v.x, 1); v.y += __shfl_xor_sync(0xffffffffu, v.y, 1); v.z += __shfl_xor_sync(0xffffffffu, v.z, 1);
      const float mean = v.x * (1.0f / T_D);
      const float var = fmaxf(fmaf(-mean, mean, v.y * (1.0f / T_D)), 0.f);
      const uint32_t mb2 = pack_bf16(mean, mean);
      const float inv = rcp_approx(rbf(sqrt_approx(rbf(rbf(var) + 1e-05f))));
      {
        const uint4 sc = lds_u32x4(sbase + OG_SMISC);
        const uint32_t key = rank_key(rbf(fmaf(fmaf(-bflo(mb2), __uint_as_float(sc.x) + __uint_as_float(sc.y), v.z), inv, __uint_as_float(sc.z) + __uint_as_float(sc.w))), m0 + 16 * w8 + (lane >> 1));
        mbar_wait(bar_end, 0);
        if (lane & 1) sts_u32(sbase + OG_SSTAT + 1024 + (16 * w8 + (lane >> 1)) * 4, key);
        else sts_u32x2(sbase + OG_SSTAT + (16 * w8 + (lane >> 1)) * 8, mb2, __float_as_uint(inv));
        __syncwarp();
        TS(3, lane == 0);
        if (lane == 0) mbar_arrive(bar_key);
      }
      const uint32_t ih = pack_bf16(inv, inv), il = pack_bf16(inv - bflo(ih), inv - bflo(ih));
      const uint32_t mba = __shfl_sync(0xffffffffu, mb2, 2 * (lane >> 2)), mbb = __shfl_sync(0xffffffffu, mb2, 2 * (lane >> 2) + 16);
      const uint32_t iha = __shfl_sync(0xffffffffu, ih, 2 * (lane >> 2)), ihb = __shfl_sync(0xffffffffu, ih, 2 * (lane >> 2) + 16);
      const uint32_t ila = __shfl_sync(0xffffffffu, il, 2 * (lane >> 2)), ilb = __shfl_sync(0xffffffffu, il, 2 * (lane >> 2) + 16);
      #pragma unroll
      for (int i = 2; i < 4; i++) { tc[i] = lds_u32x4(tcol + 768 + i * 64); ts[i] = lds_u32x4(tcol + 1024 + i * 64); tg[i] = lds_u32x4(tcol + 1280 + i * 64); }
      #pragma unroll
      for (int i = 0; i < 8; i++) {
        const uint4 &c = tc[i >> 1], &s = ts[i >> 1], &b = tg[i >> 1];
        const bool u = i & 1;
        stmatrix_x4(sbase + OG_OSLOT + (i >> 2) * 16384 + (frag ^ ((i & 3) * 32)),
                    out2(xr[4 * i], mba, iha, ila, u ? c.z : c.x, u ? s.z : s.x, u ? b.z : b.x), out2(xr[4 * i + 1], mbb, ihb, ilb, u ? c.z : c.x, u ? s.z : s.x, u ? b.z : b.x),
                    out2(xr[4 * i + 2], mba, iha, ila, u ? c.w : c.y, u ? s.w : s.y, u ? b.w : b.y), out2(xr[4 * i + 3], mbb, ihb, ilb, u ? c.w : c.y, u ? s.w : s.y, u ? b.w : b.y));
      }
      fence_proxy_async();
      __syncwarp();
      if (lane == 0) mbar_arrive(bar_out);
      TL_MARK2(24, lane == 0);
    TS(5, lane == 0);
    }
    uint4 wd[16];
    {
      mbar_wait(bar_sel, 0);
      TL_MARK2(12, lane == 0);
    TS(7, lane == 0);
      const float* src = reinterpret_cast<const float*>(g_cand + lds_u32(sbase + OG_SMISC + 72 + cwg * 4) * 256 + 128 + tid);
      float4 hf = ld_tagged4(src);
      if (has_moe) mbar_wait(bar_wd, 0);
      #pragma unroll
      for (int i = 0; i < 16; i++) wd[i] = lds_u32x4(sbase + OG_SWD + (((i >> 2) & 1) * 4 + (lane & 3)) * 8224 + (i & 3) * 2048 + w8 * 256 + (i >> 3) * 128 + (lane >> 2) * 16);
      #pragma unroll 1
      for (unsigned int spin = 0; spin < (1u << 20) && !tagged4(hf); spin++) hf = ld_tagged4(src);
      const uint4 hv = make_uint4(__float_as_uint(hf.x), __float_as_uint(hf.y), __float_as_uint(hf.z), __float_as_uint(hf.w));
      sts_u32x4(sbase + OG_SH2 + t2 * 16, hv.x, hv.y, hv.z, hv.w);
    }
    named_bar_sync(9, 256);
    if (t2 == 0) mbar_arrive(bar_h2);
    TL_MARK2(13, lane == 0);
    TS(8, lane == 0);
    if (has_moe) {
      const GemvSel sel = gemv_sel(lane);
      {
        float d[4][4];
        #pragma unroll
        for (int c = 0; c < 4; c++) { d[c][0] = 0.f; d[c][1] = 0.f; d[c][2] = 0.f; d[c][3] = 0.f; }
        #pragma unroll
        for (int st = 0; st < 8; st++) {
          const uint2 hb = lds_u32x2(sbase + OG_SH2 + ((lane >> 2) & 1) * 2048 + (w8 * 128 + st * 16 + (lane & 3) * 4) * 2);
          #pragma unroll
          for (int j = 0; j < 4; j++) mma_bf16(d[j], wv[4 * st + j].x, wv[4 * st + j].y, wv[4 * st + j].z, wv[4 * st + j].w, GEMV_B0(j, hb, sel), GEMV_B1(j, hb, sel));
        }
        #pragma unroll
        for (int e = 0; e < 4; e++) d[0][e] = (d[0][e] + d[1][e]) + (d[2][e] + d[3][e]);
        const float4 r = gemv_out(d[0], lane);
        sts_f32x4(sbase + OG_SRED + w8 * 512 + (((lane >> 4) * 2 + (lane & 1)) * 32 + ((lane >> 2) & 3) * 8 + (lane & 2) * 2) * 4, r.x, r.y, r.z, r.w);
      }
      named_bar_sync(9, 256);
      if (t2 < 64) {
        float gp[8], up[8];
        #pragma unroll
        for (int w = 0; w < 8; w++) { gp[w] = lds_f32(sbase + OG_SRED + w * 512 + t2 * 4); up[w] = lds_f32(sbase + OG_SRED + w * 512 + 256 + t2 * 4); }
        const float gs = ((gp[0] + gp[1]) + (gp[2] + gp[3])) + ((gp[4] + gp[5]) + (gp[6] + gp[7]));
        const float us = ((up[0] + up[1]) + (up[2] + up[3])) + ((up[4] + up[5]) + (up[6] + up[7]));
        asm volatile("st.shared.u16 [%0], %1;" :: "r"(sbase + OG_SGU + t2 * 2), "h"((uint16_t)pack_bf16(silu_bf(rbf(gs)) * rbf(us), 0.f)) : "memory");
      }
      named_bar_sync(9, 256);
      TS(9, lane == 0);
      float d[4][4];
      #pragma unroll
      for (int c = 0; c < 4; c++) { d[c][0] = 0.f; d[c][1] = 0.f; d[c][2] = 0.f; d[c][3] = 0.f; }
      #pragma unroll
      for (int st = 0; st < 2; st++) {
        const uint2 g = lds_u32x2(sbase + OG_SGU + ((lane >> 2) & 1) * 64 + st * 32 + (lane & 3) * 8);
        #pragma unroll
        for (int j = 0; j < 4; j++) {
          const uint32_t b0 = GEMV_B0(j, g, sel), b1 = GEMV_B1(j, g, sel);
          mma_bf16(d[j & 1], wd[4 * st + j].x, wd[4 * st + j].y, wd[4 * st + j].z, wd[4 * st + j].w, b0, b1);
          mma_bf16(d[2 + (j & 1)], wd[8 + 4 * st + j].x, wd[8 + 4 * st + j].y, wd[8 + 4 * st + j].z, wd[8 + 4 * st + j].w, b0, b1);
        }
      }
      #pragma unroll
      for (int e = 0; e < 4; e++) { d[0][e] += d[1][e]; d[2][e] += d[3][e]; }
      const float4 y0 = gemv_out(d[0], lane), y1 = gemv_out(d[2], lane);
      float* yp = g_ypart + (size_t)(bx * 2 + (lane & 1)) * T_D + w8 * 128 + (lane >> 2) * 8 + (lane & 2) * 2;
      st_tagged4(yp, y0.x, y0.y, y0.z, y0.w);
      st_tagged4(yp + 64, y1.x, y1.y, y1.z, y1.w);
      named_bar_sync(9, 256);
      if (t2 == 0) hint_arrive(CNT_Y);
    }
    TS(10, lane == 0);
    TL_CLK(4, 1, threadIdx.x == 128);
}

__device__ __forceinline__ void store_warp(Scratch* hm, uint32_t sbase, const CUtensorMap* tmO, int item0, int n_items) {
  if (elect_one()) {
    const uint32_t bars = sbase + AT_SBAR, b_q0 = bars + 80, b_ob = bars + 96, b_ordy = bars + 104, b_acq = bars + 256;
    mbar_wait(bars + 232, 0);
    const uint32_t bx = lds_u32(bars + 240);
    const unsigned int* cnt = &g_hcnt[32 * (1 + OG_MT(bx)) + 2];
    #pragma unroll 1
    for (int q = 0; q < 4 * n_items; q++) {
      const int item = item0 + (q >> 2) * 128, h = (q >> 1) & 1, w = q & 1;
      const bool last = (q >> 2) == n_items - 1;
      mbar_wait(b_ordy + 8 * (q & 3), q >> 2);
      if (q == 4 && item < 192) spin_until(&g_hcnt[32 * (1 + (item & 15)) + 1], (item & 15) < 12 ? 8u : 7u);
      store_o(tmO, (h ? (last ? sbase + AT_SQ + 32768 : sbase + 2 * 32768) : sbase + AT_SQ) + w * 8192, (item >> 4) * 2 + h, (item & 15) * 128 + w * 64);
      if (w) {
        PF(1 + (q >> 1));
        bulk_wait_read<0>();
        mbar_arrive(h ? b_ob : b_q0);
        bulk_wait<0>();
        fence_proxy_async_global();
        red_release_add(&g_hcnt[32 * (1 + (item & 15)) + 2 + (item >> 7)], 1u);
        if (bx < 128 && q == (n_items == 2 ? 5 : 3)) { spin_until(cnt, 16u); mbar_arrive(b_acq); }
      }
    }
    if (bx < 128) { spin_until(&g_hcnt[0], 8u); spin_until(cnt + 1, 16u); mbar_arrive(b_acq + 8); }
  }
}

#define TUNE_PARAM
__device__ __forceinline__ int h_first(int item, int c) { const int j = (item >> 4) + 3 * c; return j >= 7 ? j - 7 : j; }
__global__ void __launch_bounds__(384, 1)
fused_kernel(const bf16* __restrict__ x, const bf16* __restrict__ cvec, const bf16* __restrict__ w_mod, Scratch* hm, uint32_t zero, TUNE_PARAM
            const uint8_t* __restrict__ pf_wo, const bf16* __restrict__ kc, const bf16* __restrict__ vc, const bf16* __restrict__ w_r,
            const bf16* __restrict__ w_gate, const bf16* __restrict__ w_up, const bf16* __restrict__ w_down, bf16* __restrict__ out,
            const __grid_constant__ CUtensorMap tmM, const __grid_constant__ CUtensorMap tmW, const __grid_constant__ CUtensorMap tmK,
            const __grid_constant__ CUtensorMap tmV, const __grid_constant__ CUtensorMap tmO, const __grid_constant__ CUtensorMap tmOl, const __grid_constant__ CUtensorMap tmWo,
            const __grid_constant__ CUtensorMap tmX, const __grid_constant__ CUtensorMap tmOut)
{
  extern __shared__ __align__(1024) uint8_t smem_raw[];
  const uint32_t sbase = smem_u32(smem_raw);
  const uint32_t bars = sbase + AT_SBAR;
  const uint32_t b_full = bars, b_empty = bars + 40;
  const uint32_t b_q0 = bars + 80, b_q1 = bars + 88;
  const uint32_t b_ob = bars + 96;
  const uint32_t b_ordy = bars + 104;
  const uint32_t b_pin = bars + 136;
  const uint32_t b_a0 = bars + 144;
  const uint32_t b_x = bars + 160;
  const uint32_t b_w = bars + 152, b_go = bars + 224;
  const uint32_t b_bx = bars + 232, s_bx = bars + 240;
  const uint32_t b_hs = bars + 464;
  const uint32_t b_tab = bars + 272;
  const int wid = __shfl_sync(0xffffffffu, threadIdx.x >> 5, 0), wg = wid >> 2;
  const bool single = blockIdx.x >= AT_NFULL;
  const int item0 = __shfl_sync(0xffffffffu, blockIdx.x < 128 ? (int)blockIdx.x : (int)blockIdx.x + 124, 0), n_items = __shfl_sync(0xffffffffu, single ? 1 : 2, 0);
  const uint32_t t0 = clock_lo();
  TL_START(3);
  HS(0);
  if (threadIdx.x == 0) {
    if (sbase & 1023u) __trap();
    for (int i = 0; i < 5; i++) { mbar_init(b_full + 8 * i, 1); mbar_init(b_empty + 8 * i, 2); mbar_init(b_hs + 8 * i, i < 2 && !single ? 4 : 1); }
    sts_u32(bars + 504, 5u);
    mbar_init(b_q0, 1); mbar_init(b_q1, 8); mbar_init(b_ob, 1);
    for (int i = 0; i < 4; i++) mbar_init(b_ordy + 8 * i, 4);
    mbar_init(b_pin, 1); mbar_init(b_a0, 8); mbar_init(b_x, 1); mbar_init(b_w, 1); mbar_init(b_go, 1); mbar_init(b_bx, 1);
    for (int i = 0; i < 8; i++) mbar_init(b_tab + 8 * i, i < 2 ? 1 : 2);
    mbar_init(bars + 168, 1); mbar_init(bars + 176, 1); mbar_init(bars + 184, 8); mbar_init(bars + 192, 2);
    mbar_init(bars + 200, 8); mbar_init(bars + 208, 1); mbar_init(bars + 216, 1); mbar_init(bars + 248, 1); mbar_init(bars + 256, 1); mbar_init(bars + 264, 1);
    sts_u32x4(sbase + OG_SMISC + 32, 0x3F803F80u, 0x3F803F80u, 0x3F803F80u, 0x3F803F80u);
    fence_mbar_init();
    if (blockIdx.x < 128) {
      HS(1);
      wait_clock(t0, XDLY);
      mbar_expect_tx(b_x, 32768);
      bulk_load_hint(sbase + 3 * 32768, x + (size_t)blockIdx.x * 16 * T_D, 32768, b_x, pol_normal());
    }
    mbar_arrive(b_tab); mbar_arrive(b_tab + 8);
  }

  if (wg == 0) {
    reg_dealloc<AT_PREG>();
    if (wid == 0) { __syncwarp(); named_bar_arrive(6, 128); named_bar_arrive(11, 160); named_bar_arrive(12, 160); }
    if (wid >= 2) {
      named_bar_sync(6, 128);
      wait_clock(t0, GDLY2);
      gather_table(hm, sbase + 4 * 32768, b_tab, wid & 1, threadIdx.x & 31);
      if (threadIdx.x == 64) PF(0);
      if (threadIdx.x == 96 && !single) { sleep_until(t0, 40000); spin_until(&g_hcnt[32 * (1 + (item0 & 15))], 7u); mbar_arrive(b_w); }
    } else if (wid == 1) {
      named_bar_sync(6, 128);
      if (item0 < 112) {
        const int lane = threadIdx.x & 31;
        #pragma unroll 1
        for (int j0 = h_first(item0, 0), j1 = h_first(item0, 1); j0 < 16 || j1 < 16;) {
          const int c = j1 < j0, j = c ? j1 : j0;
          bf16* hg = hm->o + (size_t)((item0 & 15) * 128 + c * 64 + (lane >> 3)) * O_LD + O_H + (lane & 7) * 8 + j * 64;
          uint32_t src = sbase + AT_SQ - 16384 + c * 8192 + (lane >> 3) * 128 + (((lane ^ (lane >> 3)) & 7) << 4);
          mbar_wait(b_hs + 8 * c, j >= 7 && j < 14);
          #pragma unroll 1
          for (int i = 0; i < 4; i++, hg += 16 * O_LD, src += 2048) {
            uint4 v[4];
            #pragma unroll
            for (int k = 0; k < 4; k++) v[k] = lds_u32x4((src ^ ((k & 1) * 64)) + k * 512);
            #pragma unroll
            for (int k = 0; k < 4; k++) *reinterpret_cast<uint4*>(hg + k * 4 * O_LD) = v[k];
          }
          __syncwarp();
          if (lane == 0) mbar_arrive(b_hs + 16 + 8 * c);
          if (c) j1 += 7; else j0 += 7;
        }
        if (lane == 0) mbar_arrive(b_go);
        if (lane == 0) red_release_add(&g_hcnt[32 * (1 + (item0 & 15))], 1u);
      }
      sleep_until(t0, 26000);
      const uint32_t v = assign_tile(hm, t0, threadIdx.x & 31);
      if (threadIdx.x == 32) { sts_u32(s_bx, v); mbar_arrive(b_bx); }
      __syncwarp();
      store_warp(hm, sbase, &tmO, item0, n_items);
      __syncwarp();
    } else {
     if (elect_one()) {
      const uint64_t pol = policy_evict_first();
      prefetch_tmap(&tmW); prefetch_tmap(&tmX); prefetch_tmap(&tmWo); prefetch_tmap(&tmOl);
      if (single) {
        prefetch_tmap(&tmM);
        #pragma unroll 1
        for (uint32_t i = 0, buf = 0; i < 44; i++) {
          wait_clock(t0, i < 12 ? (blockIdx.x < 128 ? WDLY + W_OFF : WDLY) + (i & 3) * W_GAP + (i >> 2) * W_RND : W_LATE);
          #pragma unroll 1
          for (uint32_t spin = 0, n = 0; spin < (1u << 24) && n <= i; spin++) asm volatile("ld.volatile.shared.u32 %0, [%1];" : "=r"(n) : "r"(bars + 504) : "memory");
          mbar_expect_tx(bars + 464 + buf * 8, 32768);
          tma_load_2d_hint(sbase + (buf + (buf > 2 ? 2 : 0)) * 32768, &tmM, mod_col0(blockIdx.x - AT_NFULL, (int)(i >> 2) - 3), (i & 3) * 256, bars + 464 + buf * 8, pol);
          if (++buf == 5) buf = 0;
        }
        mbar_wait(b_go, 0);
      }
      {
        #pragma unroll 1
        for (int j = 0; j < T_D / 64; j++) {
          const uint32_t fb = b_full + 8 * (j & 3);
          mbar_wait(b_empty + 8 * (j & 3), ((j >> 2) & 1) ^ 1);
          mbar_expect_tx(fb, j == 0 ? 65536 : j == T_D / 64 - 1 ? 32768 : 49152);
          if (j < 2) wait_clock(t0, j ? ST1_T : PRE_T);
          if (j == 3) mbar_wait(b_a0, 0);
          if (j < 4) HS(2 + j);
          tma_load_3d_hint(sbase + (j & 3) * 32768, &tmW, j * 64, (item0 >> 4) * 4, fb, pol);
          if (j == 0) { wait_clock(t0, A_T); tma_load_2d_hint(sbase + AT_SQ, &tmX, 0, (item0 & 15) * 128, fb, pol); }
          if (j < T_D / 64 - 1) tma_load_2d_hint(sbase + AT_SQ + ((j + 1) & 3) * 16384, &tmX, (j + 1) * 64, (item0 & 15) * 128, fb, pol);
        }
      }
      uint32_t slot = 0, ph = 1;
      #pragma unroll 1
      for (int it = 0; it < n_items; it++) {
        const int item = item0 + it * 128, hp = item >> 4, qt = item & 15;
        const bool first = it == 0;
        if (!first) {
          #pragma unroll 1
          for (int j = 0; j < T_D / 64; j++) {
            const uint32_t sl = ring_slot(qp_pos(j, 1)), fb = b_full + 8 * sl;
            mbar_wait(b_empty + 8 * sl, ring_par(qp_pos(j, 1)) ^ ((j >> 2) & 1) ^ 1);
            mbar_expect_tx(fb, 49152);
            tma_load_3d_hint(sbase + sl * 32768, &tmW, j * 64, hp * 4, fb, pol);
            if (j == 0) { mbar_wait(b_q0, 0); mbar_wait(b_q1, 0); mbar_wait(b_w, 0); fence_proxy_async_global(); }
            tma_load_2d_hint(sbase + AT_SQ + (j & 3) * 16384, &tmOl, O_H + j * 64, qt * 128, fb, pol);
          }
        }
        #pragma unroll 1
        for (int j = 0; j < 4 * AT_NBLK; j++) {
          const bool isv = (j > 0 && !(j & 1)) || j == 4 * AT_NBLK - 1;
          const int row = hp * 2 * T_SEQ + (isv ? (j - 1) >> 1 : (j + 1) >> 1) * 128;
          const uint32_t fb = b_full + 8 * slot;
          mbar_wait(b_empty + 8 * slot, ph);
          if (!first && j == 3) mbar_wait(b_ob, 0);
          if (!first && j == 4) hint_arrive(&g_hcnt[32 * (1 + qt) + 1]);
          if (first && j == 4 && item0 < 112) mbar_wait(b_go, 0);
          mbar_expect_tx(fb, 32768);
          tma_load_2d_hint(sbase + slot * 32768, isv ? &tmV : &tmK, 0, row, fb, pol);
          tma_load_2d_hint(sbase + slot * 32768 + 16384, isv ? &tmV : &tmK, 64, row, fb, pol);
          if (it == 1 && isv && j >= 2 * WO_LATE && j < 2 * WO_LATE + 32 && blockIdx.x < 64)
            l2_prefetch_bulk(pf_wo + (size_t)blockIdx.x * 131072 + ((j >> 1) - WO_LATE) * 8192, 8192);
          if (++slot == 5) { slot = 0; ph ^= 1; }
        }
      }
      mbar_wait(b_bx, 0);
      const uint32_t bx = lds_u32(s_bx);
      if (bx < 128) {
        if (single) mbar_wait(b_go, 1);
        tail_producer(hm, bx, sbase, 0, n_items - 1, pol, &tmOl, &tmWo, &tmX, w_down);
      }
     }
    }
    __syncwarp();
    PSV(0, threadIdx.x == 96, t0);
    mbar_wait(b_bx, 0);
    const uint32_t bx = __shfl_sync(0xffffffffu, lds_u32(s_bx), 0);
    if (bx < 128) tail_exchange(hm, bx, sbase, wid, __shfl_sync(0xffffffffu, threadIdx.x, threadIdx.x), &tmOut, out);
  } else {
    if (wg == 1 && blockIdx.x < 128) head_first(hm, sbase + 4 * 32768 + 4096, threadIdx.x - 128, cvec, w_mod);
    named_bar_sync(10 + wg, 160);
    if (wg == 2 && blockIdx.x < 128) head_stats(hm, sbase + 3 * 32768, b_x, threadIdx.x - 256);
    if (single) {
      mod_rest(hm, t0, sbase, bars + 464, threadIdx.x - 128, (int)blockIdx.x - AT_NFULL, cvec, w_r);
      named_bar_sync(5, 256);
      if (threadIdx.x == 128) mbar_arrive(b_go);
    }
    if (wg == 1) { wait_clock(t0, GDLY); head_gather(hm, sbase + 4 * 32768, threadIdx.x - 128); }
    reg_alloc<AT_CREG>();
    const int cwg = wg - 1;
    const int tid = __shfl_sync(0xffffffffu, threadIdx.x, threadIdx.x) & 127;
    const int warp = wid & 3, lane = tid & 31;
    const uint32_t dbase = (sbase & 0x3FFFFu) >> 4;
    const uint32_t k_base = dbase + (1u << 16);
    const uint32_t v_base = dbase + (1024u << 16);
    const uint32_t w_base = dbase + (512u << 16);
    const uint32_t frag = cwg * 8192 + (16 * warp + (lane & 7) + 8 * ((lane >> 3) & 1)) * 128;
    if (cwg == 1) named_bar_arrive(1, 256);
    bool raw = false;
    constexpr int nkb = T_D / 64;
    float acc[128], c0, c1;
    {
      FS(0, 0);
      uint32_t af[2][16], rw[16];
      uint4 tb[4];
      uint32_t xa[4];
      #pragma unroll
      for (int st = 0; st < 4; st++) xa[st] = __shfl_sync(0xffffffffu, (sbase + AT_SQ + frag + (((lane >> 4) ^ (lane & 7)) << 4)) ^ (st * 32), lane);
      const uint32_t xt = __shfl_sync(0xffffffffu, sbase + 4 * 32768 + (lane & 3) * 16, lane);
      auto qp_fetch = [&](int j) {
        #pragma unroll
        for (int st = 0; st < 4; st++) {
          ldmatrix_x4(xa[st] + (j & 3) * 16384, rw[4 * st], rw[4 * st + 1], rw[4 * st + 2], rw[4 * st + 3]);
          tb[st] = lds_u32x4(xt + (j & 15) * 256 + st * 64);
        }
      };
      zero_regs(acc);
      #pragma unroll
      for (int i = 0; i < 16; i++) af[1][i] = 0u;
      const float2* stp = hm->stat + (item0 & 15) * 256 + (cwg * 4 + warp) * 32 + (lane & 3) * 8 + (lane >> 2);
      HS(4);
      wait_clock(t0, SDLY);
      float2 sv = ld_tagged2(stp);
      named_bar_sync(5, 256);
      mbar_wait(b_full, 0);
      HS(5);
      qp_fetch(0);
      #pragma unroll 1
      for (unsigned int spin = 0; spin < (1u << 22); spin++) {
        if (__all_sync(0xffffffffu, (__float_as_uint(sv.x) != 0u) & (__float_as_uint(sv.y) != 0u))) break;
        sv = ld_tagged2(stp);
      }
      HS(6);
      if (lane == 0) mbar_arrive(b_a0 + (rw[3] & rw[7] & rw[11] & rw[15] & zero));
      const uint32_t st = ln_stat(sv.x + __shfl_xor_sync(0xffffffffu, sv.x, 1), sv.y + __shfl_xor_sync(0xffffffffu, sv.y, 1)), so = __shfl_xor_sync(0xffffffffu, st, 2);
      const uint32_t sta = (lane & 2) ? so : st, stb = (lane & 2) ? st : so;
      const uint32_t mean_a = __byte_perm(sta, 0u, 0x1010), mean_b = __byte_perm(stb, 0u, 0x1010), sd_a = __byte_perm(sta, 0u, 0x3232), sd_b = __byte_perm(stb, 0u, 0x3232);
      c0 = AT_C * rcp_approx(bfhi(sta)); c1 = AT_C * rcp_approx(bfhi(stb));
      sts_u32(sbase + OG_SMISC + 256 + (cwg * 4 + warp) * 64 + (lane & 28) + (lane & 2) * 16, __float_as_uint((lane & 2) ? c1 : c0));
      int jst = item0 < 112 ? h_first(item0, cwg) : 99;
      #pragma unroll 1
      for (int j2 = 0; j2 < nkb; j2 += 2) {
        #pragma unroll
        for (int u = 0; u < 2; u++) {
          const int j = j2 + u;
          const uint32_t bt = b_tab + 4 * ((j + 1) & 15);
          if (u == 1) {
            #pragma unroll 1
            for (uint32_t z = 0; z < zero; z++)
              #pragma unroll
              for (int i = 0; i < 16; i += 4) sts_u32x4(xt + i * 4, af[1][i], af[1][i + 1], af[1][i + 2], af[1][i + 3]);
          }
          bool ok = mbar_test(b_full + 8 * (j & 3), (j >> 2) & 1);
          if (u == 1) ok &= mbar_test(bt, 0);
          #pragma unroll
          for (int st = 0; st < 4; st++) {
            af[u][4 * st + 0] = bfma2(bsub2(rw[4 * st + 0], mean_a), tb[st].x, bmul2(tb[st].z, sd_a));
            af[u][4 * st + 1] = bfma2(bsub2(rw[4 * st + 1], mean_b), tb[st].x, bmul2(tb[st].z, sd_b));
            af[u][4 * st + 2] = bfma2(bsub2(rw[4 * st + 2], mean_a), tb[st].y, bmul2(tb[st].w, sd_a));
            af[u][4 * st + 3] = bfma2(bsub2(rw[4 * st + 3], mean_b), tb[st].y, bmul2(tb[st].w, sd_b));
          }
          if (!ok || j == jst) {
            if (!ok) { mbar_wait(b_full + 8 * (j & 3), (j >> 2) & 1); if (u == 1) mbar_wait(bt, 0); }
            if (j == jst) {
              if (j >= 7) mbar_wait(b_hs + 16 + 8 * cwg, j >= 14);
              #pragma unroll
              for (int st = 0; st < 4; st++) stmatrix_x4(xa[st] - 16384, af[u][4 * st], af[u][4 * st + 1], af[u][4 * st + 2], af[u][4 * st + 3]);
              __syncwarp();
              if (lane == 0) mbar_arrive(b_hs + 8 * cwg);
              jst += 7;
            }
          }
          qp_fetch(j + 1);
          if (cwg == 1 && j == nkb - QP_STAG) named_bar_sync(7, 256);
          const uint32_t b_lo = w_base + (j & 3) * 2048;
          wgmma_fence();
          wgmma_m64n256k16_rs_tb<0>(acc, af[u][0], af[u][1], af[u][2], af[u][3], b_lo, 1);
          wgmma_m64n256k16_rs_tb<128>(acc, af[u][4], af[u][5], af[u][6], af[u][7], b_lo, 1);
          wgmma_m64n256k16_rs_tb<256>(acc, af[u][8], af[u][9], af[u][10], af[u][11], b_lo, 1);
          wgmma_m64n256k16_rs_tb<384>(acc, af[u][12], af[u][13], af[u][14], af[u][15], b_lo, 1);
          wgmma_commit();
          if (cwg == 0 && j == nkb - 1) named_bar_arrive(7, 256);
          if (j == 0) HS(7);
          wgmma_wait<1>();
          if (tid == 0) mbar_arrive(j > 0 ? b_empty + 8 * ((j - 1) & 3) : b_pin);
        }
      }
      wgmma_wait<0>();
      fence_regs(acc);
    }
    uint32_t bx;
    #pragma unroll 1
    for (int it = 0;;) {
      const int item = item0 + it * 128, hp = item >> 4;
      const bool more = it + 1 < n_items;
      const int ta = __shfl_sync(0xffffffffu, 4 * it, 0);
      FS(2 * it, 1);
      PS(1 + 2 * it, threadIdx.x == 256);
      if (tid == 0) mbar_arrive(b_empty + 24);
      float o[64], s[64];
      uint32_t p[32], q[32];
      #pragma unroll
      for (int i = 0; i < 32; i++) q[i] = pack_bf16(acc[2 * i] * ((i & 1) ? c1 : c0), acc[2 * i + 1] * ((i & 1) ? c1 : c0));
      zero_regs(s);
      const uint32_t sq = sbase + AT_SQ + cwg * 8192;
      const bool last_wg1 = cwg == 1 && !more;
      float mc0, mc1, al0 = 1.0f, al1 = 1.0f, l0 = 0.f, l1 = 0.f;
      bool redo0 = false;
      FS(2 * it, 2);
      {
        uint32_t dep = zero;
        #pragma unroll
        for (int i = 0; i < 32; i++) dep &= q[i];
        mbar_wait(b_full + 8 * ring_slot(ta) + dep, ring_par(ta));
      }
      named_bar_sync(1 + cwg, 256);
      FS(2 * it, 3);
      issue_qk(s, q, k_base + ring_slot(ta) * 2048);
      named_bar_arrive(1 + (cwg ^ 1), 256);
      const uint32_t rdy = (uint32_t)mbar_test(b_full + 8 * ring_slot(ta + 1), ring_par(ta + 1));
      bool ready = rdy & mbar_test(b_full + 8 * ring_slot(ta + 2), ring_par(ta + 2));
      stage_o(*reinterpret_cast<const float (*)[64]>(&acc[64]), c0, c1, sbase + AT_SQ + 32768 + frag, lane);
      wgmma_wait<0>();
      fence_regs(s);
      if (tid == 0) mbar_arrive(b_empty + 8 * ring_slot(ta));
      mc0 = 0.f; mc1 = 0.f;
      if (!raw) {
        raw = softmax_mode(s, mc0, mc1);
        if (__builtin_expect(!raw, 0)) softmax_sub(s, mc0, mc1);
      }
      softmax_exp<0, 64>(s);
      stage_qregs(q, sbase + AT_SQ + frag, lane);
      pack_p(p, s);
      zero_regs(o);
      FS(2 * it, 4);
      uint32_t ks = ring_slot(ta + 1), vs = ring_slot(ta + 2), kp = ring_par(ta + 1), vp = ring_par(ta + 2);
      if (!ready) { mbar_wait(b_full + 8 * ks, kp); mbar_wait(b_full + 8 * vs, vp); }
      #pragma unroll 1
      for (int n = 1; n < 2 * AT_NBLK; n++) {
        named_bar_sync(1 + cwg, 256);
        issue_qk(s, q, k_base + ks * 2048);
        if (n == AT_NBLK + 1) {
          if (!redo0) stage_o(o, 1.0f, 1.0f, sbase + AT_SQ + frag, lane);
        }
        issue_pv(o, p, v_base + vs * 2048, (n & 15) != 1);
        if (!(last_wg1 && n == 2 * AT_NBLK - 1)) named_bar_arrive(1 + (cwg ^ 1), 256);
        wgmma_wait<1>();
        fence_regs(s);
        if (tid == 0) mbar_arrive(b_empty + 8 * ks);
        if (__builtin_expect(!raw || (n + 1) >> 1 == AT_NBLK / 2, 0)) {
          if (n == AT_NBLK - 1) {
            #pragma unroll
            for (int J = 0; J < 16; J += 2)
              ldmatrix_x4(sbase + AT_SQ + 32768 + frag + (J >> 3) * 16384 + ((((J & 7) + (lane >> 4)) ^ (lane & 7)) << 4), q[2 * J], q[2 * J + 1], q[2 * J + 2], q[2 * J + 3]);
          }
          if (n == AT_NBLK && lane == 0) mbar_arrive(b_q1);
          if (!raw) {
            const float m0 = mc0, m1 = mc1;
            const bool ok = softmax_mode(s, mc0, mc1);
            if (n == AT_NBLK) raw = ok;
            else {
              mc0 = mc0 - AT_HEAD > m0 ? mc0 : m0; mc1 = mc1 - AT_HEAD > m1 ? mc1 : m1;
              al0 = ex2_approx(m0 - mc0); al1 = ex2_approx(m1 - mc1);
            }
            if (!raw) softmax_sub(s, mc0, mc1);
          }
        }
        softmax_exp<0, AT_SPLIT>(s);
        add_rowsum(p, l0, l1);
        if (tid == 0) {
          uint32_t dep = zero & __float_as_uint(l0) & __float_as_uint(l1);
          #pragma unroll
          for (int i = AT_SPLIT - AT_PIN - PINB; i < AT_SPLIT - PINB; i += 2) dep &= __float_as_uint(s[i]) & __float_as_uint(s[i + 1]);
          mbar_arrive(b_pin + dep);
        }
        wgmma_wait<0>();
        fence_regs(o);
        if (tid == 0) mbar_arrive(b_empty + 8 * vs);
        ks += 2; if (ks >= 5) { ks -= 5; kp ^= 1; }
        vs += 2; if (vs >= 5) { vs -= 5; vp ^= 1; }
        ready = mbar_test(b_full + 8 * ks, kp) & mbar_test(b_full + 8 * vs, vp);
        if (__builtin_expect(n == AT_NBLK, 0)) {
          redo0 = finish_l(l0, l1);
          softmax_exp<AT_SPLIT, 64>(s);
          rescale_o(o, l0, l1);
          pack_p(p, s);
          l0 = 0.f; l1 = 0.f;
        } else {
          softmax_exp<AT_SPLIT, 64>(s);
          pack_p(p, s);
        }
        if (__builtin_expect(!raw || !ready || n == AT_NBLK + 1, 0)) {
        if (n == AT_NBLK + 1 && !redo0) { fence_proxy_async(); __syncwarp(); if (lane == 0) mbar_arrive(b_ordy + 8 * cwg); }
        if (!raw && __any_sync(0xffffffffu, al0 != 1.0f || al1 != 1.0f)) {
          rescale_o(o, al0, al1);
          l0 *= al0; l1 *= al1;
          al0 = 1.0f; al1 = 1.0f;
        }
        if (!ready && n < 2 * AT_NBLK - 1) {
          mbar_wait(b_full + 8 * ks, kp);
          mbar_wait(b_full + 8 * vs, vp);
        }
        }
      }
      FS(2 * it + 1, 5);
      const uint32_t vl = ring_slot(ta + 63);
      vs = ring_slot(ta + 62);
      const uint32_t ob = more ? sbase + vs * 32768 : sbase + AT_SQ + 32768;
      mbar_wait(b_full + 8 * vl, ring_par(ta + 63));
      issue_pv(o, p, v_base + vl * 2048, 1);
      add_rowsum(p, l0, l1);
      const bool overflow = finish_l(l0, l1);
      mbar_wait(b_bx, 0);
      bx = __shfl_sync(0xffffffffu, lds_u32(s_bx), 0);
      mbar_wait(b_empty + 8 * vs, ring_par(ta + 62));
      wgmma_wait<0>();
      fence_regs(o);
      if (tid == 0) mbar_arrive(b_empty + 8 * vl);
      FS(2 * it + 1, 6);
      if (overflow) stage_qregs(q, ob + frag, lane);
      else stage_o(o, l0, l1, ob + frag, lane);
      if (__builtin_expect(overflow || redo0, 0)) {
        __syncwarp();
        #pragma unroll 1
        for (int h = redo0 ? 0 : 1; h < (overflow ? 2 : 1); h++)
          attn_rows_exact(h ? ob + cwg * 8192 : sq, warp, lane, kc + (size_t)(hp * 2 + h) * T_SEQ * T_DH, vc + (size_t)(hp * 2 + h) * T_SEQ * T_DH);
        fence_proxy_async();
        __syncwarp();
        if (lane == 0 && redo0) mbar_arrive(b_ordy + 8 * cwg);
        raw = false;
      }
      fence_proxy_async();
      __syncwarp();
      if (lane == 0) mbar_arrive(b_ordy + 16 + 8 * cwg);
      named_bar_sync(3 + cwg, 128);
      FS(2 * it + 1, 7);
      PS(2 + 2 * it, threadIdx.x == 256);
      if (++it == n_items) break;
      FS(2 * it, 0);
      zero_regs(acc);
      auto ss_step = [&](int j, int accumulate) {
        const uint32_t slot = ring_slot(qp_pos(j, 1));
        mbar_wait(b_full + 8 * slot, ring_par(qp_pos(j, 1)) ^ ((j >> 2) & 1));
        if (cwg == 1 && j == nkb - QP_STAG) named_bar_sync(7, 256);
        const uint32_t a_lo = dbase + ((AT_SQ + cwg * 8192) >> 4) + (1u << 16) + (j & 3) * 1024, b_lo = w_base + slot * 2048;
        wgmma_fence();
        wgmma_m64n256k16_ss_tb<0, 0>(acc, a_lo, b_lo, accumulate);
        wgmma_m64n256k16_ss_tb<2, 128>(acc, a_lo, b_lo, 1);
        wgmma_m64n256k16_ss_tb<4, 256>(acc, a_lo, b_lo, 1);
        wgmma_m64n256k16_ss_tb<6, 384>(acc, a_lo, b_lo, 1);
        wgmma_commit();
        return b_empty + 8 * slot;
      };
      uint32_t prev = ss_step(0, 0);
      c0 = lds_f32(sbase + OG_SMISC + 256 + (cwg * 4 + warp) * 64 + (lane & 28)); c1 = lds_f32(sbase + OG_SMISC + 288 + (cwg * 4 + warp) * 64 + (lane & 28));
      #pragma unroll 1
      for (int j = 1; j < nkb; j++) {
        const uint32_t cur = ss_step(j, 1);
        if (cwg == 0 && j == nkb - 1) named_bar_arrive(7, 256);
        wgmma_wait<1>();
        if (tid == 0) mbar_arrive(prev);
        prev = cur;
      }
      wgmma_wait<0>();
      fence_regs(acc);
    }
    if (n_items == 1) {
      named_bar_sync(5, 256);
      if (threadIdx.x == 128) {
        #pragma unroll 1
        for (int i = 4; i < 8; i++) {
          mbar_arrive(b_full + 8 * ring_slot(i));
          mbar_arrive(b_empty + 8 * ring_slot(i)); mbar_arrive(b_empty + 8 * ring_slot(i));
        }
        mbar_arrive(b_go);
      }
      named_bar_sync(5, 256);
    }
    TL_CLK(3, 1, threadIdx.x == 128);
    TL_CTA(1, threadIdx.x == 256);
    TL_END(3, tid == 0);
    __syncwarp();
    QDUMP();
    TL_MARK2(19, tid == 0 && !single);
    if (bx < 128) {
      tail_consumer(hm, bx, sbase, tid, wid - 4, w_gate, w_up);
    }
  }
}

typedef CUresult (*PFN_encodeTiled)(CUtensorMap*, CUtensorMapDataType, cuuint32_t, void*, const cuuint64_t*, const cuuint64_t*,
                                    const cuuint32_t*, const cuuint32_t*, CUtensorMapInterleave, CUtensorMapSwizzle,
                                    CUtensorMapL2promotion, CUtensorMapFloatOOBfill);

CUtensorMap make_map_2d(PFN_encodeTiled enc, const void* ptr, uint64_t inner, uint64_t outer, uint64_t stride_bytes, uint32_t box_inner, uint32_t box_outer) {
  CUtensorMap m;
  cuuint64_t gd[2] = {inner, outer}; cuuint64_t gs[1] = {stride_bytes};
  cuuint32_t bx[2] = {box_inner, box_outer}; cuuint32_t es[2] = {1, 1};
  enc(&m, CU_TENSOR_MAP_DATA_TYPE_BFLOAT16, 2, const_cast<void*>(ptr), gd, gs, bx, es, CU_TENSOR_MAP_INTERLEAVE_NONE,
      CU_TENSOR_MAP_SWIZZLE_128B, CU_TENSOR_MAP_L2_PROMOTION_L2_128B, CU_TENSOR_MAP_FLOAT_OOB_FILL_NONE);
  return m;
}

CUtensorMap make_map_3d(PFN_encodeTiled enc, const void* ptr, uint64_t cols, uint64_t rows, uint32_t box_rows, uint32_t chunks) {
  CUtensorMap m;
  cuuint64_t gd[3] = {64, rows, cols / 64}; cuuint64_t gs[2] = {cols * 2, 128};
  cuuint32_t bx[3] = {64, box_rows, chunks}; cuuint32_t es[3] = {1, 1, 1};
  enc(&m, CU_TENSOR_MAP_DATA_TYPE_BFLOAT16, 3, const_cast<void*>(ptr), gd, gs, bx, es, CU_TENSOR_MAP_INTERLEAVE_NONE,
      CU_TENSOR_MAP_SWIZZLE_128B, CU_TENSOR_MAP_L2_PROMOTION_L2_128B, CU_TENSOR_MAP_FLOAT_OOB_FILL_NONE);
  return m;
}

}

extern "C" void kernel_launch(void* const* d_in, const int* in_sizes, int n_in, void* d_out, int out_size) {
  const bf16* x      = (const bf16*)d_in[0];
  const bf16* kc     = (const bf16*)d_in[1];
  const bf16* vc     = (const bf16*)d_in[2];
  const bf16* wq     = (const bf16*)d_in[3];
  const bf16* wo     = (const bf16*)d_in[4];
  const bf16* w_r    = (const bf16*)d_in[6];
  const bf16* w_gate = (const bf16*)d_in[7];
  const bf16* w_up   = (const bf16*)d_in[8];
  const bf16* w_down = (const bf16*)d_in[9];
  const bf16* cvec   = (const bf16*)d_in[10];
  const bf16* w_mod  = (const bf16*)d_in[11];
  bf16* out = (bf16*)d_out;

  static PFN_encodeTiled enc = nullptr;
  static void* p_hm = nullptr;
  if (!enc) {
    void* fn = nullptr; cudaDriverEntryPointQueryResult qres;
    cudaGetDriverEntryPoint("cuTensorMapEncodeTiled", &fn, cudaEnableDefault, &qres);
    enc = (PFN_encodeTiled)fn;
    cudaGetSymbolAddress(&p_hm, g_scr);
    cudaFuncSetAttribute(fused_kernel, cudaFuncAttributeMaxDynamicSharedMemorySize, (int)AT_SMEM);
  }
  const CUtensorMap tm_m   = make_map_2d(enc, w_mod, 6 * T_D, T_D, 6 * T_D * 2, 64, 256);
  const CUtensorMap tm_wq  = make_map_3d(enc, wq, T_DQKV, T_D, 64, 4);
  const CUtensorMap tm_k   = make_map_2d(enc, kc, T_DH, (uint64_t)T_NH * T_SEQ, T_DH * 2, 64, 128);
  const CUtensorMap tm_v   = make_map_2d(enc, vc, T_DH, (uint64_t)T_NH * T_SEQ, T_DH * 2, 64, 128);
  const CUtensorMap tm_ost = make_map_2d(enc, ((Scratch*)p_hm)->o, O_LD, T_SEQ, O_LD * 2, 64, 64);
  const CUtensorMap tm_old = make_map_2d(enc, ((Scratch*)p_hm)->o, O_LD, T_SEQ, O_LD * 2, 64, 128);
  const CUtensorMap tm_wo  = make_map_2d(enc, wo, T_D, T_DQKV, T_D * 2, 64, 64);
  const CUtensorMap tm_x   = make_map_2d(enc, x, T_D, T_SEQ, T_D * 2, 64, 128);
  const CUtensorMap tm_out = make_map_2d(enc, out, T_D, T_SEQ, T_D * 2, 64, 128);

#define TUNE_ARG
  fused_kernel<<<132, 384, AT_SMEM, cudaStreamPerThread>>>(x, cvec, w_mod, (Scratch*)p_hm, 0u, TUNE_ARG (const uint8_t*)wo, kc, vc, w_r, w_gate, w_up, w_down, out,
             tm_m, tm_wq, tm_k, tm_v, tm_ost, tm_old, tm_wo, tm_x, tm_out);
}
```

```cpp
#include <cuda_runtime.h>
#include <cuda_bf16.h>
#include <cuda.h>
#include <stdint.h>

namespace {

typedef __nv_bfloat16 bf16;

constexpr int T_SEQ = 2048, T_D = 1024, T_NH = 32, T_DH = 128, T_DQKV = 4096, T_F = 3584;

struct __align__(2048) TailMail {
  float4 part1[T_SEQ * 8];
  uint32_t key[256];
  uint4 cand[16 * 2 * 2 * 128];
  uint32_t cnt[32];
  float ypart[(T_F / 32) * 2 * T_D];
};
constexpr int O_LD = T_DQKV, O_H = 16 * T_DH;
struct __align__(2048) Scratch {
  TailMail mail;
  float mod[2 * T_D];
  float modu[16 * 512];
  float2 stat[T_SEQ * 2];
  uint32_t gkey[160];
  uint8_t col[8 * 1536];
  unsigned int hcnt[17 * 32];
  float scal[4];
  __align__(1024) bf16 o[T_SEQ * O_LD];
};
__device__ Scratch g_scr;
#define g_part1 hm->mail.part1
#define g_key hm->mail.key
#define g_cand hm->mail.cand
#define CNT_Y hm->mail.cnt
#define g_ypart hm->mail.ypart
#define g_col hm->col
#define g_scal hm->scal
#define g_hcnt hm->hcnt

__device__ __forceinline__ uint32_t smem_u32(const void* p) { return (uint32_t)__cvta_generic_to_shared(p); }
__device__ __forceinline__ void mbar_init(uint32_t bar, uint32_t cnt) { asm volatile("mbarrier.init.shared::cta.b64 [%0], %1;" :: "r"(bar), "r"(cnt)); }
__device__ __forceinline__ void mbar_expect_tx(uint32_t bar, uint32_t bytes) { asm volatile("mbarrier.arrive.expect_tx.shared::cta.b64 _, [%0], %1;" :: "r"(bar), "r"(bytes) : "memory"); }
__device__ __forceinline__ void mbar_arrive(uint32_t bar) { asm volatile("mbarrier.arrive.shared::cta.b64 _, [%0];" :: "r"(bar) : "memory"); }
__device__ __forceinline__ void mbar_wait(uint32_t bar, uint32_t parity) {
  asm volatile("{\n.reg .pred p;\nLAB_WAIT:\nmbarrier.try_wait.parity.shared::cta.b64 p, [%0], %1;\n@!p bra LAB_WAIT;\n}\n" :: "r"(bar), "r"(parity) : "memory");
}
__device__ __forceinline__ bool mbar_test(uint32_t bar, uint32_t parity) {
  uint32_t r; asm volatile("{\n.reg .pred p;\nmbarrier.test_wait.parity.shared::cta.b64 p, [%1], %2;\nselp.u32 %0, 1, 0, p;\n}\n" : "=r"(r) : "r"(bar), "r"(parity) : "memory");
  return r != 0;
}
__device__ __forceinline__ void fence_mbar_init() { asm volatile("fence.mbarrier_init.release.cluster;" ::: "memory"); }
__device__ __forceinline__ uint64_t policy_evict_first() {
  uint64_t p; asm volatile("createpolicy.fractional.L2::evict_first.b64 %0, 1.0;" : "=l"(p)); return p;
}
__device__ __forceinline__ void tma_load_2d_hint(uint32_t dst, const CUtensorMap* map, int c0, int c1, uint32_t bar, uint64_t pol) {
  asm volatile("cp.async.bulk.tensor.2d.shared::cluster.global.mbarrier::complete_tx::bytes.L2::cache_hint [%0], [%1, {%3, %4}], [%2], %5;"
    :: "r"(dst), "l"(map), "r"(bar), "r"(c0), "r"(c1), "l"(pol) : "memory");
}
__device__ __forceinline__ void tma_load_3d_hint(uint32_t dst, const CUtensorMap* map, int c1, int c2, uint32_t bar, uint64_t pol) {
  asm volatile("cp.async.bulk.tensor.3d.shared::cluster.global.mbarrier::complete_tx::bytes.L2::cache_hint [%0], [%1, {%6, %3, %4}], [%2], %5;"
    :: "r"(dst), "l"(map), "r"(bar), "r"(c1), "r"(c2), "l"(pol), "r"(0) : "memory");
}
__device__ __forceinline__ void tma_store_2d(const CUtensorMap* map, uint32_t src, int c0, int c1) {
  asm volatile("cp.async.bulk.tensor.2d.global.shared::cta.bulk_group [%0, {%2, %3}], [%1];" :: "l"(map), "r"(src), "r"(c0), "r"(c1) : "memory");
}
__device__ __forceinline__ void prefetch_tmap(const CUtensorMap* map) { asm volatile("prefetch.tensormap [%0];" :: "l"(map) : "memory"); }
__device__ __forceinline__ void l2_prefetch_bulk(const void* p, uint32_t bytes) {
  asm volatile("cp.async.bulk.prefetch.L2.global [%0], %1;" :: "l"(p), "r"(bytes) : "memory");
}
__device__ __forceinline__ void bulk_commit() { asm volatile("cp.async.bulk.commit_group;" ::: "memory"); }
template<int N> __device__ __forceinline__ void bulk_wait_read() { asm volatile("cp.async.bulk.wait_group.read %0;" :: "n"(N) : "memory"); }
template<int N> __device__ __forceinline__ void bulk_wait() { asm volatile("cp.async.bulk.wait_group %0;" :: "n"(N) : "memory"); }
__device__ __forceinline__ void named_bar_sync(int id, int nthreads) { asm volatile("bar.sync %0, %1;" :: "r"(id), "r"(nthreads) : "memory"); }
__device__ __forceinline__ void named_bar_arrive(int id, int nthreads) { asm volatile("bar.arrive %0, %1;" :: "r"(id), "r"(nthreads) : "memory"); }
__device__ __forceinline__ void wgmma_fence() { asm volatile("wgmma.fence.sync.aligned;" ::: "memory"); }
__device__ __forceinline__ void wgmma_commit() { asm volatile("wgmma.commit_group.sync.aligned;" ::: "memory"); }
template<int N> __device__ __forceinline__ void wgmma_wait() { asm volatile("wgmma.wait_group.sync.aligned %0;" :: "n"(N) : "memory"); }
template<int R> __device__ __forceinline__ void reg_alloc() { asm volatile("setmaxnreg.inc.sync.aligned.u32 %0;" :: "n"(R)); }
template<int R> __device__ __forceinline__ void reg_dealloc() { asm volatile("setmaxnreg.dec.sync.aligned.u32 %0;" :: "n"(R)); }
__device__ __forceinline__ bool elect_one() {
  uint32_t pred; asm volatile("{\n.reg .pred p;\nelect.sync _|p, 0xffffffff;\nselp.u32 %0, 1, 0, p;\n}\n" : "=r"(pred)); return pred != 0;
}
__device__ __forceinline__ uint32_t pack_bf16(float lo, float hi) {
  uint32_t r; asm("cvt.rn.bf16x2.f32 %0, %1, %2;" : "=r"(r) : "f"(hi), "f"(lo)); return r;
}
__device__ __forceinline__ void stmatrix_x4(uint32_t addr, uint32_t r0, uint32_t r1, uint32_t r2, uint32_t r3) {
  asm volatile("stmatrix.sync.aligned.m8n8.x4.shared.b16 [%0], {%1, %2, %3, %4};" :: "r"(addr), "r"(r0), "r"(r1), "r"(r2), "r"(r3) : "memory");
}
__device__ __forceinline__ void fence_proxy_async() { asm volatile("fence.proxy.async.shared::cta;" ::: "memory"); }
__device__ __forceinline__ float ex2_approx(float x) { float y; asm("ex2.approx.ftz.f32 %0, %1;" : "=f"(y) : "f"(x)); return y; }
template<int N> __device__ __forceinline__ void fence_regs(float (&r)[N]) {
  #pragma unroll
  for (int i = 0; i < N; i++) asm volatile("" : "+f"(r[i]) :: "memory");
}
template<int N> __device__ __forceinline__ void zero_regs(float (&r)[N]) {
  #pragma unroll
  for (int i = 0; i < N; i += 2) asm volatile("mov.b64 {%0, %1}, 0;" : "=f"(r[i]), "=f"(r[i + 1]));
}
__device__ __forceinline__ float rbf(float x) { return __uint_as_float(pack_bf16(0.f, x)); }
__device__ __forceinline__ float bflo(uint32_t v) { return __uint_as_float(v << 16); }
__device__ __forceinline__ float bfhi(uint32_t v) { return __uint_as_float(v & 0xffff0000u); }

#define TL_START(k) do {} while (0)
#define TL_END(k, cond) do {} while (0)
#define TL_CTA(i, cond) do {} while (0)
#define FS(slot, k) do {} while (0)
#define QS(idx) do {} while (0)
#define QDUMP() do {} while (0)
#define TL_MARK2(k, cond) do {} while (0)
#define TL_CLK(k, i, cond) do {} while (0)

#define HS(k) do {} while (0)
#define HSD(k, dep) do {} while (0)
#define HSDUMP() do {} while (0)
#define PS(k, cond) do {} while (0)
#define PSV(k, cond, v) do {} while (0)
#define PF(k) do {} while (0)
#define TS(k, cond) do {} while (0)
template <int OFFA, int OFFB>
__device__ __forceinline__ void wgmma_m64n256k16_ss_tb(float (&d)[128], uint32_t a_lo, uint32_t b_lo, int scaleD) {
  asm volatile("{\n.reg .pred p;\n.reg .b32 ta, tb;\n.reg .b64 da, db;\nsetp.ne.b32 p, %130, 0;\n"
    "add.u32 ta, %128, %131;\nadd.u32 tb, %129, %132;\n"
    "mov.b64 da, {ta, 0x40000040};\nmov.b64 db, {tb, 0x40000040};\n"
    "wgmma.mma_async.sync.aligned.m64n256k16.f32.bf16.bf16 "
    "{%0, %1, %2, %3, %4, %5, %6, %7, %8, %9, %10, %11, %12, %13, %14, %15, %16, %17, %18, %19, %20, %21, %22, %23, %24, %25, %26, %27, %28, %29, %30, %31, %32, %33, %34, %35, %36, %37, %38, %39, %40, %41, %42, %43, %44, %45, %46, %47, %48, %49, %50, %51, %52, %53, %54, %55, %56, %57, %58, %59, %60, %61, %62, %63, %64, %65, %66, %67, %68, %69, %70, %71, %72, %73, %74, %75, %76, %77, %78, %79, %80, %81, %82, %83, %84, %85, %86, %87, %88, %89, %90, %91, %92, %93, %94, %95, %96, %97, %98, %99, %100, %101, %102, %103, %104, %105, %106, %107, %108, %109, %110, %111, %112, %113, %114, %115, %116, %117, %118, %119, %120, %121, %122, %123, %124, %125, %126, %127}, "
    "da, db, p, 1, 1, 0, 1;\n}\n"
    : "+f"(d[0]), "+f"(d[1]), "+f"(d[2]), "+f"(d[3]), "+f"(d[4]), "+f"(d[5]), "+f"(d[6]), "+f"(d[7]), "+f"(d[8]), "+f"(d[9]), "+f"(d[10]), "+f"(d[11]), "+f"(d[12]), "+f"(d[13]), "+f"(d[14]), "+f"(d[15]), "+f"(d[16]), "+f"(d[17]), "+f"(d[18]), "+f"(d[19]), "+f"(d[20]), "+f"(d[21]), "+f"(d[22]), "+f"(d[23]), "+f"(d[24]), "+f"(d[25]), "+f"(d[26]), "+f"(d[27]), "+f"(d[28]), "+f"(d[29]), "+f"(d[30]), "+f"(d[31]), "+f"(d[32]), "+f"(d[33]), "+f"(d[34]), "+f"(d[35]), "+f"(d[36]), "+f"(d[37]), "+f"(d[38]), "+f"(d[39]), "+f"(d[40]), "+f"(d[41]), "+f"(d[42]), "+f"(d[43]), "+f"(d[44]), "+f"(d[45]), "+f"(d[46]), "+f"(d[47]), "+f"(d[48]), "+f"(d[49]), "+f"(d[50]), "+f"(d[51]), "+f"(d[52]), "+f"(d[53]), "+f"(d[54]), "+f"(d[55]), "+f"(d[56]), "+f"(d[57]), "+f"(d[58]), "+f"(d[59]), "+f"(d[60]), "+f"(d[61]), "+f"(d[62]), "+f"(d[63]), "+f"(d[64]), "+f"(d[65]), "+f"(d[66]), "+f"(d[67]), "+f"(d[68]), "+f"(d[69]), "+f"(d[70]), "+f"(d[71]), "+f"(d[72]), "+f"(d[73]), "+f"(d[74]), "+f"(d[75]), "+f"(d[76]), "+f"(d[77]), "+f"(d[78]), "+f"(d[79]), "+f"(d[80]), "+f"(d[81]), "+f"(d[82]), "+f"(d[83]), "+f"(d[84]), "+f"(d[85]), "+f"(d[86]), "+f"(d[87]), "+f"(d[88]), "+f"(d[89]), "+f"(d[90]), "+f"(d[91]), "+f"(d[92]), "+f"(d[93]), "+f"(d[94]), "+f"(d[95]), "+f"(d[96]), "+f"(d[97]), "+f"(d[98]), "+f"(d[99]), "+f"(d[100]), "+f"(d[101]), "+f"(d[102]), "+f"(d[103]), "+f"(d[104]), "+f"(d[105]), "+f"(d[106]), "+f"(d[107]), "+f"(d[108]), "+f"(d[109]), "+f"(d[110]), "+f"(d[111]), "+f"(d[112]), "+f"(d[113]), "+f"(d[114]), "+f"(d[115]), "+f"(d[116]), "+f"(d[117]), "+f"(d[118]), "+f"(d[119]), "+f"(d[120]), "+f"(d[121]), "+f"(d[122]), "+f"(d[123]), "+f"(d[124]), "+f"(d[125]), "+f"(d[126]), "+f"(d[127])
    : "r"(a_lo), "r"(b_lo), "r"(scaleD), "n"(OFFA), "n"(OFFB));
}

template <int OFFA, int OFFB>
__device__ __forceinline__ void wgmma_m64n128k16_ss_tb(float (&d)[64], uint32_t a_lo, uint32_t b_lo, int scaleD) {
  asm volatile("{\n.reg .pred p;\n.reg .b32 ta, tb;\n.reg .b64 da, db;\nsetp.ne.b32 p, %66, 0;\n"
    "add.u32 ta, %64, %67;\nadd.u32 tb, %65, %68;\n"
    "mov.b64 da, {ta, 0x40000040};\nmov.b64 db, {tb, 0x40000040};\n"
    "wgmma.mma_async.sync.aligned.m64n128k16.f32.bf16.bf16 "
    "{%0, %1, %2, %3, %4, %5, %6, %7, %8, %9, %10, %11, %12, %13, %14, %15, %16, %17, %18, %19, %20, %21, %22, %23, %24, %25, %26, %27, %28, %29, %30, %31, %32, %33, %34, %35, %36, %37, %38, %39, %40, %41, %42, %43, %44, %45, %46, %47, %48, %49, %50, %51, %52, %53, %54, %55, %56, %57, %58, %59, %60, %61, %62, %63}, "
    "da, db, p, 1, 1, 0, 1;\n}\n"
    : "+f"(d[0]), "+f"(d[1]), "+f"(d[2]), "+f"(d[3]), "+f"(d[4]), "+f"(d[5]), "+f"(d[6]), "+f"(d[7]), "+f"(d[8]), "+f"(d[9]), "+f"(d[10]), "+f"(d[11]), "+f"(d[12]), "+f"(d[13]), "+f"(d[14]), "+f"(d[15]), "+f"(d[16]), "+f"(d[17]), "+f"(d[18]), "+f"(d[19]), "+f"(d[20]), "+f"(d[21]), "+f"(d[22]), "+f"(d[23]), "+f"(d[24]), "+f"(d[25]), "+f"(d[26]), "+f"(d[27]), "+f"(d[28]), "+f"(d[29]), "+f"(d[30]), "+f"(d[31]), "+f"(d[32]), "+f"(d[33]), "+f"(d[34]), "+f"(d[35]), "+f"(d[36]), "+f"(d[37]), "+f"(d[38]), "+f"(d[39]), "+f"(d[40]), "+f"(d[41]), "+f"(d[42]), "+f"(d[43]), "+f"(d[44]), "+f"(d[45]), "+f"(d[46]), "+f"(d[47]), "+f"(d[48]), "+f"(d[49]), "+f"(d[50]), "+f"(d[51]), "+f"(d[52]), "+f"(d[53]), "+f"(d[54]), "+f"(d[55]), "+f"(d[56]), "+f"(d[57]), "+f"(d[58]), "+f"(d[59]), "+f"(d[60]), "+f"(d[61]), "+f"(d[62]), "+f"(d[63])
    : "r"(a_lo), "r"(b_lo), "r"(scaleD), "n"(OFFA), "n"(OFFB));
}

template <int OFFB>
__device__ __forceinline__ void wgmma_m64n256k16_rs_tb(float (&d)[128], uint32_t a0, uint32_t a1, uint32_t a2, uint32_t a3, uint32_t b_lo, int scaleD) {
  asm volatile("{\n.reg .pred p;\n.reg .b32 tb;\n.reg .b64 db;\nsetp.ne.b32 p, %133, 0;\n"
    "add.u32 tb, %132, %134;\n"
    "mov.b64 db, {tb, 0x40000040};\n"
    "wgmma.mma_async.sync.aligned.m64n256k16.f32.bf16.bf16 "
    "{%0, %1, %2, %3, %4, %5, %6, %7, %8, %9, %10, %11, %12, %13, %14, %15, %16, %17, %18, %19, %20, %21, %22, %23, %24, %25, %26, %27, %28, %29, %30, %31, %32, %33, %34, %35, %36, %37, %38, %39, %40, %41, %42, %43, %44, %45, %46, %47, %48, %49, %50, %51, %52, %53, %54, %55, %56, %57, %58, %59, %60, %61, %62, %63, %64, %65, %66, %67, %68, %69, %70, %71, %72, %73, %74, %75, %76, %77, %78, %79, %80, %81, %82, %83, %84, %85, %86, %87, %88, %89, %90, %91, %92, %93, %94, %95, %96, %97, %98, %99, %100, %101, %102, %103, %104, %105, %106, %107, %108, %109, %110, %111, %112, %113, %114, %115, %116, %117, %118, %119, %120, %121, %122, %123, %124, %125, %126, %127}, "
    "{%128, %129, %130, %131}, db, p, 1, 1, 1;\n}\n"
    : "+f"(d[0]), "+f"(d[1]), "+f"(d[2]), "+f"(d[3]), "+f"(d[4]), "+f"(d[5]), "+f"(d[6]), "+f"(d[7]), "+f"(d[8]), "+f"(d[9]), "+f"(d[10]), "+f"(d[11]), "+f"(d[12]), "+f"(d[13]), "+f"(d[14]), "+f"(d[15]), "+f"(d[16]), "+f"(d[17]), "+f"(d[18]), "+f"(d[19]), "+f"(d[20]), "+f"(d[21]), "+f"(d[22]), "+f"(d[23]), "+f"(d[24]), "+f"(d[25]), "+f"(d[26]), "+f"(d[27]), "+f"(d[28]), "+f"(d[29]), "+f"(d[30]), "+f"(d[31]), "+f"(d[32]), "+f"(d[33]), "+f"(d[34]), "+f"(d[35]), "+f"(d[36]), "+f"(d[37]), "+f"(d[38]), "+f"(d[39]), "+f"(d[40]), "+f"(d[41]), "+f"(d[42]), "+f"(d[43]), "+f"(d[44]), "+f"(d[45]), "+f"(d[46]), "+f"(d[47]), "+f"(d[48]), "+f"(d[49]), "+f"(d[50]), "+f"(d[51]), "+f"(d[52]), "+f"(d[53]), "+f"(d[54]), "+f"(d[55]), "+f"(d[56]), "+f"(d[57]), "+f"(d[58]), "+f"(d[59]), "+f"(d[60]), "+f"(d[61]), "+f"(d[62]), "+f"(d[63]), "+f"(d[64]), "+f"(d[65]), "+f"(d[66]), "+f"(d[67]), "+f"(d[68]), "+f"(d[69]), "+f"(d[70]), "+f"(d[71]), "+f"(d[72]), "+f"(d[73]), "+f"(d[74]), "+f"(d[75]), "+f"(d[76]), "+f"(d[77]), "+f"(d[78]), "+f"(d[79]), "+f"(d[80]), "+f"(d[81]), "+f"(d[82]), "+f"(d[83]), "+f"(d[84]), "+f"(d[85]), "+f"(d[86]), "+f"(d[87]), "+f"(d[88]), "+f"(d[89]), "+f"(d[90]), "+f"(d[91]), "+f"(d[92]), "+f"(d[93]), "+f"(d[94]), "+f"(d[95]), "+f"(d[96]), "+f"(d[97]), "+f"(d[98]), "+f"(d[99]), "+f"(d[100]), "+f"(d[101]), "+f"(d[102]), "+f"(d[103]), "+f"(d[104]), "+f"(d[105]), "+f"(d[106]), "+f"(d[107]), "+f"(d[108]), "+f"(d[109]), "+f"(d[110]), "+f"(d[111]), "+f"(d[112]), "+f"(d[113]), "+f"(d[114]), "+f"(d[115]), "+f"(d[116]), "+f"(d[117]), "+f"(d[118]), "+f"(d[119]), "+f"(d[120]), "+f"(d[121]), "+f"(d[122]), "+f"(d[123]), "+f"(d[124]), "+f"(d[125]), "+f"(d[126]), "+f"(d[127])
    : "r"(a0), "r"(a1), "r"(a2), "r"(a3), "r"(b_lo), "r"(scaleD), "n"(OFFB));
}

template <int OFFB>
__device__ __forceinline__ void wgmma_m64n128k16_rs_tb(float (&d)[64], uint32_t a0, uint32_t a1, uint32_t a2, uint32_t a3, uint32_t b_lo, int scaleD) {
  asm volatile("{\n.reg .pred p;\n.reg .b32 tb;\n.reg .b64 db;\nsetp.ne.b32 p, %69, 0;\n"
    "add.u32 tb, %68, %70;\n"
    "mov.b64 db, {tb, 0x40000040};\n"
    "wgmma.mma_async.sync.aligned.m64n128k16.f32.bf16.bf16 "
    "{%0, %1, %2, %3, %4, %5, %6, %7, %8, %9, %10, %11, %12, %13, %14, %15, %16, %17, %18, %19, %20, %21, %22, %23, %24, %25, %26, %27, %28, %29, %30, %31, %32, %33, %34, %35, %36, %37, %38, %39, %40, %41, %42, %43, %44, %45, %46, %47, %48, %49, %50, %51, %52, %53, %54, %55, %56, %57, %58, %59, %60, %61, %62, %63}, "
    "{%64, %65, %66, %67}, db, p, 1, 1, 1;\n}\n"
    : "+f"(d[0]), "+f"(d[1]), "+f"(d[2]), "+f"(d[3]), "+f"(d[4]), "+f"(d[5]), "+f"(d[6]), "+f"(d[7]), "+f"(d[8]), "+f"(d[9]), "+f"(d[10]), "+f"(d[11]), "+f"(d[12]), "+f"(d[13]), "+f"(d[14]), "+f"(d[15]), "+f"(d[16]), "+f"(d[17]), "+f"(d[18]), "+f"(d[19]), "+f"(d[20]), "+f"(d[21]), "+f"(d[22]), "+f"(d[23]), "+f"(d[24]), "+f"(d[25]), "+f"(d[26]), "+f"(d[27]), "+f"(d[28]), "+f"(d[29]), "+f"(d[30]), "+f"(d[31]), "+f"(d[32]), "+f"(d[33]), "+f"(d[34]), "+f"(d[35]), "+f"(d[36]), "+f"(d[37]), "+f"(d[38]), "+f"(d[39]), "+f"(d[40]), "+f"(d[41]), "+f"(d[42]), "+f"(d[43]), "+f"(d[44]), "+f"(d[45]), "+f"(d[46]), "+f"(d[47]), "+f"(d[48]), "+f"(d[49]), "+f"(d[50]), "+f"(d[51]), "+f"(d[52]), "+f"(d[53]), "+f"(d[54]), "+f"(d[55]), "+f"(d[56]), "+f"(d[57]), "+f"(d[58]), "+f"(d[59]), "+f"(d[60]), "+f"(d[61]), "+f"(d[62]), "+f"(d[63])
    : "r"(a0), "r"(a1), "r"(a2), "r"(a3), "r"(b_lo), "r"(scaleD), "n"(OFFB));
}

template <int OFFB>
__device__ __forceinline__ void wgmma_m64n128k16_rs(float (&d)[64], uint32_t a0, uint32_t a1, uint32_t a2, uint32_t a3, uint32_t b_lo, int scaleD) {
  asm volatile("{\n.reg .pred p;\n.reg .b32 tb;\n.reg .b64 db;\nsetp.ne.b32 p, %69, 0;\n"
    "add.u32 tb, %68, %70;\n"
    "mov.b64 db, {tb, 0x40000040};\n"
    "wgmma.mma_async.sync.aligned.m64n128k16.f32.bf16.bf16 "
    "{%0, %1, %2, %3, %4, %5, %6, %7, %8, %9, %10, %11, %12, %13, %14, %15, %16, %17, %18, %19, %20, %21, %22, %23, %24, %25, %26, %27, %28, %29, %30, %31, %32, %33, %34, %35, %36, %37, %38, %39, %40, %41, %42, %43, %44, %45, %46, %47, %48, %49, %50, %51, %52, %53, %54, %55, %56, %57, %58, %59, %60, %61, %62, %63}, "
    "{%64, %65, %66, %67}, db, p, 1, 1, 0;\n}\n"
    : "+f"(d[0]), "+f"(d[1]), "+f"(d[2]), "+f"(d[3]), "+f"(d[4]), "+f"(d[5]), "+f"(d[6]), "+f"(d[7]), "+f"(d[8]), "+f"(d[9]), "+f"(d[10]), "+f"(d[11]), "+f"(d[12]), "+f"(d[13]), "+f"(d[14]), "+f"(d[15]), "+f"(d[16]), "+f"(d[17]), "+f"(d[18]), "+f"(d[19]), "+f"(d[20]), "+f"(d[21]), "+f"(d[22]), "+f"(d[23]), "+f"(d[24]), "+f"(d[25]), "+f"(d[26]), "+f"(d[27]), "+f"(d[28]), "+f"(d[29]), "+f"(d[30]), "+f"(d[31]), "+f"(d[32]), "+f"(d[33]), "+f"(d[34]), "+f"(d[35]), "+f"(d[36]), "+f"(d[37]), "+f"(d[38]), "+f"(d[39]), "+f"(d[40]), "+f"(d[41]), "+f"(d[42]), "+f"(d[43]), "+f"(d[44]), "+f"(d[45]), "+f"(d[46]), "+f"(d[47]), "+f"(d[48]), "+f"(d[49]), "+f"(d[50]), "+f"(d[51]), "+f"(d[52]), "+f"(d[53]), "+f"(d[54]), "+f"(d[55]), "+f"(d[56]), "+f"(d[57]), "+f"(d[58]), "+f"(d[59]), "+f"(d[60]), "+f"(d[61]), "+f"(d[62]), "+f"(d[63])
    : "r"(a0), "r"(a1), "r"(a2), "r"(a3), "r"(b_lo), "r"(scaleD), "n"(OFFB));
}

__device__ __forceinline__ uint4 ldg_nc_v4(const void* p) {
  uint4 v;
    asm volatile("{\n.reg .b64 pol;\ncreatepolicy.fractional.L2::evict_first.b64 pol, 1.0;\n"
                 "ld.global.nc.L1::no_allocate.L2::cache_hint.v4.u32 {%0, %1, %2, %3}, [%4], pol;\n}\n" : "=r"(v.x), "=r"(v.y), "=r"(v.z), "=r"(v.w) : "l"(p));
  return v;
}
__device__ __forceinline__ uint64_t pol_normal() {
  uint64_t p; asm volatile("createpolicy.fractional.L2::evict_normal.b64 %0, 1.0;" : "=l"(p)); return p;
}
__device__ __forceinline__ float rcp_approx(float x) { float y; asm("rcp.approx.ftz.f32 %0, %1;" : "=f"(y) : "f"(x)); return y; }
__device__ __forceinline__ float sigmoid_f(float v) { return rcp_approx(1.0f + ex2_approx(v * -1.4426950408889634f)); }
__device__ __forceinline__ float silu_bf(float v) { return rbf(v * sigmoid_f(v)); }
__device__ __forceinline__ uint32_t rank_key(float r, int idx) {
  const uint32_t b = __float_as_uint(r) >> 16;
  const uint32_t u = (r != r) ? 0u : ((b & 0x8000u) ? (~b & 0xffffu) : (b | 0x8000u));
  return (u << 16) | (0xffffu - (uint32_t)idx);
}
__device__ __forceinline__ void warp_top2(uint32_t& k1, uint32_t& k2) {
  const uint32_t m1 = __reduce_max_sync(0xffffffffu, k1);
  k2 = __reduce_max_sync(0xffffffffu, k1 == m1 ? k2 : k1);
  k1 = m1;
}
__device__ __forceinline__ uint32_t bmul2(uint32_t a, uint32_t b) { uint32_t r; asm("mul.rn.bf16x2 %0, %1, %2;" : "=r"(r) : "r"(a), "r"(b)); return r; }
__device__ __forceinline__ uint32_t badd2(uint32_t a, uint32_t b) { uint32_t r; asm("add.rn.bf16x2 %0, %1, %2;" : "=r"(r) : "r"(a), "r"(b)); return r; }
__device__ __forceinline__ uint32_t bsub2(uint32_t a, uint32_t b) { uint32_t r; asm("sub.rn.bf16x2 %0, %1, %2;" : "=r"(r) : "r"(a), "r"(b)); return r; }
__device__ __forceinline__ float sqrt_approx(float x) { float y; asm("sqrt.approx.f32 %0, %1;" : "=f"(y) : "f"(x)); return y; }
__device__ __forceinline__ uint32_t ln_norm2(uint32_t x1, uint32_t mb2, float inv) {
  const uint32_t d = bsub2(x1, mb2);
  return pack_bf16(bflo(d) * inv, bfhi(d) * inv);
}
__device__ __forceinline__ uint32_t ln_mod2(uint32_t x1, uint32_t mb2, float inv, uint32_t c1, uint32_t sb) { return badd2(bmul2(ln_norm2(x1, mb2, inv), c1), sb); }
__device__ __forceinline__ void ldmatrix_x4(uint32_t addr, uint32_t& r0, uint32_t& r1, uint32_t& r2, uint32_t& r3) {
  asm volatile("ldmatrix.sync.aligned.m8n8.x4.shared.b16 {%0, %1, %2, %3}, [%4];" : "=r"(r0), "=r"(r1), "=r"(r2), "=r"(r3) : "r"(addr) : "memory");
}
__device__ __forceinline__ uint4 ldg_stream_v4(const void* p, uint64_t pol) {
  uint4 v; asm volatile("ld.global.nc.L1::no_allocate.L2::cache_hint.L2::128B.v4.u32 {%0, %1, %2, %3}, [%4], %5;" : "=r"(v.x), "=r"(v.y), "=r"(v.z), "=r"(v.w) : "l"(p), "l"(pol)); return v;
}
__device__ __forceinline__ void bulk_load_hint(uint32_t dst, const void* src, uint32_t bytes, uint32_t bar, uint64_t pol) {
  asm volatile("cp.async.bulk.shared::cluster.global.mbarrier::complete_tx::bytes.L2::cache_hint [%0], [%1], %2, [%3], %4;"
    :: "r"(dst), "l"(src), "r"(bytes), "r"(bar), "l"(pol) : "memory");
}
__device__ __forceinline__ void red_release_add(unsigned int* p, unsigned int v) { asm volatile("red.release.gpu.global.add.u32 [%0], %1;" :: "l"(p), "r"(v) : "memory"); }
__device__ __forceinline__ unsigned int ld_acquire(const unsigned int* p) { unsigned int v; asm volatile("ld.acquire.gpu.global.u32 %0, [%1];" : "=r"(v) : "l"(p) : "memory"); return v; }
__device__ __forceinline__ void spin_until(const unsigned int* p, unsigned int target) {
  #pragma unroll 1
  for (unsigned int i = 0; i < (1u << 22); i++) { if (ld_acquire(p) >= target) return; }
}
__device__ __forceinline__ float lds_f32(uint32_t a) { float v; asm volatile("ld.shared.f32 %0, [%1];" : "=f"(v) : "r"(a) : "memory"); return v; }
__device__ __forceinline__ uint2 lds_u32x2(uint32_t a) { uint2 v; asm volatile("ld.shared.v2.u32 {%0, %1}, [%2];" : "=r"(v.x), "=r"(v.y) : "r"(a) : "memory"); return v; }
__device__ __forceinline__ uint32_t lds_u32(uint32_t a) { uint32_t v; asm volatile("ld.shared.u32 %0, [%1];" : "=r"(v) : "r"(a) : "memory"); return v; }
__device__ __forceinline__ void sts_u32(uint32_t a, uint32_t v) { asm volatile("st.shared.u32 [%0], %1;" :: "r"(a), "r"(v) : "memory"); }
__device__ __forceinline__ void sts_u32x2(uint32_t a, uint32_t x, uint32_t y) { asm volatile("st.shared.v2.u32 [%0], {%1, %2};" :: "r"(a), "r"(x), "r"(y) : "memory"); }
__device__ __forceinline__ void sts_f32(uint32_t a, float v) { asm volatile("st.shared.f32 [%0], %1;" :: "r"(a), "f"(v) : "memory"); }
__device__ __forceinline__ void sts_f32x4(uint32_t a, float x, float y, float z, float w) { asm volatile("st.shared.v4.f32 [%0], {%1, %2, %3, %4};" :: "r"(a), "f"(x), "f"(y), "f"(z), "f"(w) : "memory"); }

__device__ __forceinline__ uint4 lds_u32x4(uint32_t a) { uint4 v; asm volatile("ld.shared.v4.u32 {%0, %1, %2, %3}, [%4];" : "=r"(v.x), "=r"(v.y), "=r"(v.z), "=r"(v.w) : "r"(a) : "memory"); return v; }
__device__ __forceinline__ void sts_u32x4(uint32_t a, uint32_t x, uint32_t y, uint32_t z, uint32_t w) { asm volatile("st.shared.v4.u32 [%0], {%1, %2, %3, %4};" :: "r"(a), "r"(x), "r"(y), "r"(z), "r"(w) : "memory"); }
__device__ __forceinline__ void st_tagged(float* p, float v) {
  const uint32_t b = __float_as_uint(v);
  asm volatile("st.relaxed.gpu.global.u32 [%0], %1;" :: "l"(p), "r"(b == 0u ? 0x80000000u : b) : "memory");
}
__device__ __forceinline__ void st_tagged4(float* p, float x, float y, float z, float w) {
  const uint32_t a = __float_as_uint(x), b = __float_as_uint(y), c = __float_as_uint(z), d = __float_as_uint(w);
  asm volatile("st.relaxed.gpu.global.v4.u32 [%0], {%1, %2, %3, %4};" :: "l"(p), "r"(a == 0u ? 0x80000000u : a), "r"(b == 0u ? 0x80000000u : b),
               "r"(c == 0u ? 0x80000000u : c), "r"(d == 0u ? 0x80000000u : d) : "memory");
}
__device__ __forceinline__ void st_relaxed2(void* p, uint32_t a, uint32_t b) { asm volatile("st.relaxed.gpu.global.v2.u32 [%0], {%1, %2};" :: "l"(p), "r"(a), "r"(b) : "memory"); }
__device__ __forceinline__ float4 ld_tagged4(const float* p) {
  float4 v; asm volatile("ld.relaxed.gpu.global.v4.f32 {%0, %1, %2, %3}, [%4];" : "=f"(v.x), "=f"(v.y), "=f"(v.z), "=f"(v.w) : "l"(p) : "memory"); return v;
}
__device__ __forceinline__ bool tagged4(const float4& v) {
  return __float_as_uint(v.x) != 0u && __float_as_uint(v.y) != 0u && __float_as_uint(v.z) != 0u && __float_as_uint(v.w) != 0u;
}
__device__ __forceinline__ void hint_arrive(uint32_t* p) { asm volatile("red.relaxed.gpu.global.add.u32 [%0], 1;" :: "l"(p) : "memory"); }
__device__ __forceinline__ void hint_wait(const uint32_t* p, uint32_t target) {
  uint32_t v = 0u;
  #pragma unroll 1
  for (unsigned int i = 0; i < (1u << 22) && v < target; i++) asm volatile("ld.relaxed.gpu.global.u32 %0, [%1];" : "=r"(v) : "l"(p) : "memory");
}
__device__ __forceinline__ void fence_proxy_async_global() { asm volatile("fence.proxy.async.global;" ::: "memory"); }

__device__ __forceinline__ void mma_bf16(float (&d)[4], uint32_t a0, uint32_t a1, uint32_t a2, uint32_t a3, uint32_t b0, uint32_t b1) {
  asm volatile("mma.sync.aligned.m16n8k16.row.col.f32.bf16.bf16.f32 {%0, %1, %2, %3}, {%4, %5, %6, %7}, {%8, %9}, {%0, %1, %2, %3};"
               : "+f"(d[0]), "+f"(d[1]), "+f"(d[2]), "+f"(d[3]) : "r"(a0), "r"(a1), "r"(a2), "r"(a3), "r"(b0), "r"(b1));
}
__device__ __forceinline__ uint32_t bfma2(uint32_t a, uint32_t b, uint32_t c) { uint32_t r; asm("fma.rn.bf16x2 %0, %1, %2, %3;" : "=r"(r) : "r"(a), "r"(b), "r"(c)); return r; }
#define XDLY 1000
#define PRE_T 1000
#define GDLY 4150
#define A_T 4800
#define SDLY 5800
#define ST1_T 6000
#define GDLY2 8000
#define WDLY 3800
#define W_OFF 2000
#define W_GAP 300
#define W_RND 3600
#define W_LATE 27000
#define CLR_T 70000
#define SGL_T 79000
#define OG_PRE 12
#define OG_LEN 6
#define WD_0 16
#define WD_S 6
#define NDUM 16
__device__ __forceinline__ uint32_t clock_lo() { uint32_t c; asm volatile("mov.u32 %0, %%clock;" : "=r"(c) :: "memory"); return c; }
__device__ __forceinline__ void wait_clock(uint32_t t0, uint32_t n) {
  #pragma unroll 1
  while (clock_lo() - t0 < n) {}
}
__device__ __forceinline__ void sleep_until(uint32_t t0, uint32_t n) {
  #pragma unroll 1
  while (clock_lo() - t0 < n) __nanosleep(500);
}
__device__ __forceinline__ float2 ld_tagged2(const float2* p) {
  float2 v; asm volatile("ld.relaxed.gpu.global.v2.f32 {%0, %1}, [%2];" : "=f"(v.x), "=f"(v.y) : "l"(p) : "memory"); return v;
}
template <int N>
__device__ __forceinline__ void gemv64(float (&d)[2][4], const uint4 (&w)[N], const uint32_t (&sv)[N / 2], int lane) {
  const int g = lane >> 2;
  const uint32_t lo = (g & 1) ? 0x1044u : 0x4410u, hi = (g & 1) ? 0x3244u : 0x4432u;
  const uint32_t lo0 = g < 2 ? lo : 0x4444u, hi0 = g < 2 ? hi : 0x4444u, lo1 = (g & 6) == 2 ? lo : 0x4444u, hi1 = (g & 6) == 2 ? hi : 0x4444u;
  #pragma unroll
  for (int i = 0; i < N; i++)
    mma_bf16(d[i & 1], w[i].x, w[i].y, w[i].z, w[i].w, __byte_perm(sv[i >> 1], 0u, (i & 1) ? hi0 : lo0), __byte_perm(sv[i >> 1], 0u, (i & 1) ? hi1 : lo1));
}
template <int NW>
__device__ __forceinline__ float gemv64_sum(const float (&d)[2][4], uint32_t scr, int t2) {
  if ((t2 & 2) == 0) sts_f32x4(scr + (t2 >> 2) * 32 + (t2 & 1) * 16, d[0][0] + d[1][0], d[0][1] + d[1][1], d[0][2] + d[1][2], d[0][3] + d[1][3]);
  named_bar_sync(NW == 8 ? 5 : 3, NW * 32);
  float sum = 0.f;
  #pragma unroll
  for (int i = 0; i < NW; i += 2) sum += lds_f32(scr + i * 256 + (t2 & 63) * 4) + lds_f32(scr + i * 256 + 256 + (t2 & 63) * 4);
  return sum;
}
__device__ __forceinline__ uint32_t silu2(uint32_t c) { return pack_bf16(silu_bf(bflo(c)), silu_bf(bfhi(c))); }
__device__ __forceinline__ void head_first(Scratch* hm, uint32_t scr, int t2, const bf16* __restrict__ cvec, const bf16* __restrict__ w_mod) {
  const int row = (blockIdx.x >> 3) * 64 + (t2 >> 5) * 16 + (t2 & 3) * 4;
  const bf16* wp = w_mod + (size_t)row * (6 * T_D) + (blockIdx.x & 4) * 256 + (blockIdx.x & 3) * 64 + (t2 & 28) * 2;
  uint4 w[4];
  #pragma unroll
  for (int i = 0; i < 4; i++) w[i] = ldg_nc_v4(wp + i * 6 * T_D);
  const uint2 c = *reinterpret_cast<const uint2*>(cvec + row);
  const uint32_t sv[2] = {silu2(c.x), silu2(c.y)};
  float d[2][4] = {{0.f, 0.f, 0.f, 0.f}, {0.f, 0.f, 0.f, 0.f}};
  gemv64<4>(d, w, sv, t2 & 31);
  const float sum = gemv64_sum<4>(d, scr, t2);
  if (t2 < 64) st_tagged(hm->modu + (blockIdx.x >> 3) * 512 + (blockIdx.x & 7) * 64 + t2, sum);
  HS(1);
}
__device__ __forceinline__ void head_stats(Scratch* hm, uint32_t xs, uint32_t b_x, int tid) {
  const int lane = tid & 31, w = tid >> 5, g = lane >> 2;
  float d[4][4] = {{0.f, 0.f, 0.f, 0.f}, {0.f, 0.f, 0.f, 0.f}, {0.f, 0.f, 0.f, 0.f}, {0.f, 0.f, 0.f, 0.f}};
  const uint32_t xa = xs + ((w & 1) * 8 + g) * 2048 + (w >> 1) * 1024 + (g & 1) * 64 + (lane & 3) * 16;
  float2* dst = hm->stat + ((blockIdx.x * 2 + (w & 1)) * 2 + (w >> 1)) * 8 + g;
  mbar_wait(b_x, 0);
  #pragma unroll
  for (int j = 0; j < 16; j++) {
    const uint4 v = lds_u32x4((xa ^ ((j & 1) * 64)) + (j >> 1) * 128);
    mma_bf16(d[2 * (j & 1)], v.x, 0x3F803F80u, v.y, 0x3F803F80u, v.x, v.y);
    mma_bf16(d[2 * (j & 1) + 1], v.z, 0x3F803F80u, v.w, 0x3F803F80u, v.z, v.w);
  }
  #pragma unroll
  for (int e = 0; e < 4; e++) d[0][e] = (d[0][e] + d[1][e]) + (d[2][e] + d[3][e]);
  const uint32_t sm = __float_as_uint((g & 1) ? d[0][3] : d[0][2]), sq = __float_as_uint((g & 1) ? d[0][1] : d[0][0]);
  if ((lane & 3) == (g >> 1)) st_relaxed2(dst, sm == 0u ? 0x80000000u : sm, sq == 0u ? 0x80000000u : sq);
  HSD(3, sm);
}
__device__ __forceinline__ void put_table(uint32_t tab, int l, bool ca, const float4& v) {
  uint32_t m0 = pack_bf16(v.x, v.y), m1 = pack_bf16(v.z, v.w);
  if (ca) { m0 = badd2(m0, 0x3F803F80u); m1 = badd2(m1, 0x3F803F80u); }
  tab += (l >> 2) * 64 + (l & 1) * 32 + (l & 2) * 2 + (ca ? 0 : 8);
  sts_u32(tab, m0); sts_u32(tab + 16, m1);
}
__device__ __forceinline__ void head_gather(Scratch* hm, uint32_t tab, int tid) {
  float4 p[16];
  #pragma unroll 1
  for (unsigned int spin = 0; spin < (1u << 22); spin++) {
    uint32_t m = 0xffffffffu;
    #pragma unroll
    for (int k = 0; k < 16; k++) p[k] = ld_tagged4(hm->modu + k * 512 + tid * 4);
    #pragma unroll
    for (int k = 0; k < 16; k++) m = min(min(m, min(__float_as_uint(p[k].x), __float_as_uint(p[k].y))), min(__float_as_uint(p[k].z), __float_as_uint(p[k].w)));
    if (m != 0u) break;
  }
  #pragma unroll
  for (int o = 1; o < 16; o <<= 1)
    #pragma unroll
    for (int k = 0; k < 16; k += 2 * o) { p[k].x += p[k + o].x; p[k].y += p[k + o].y; p[k].z += p[k + o].z; p[k].w += p[k + o].w; }
  put_table(tab, tid & 63, tid >= 64, p[0]);
  __syncwarp();
  HS(2);
}
__device__ __forceinline__ uint32_t ln_stat(float sm, float sq) {
  const float mean = sm * (1.0f / T_D), var = fmaxf(fmaf(-mean, mean, sq * (1.0f / T_D)), 0.f);
  return pack_bf16(mean, sqrt_approx(rbf(rbf(var) + 1e-05f)));
}
__device__ __forceinline__ void gather_table(Scratch* hm, uint32_t tab0, uint32_t b_tab, int a, int lane) {
  #pragma unroll 1
  for (int r = 2; r < 8; r++) {
    float4 v;
    #pragma unroll 1
    for (unsigned int spin = 0; spin < (1u << 22); spin++) {
      v = ld_tagged4(hm->mod + a * T_D + r * 128 + lane * 4);
      if (__all_sync(0xffffffffu, tagged4(v))) break;
      __nanosleep(50);
    }
    put_table(tab0 + r * 512, lane, a, v);
    __syncwarp();
    if (lane == 0) mbar_arrive(b_tab + 8 * r);
    if (r < 6) HS(2 + r);
  }
}

__device__ __forceinline__ uint32_t assign_tile(Scratch* hm, uint32_t t0, int lane) {
  uint32_t me; asm("mov.u32 %0, %%smid;" : "=r"(me));
  me = (me & 255u) + 1u;
  if (lane == 0) asm volatile("st.relaxed.gpu.global.u32 [%0], %1;" :: "l"(hm->gkey + blockIdx.x), "r"((t0 & ~511u) | me) : "memory");
  uint32_t k[5];
  #pragma unroll 1
  for (unsigned int spin = 0; spin < (1u << 20); spin++) {
    __nanosleep(200);
    #pragma unroll
    for (int m = 0; m < 5; m++) asm volatile("ld.relaxed.gpu.global.u32 %0, [%1];" : "=r"(k[m]) : "l"(hm->gkey + m * 32 + lane) : "memory");
    if (__all_sync(0xffffffffu, k[0] != 0u && k[1] != 0u && k[2] != 0u && k[3] != 0u && (k[4] != 0u || lane >= 4))) break;
  }
  uint32_t sz = 0u, g = 0u, rank = 0u, w[5];
  #pragma unroll
  for (int m = 0; m < 5; m++) w[m] = k[m] == 0u ? 0u : (k[m] & 511u) < me ? 257u : (k[m] & 511u) == me ? 65537u : 1u;
  #pragma unroll 1
  for (int i = 0; i < 16; i++) {
    const uint32_t v = __reduce_max_sync(0xffffffffu, max(max(max(k[0], k[1]), max(k[2], k[3])), k[4])), lo = (i == 15 || v < 2048u) ? 0u : v - 2048u;
    uint32_t n = 0u;
    #pragma unroll
    for (int m = 0; m < 5; m++) { const bool in = k[m] >= lo; n += in ? w[m] : 0u; w[m] = in ? 0u : w[m]; k[m] = in ? 0u : k[m]; }
    n = __reduce_add_sync(0xffffffffu, n);
    if (lane == i) sz = n & 255u;
    if (n >> 16) { g = i; rank = (n >> 8) & 255u; }
  }
  #pragma unroll 1
  for (int d = 0; d < 4; d += 2)
    if ((__reduce_max_sync(0xffffffffu, sz * 32u + lane) & 31u) == (uint32_t)lane) sz -= 2;
  const uint32_t gs = __shfl_sync(0xffffffffu, sz, g);
  const uint32_t off = __reduce_add_sync(0xffffffffu, (sz != 16u) * 32u + lane < (gs != 16u) * 32u + g ? sz : 0u);
  return rank < gs ? off + rank : 128u;
}

__device__ __forceinline__ int col_pos(int c) { return (c & ~31) + ((c >> 1) & 3) * 8 + ((c >> 3) & 3) * 2 + (c & 1); }
__device__ __forceinline__ int mod_col0(int j, int b) { return b < 0 ? (j & 1) * T_D + (b + 4) * 256 + ((j >> 1) ^ 2) * 64 : 2 * T_D + j * 512 + b * 64; }
__device__ __noinline__ void mod_rest(Scratch* hm, uint32_t t0, uint32_t sbase, uint32_t bar, int t2, int j, const bf16* __restrict__ cvec, const bf16* __restrict__ w_r) {
  const uint32_t scr = sbase + 4 * 32768 + 8192;
  const int kind = j >> 1;
  const uint2 c4 = *reinterpret_cast<const uint2*>(cvec + t2 * 4);
  sts_u32x2(scr + t2 * 8, silu2(c4.x), silu2(c4.y));
  const int w8 = t2 >> 5, t = t2 & 3, g = (t2 >> 2) & 7;
  float dot = 0.f;
  uint32_t buf = 0, par = 0;
  named_bar_sync(5, 256);
  #pragma unroll 1
  for (int b = -3; b < 8; b++) {
    float d[2][4] = {{0.f, 0.f, 0.f, 0.f}, {0.f, 0.f, 0.f, 0.f}};
    #pragma unroll 1
    for (int k = 0; k < 4; k++) {
      const uint32_t wa = sbase + (buf + (buf > 2 ? 2 : 0)) * 32768 + w8 * 4096 + t * 256;
      uint4 w[8];
      uint32_t sv[4];
      #pragma unroll
      for (int i = 0; i < 4; i++) sv[i] = lds_u32(scr + k * 512 + w8 * 64 + i * 16 + t * 4);
      mbar_wait(bar + buf * 8, par);
      #pragma unroll
      for (int i = 0; i < 8; i++) w[i] = lds_u32x4(wa + (i >> 1) * 1024 + (i & 1) * 128 + ((g ^ (t * 2 + (i & 1))) << 4));
      gemv64<8>(d, w, sv, t2 & 31);
      named_bar_sync(5, 256);
      if (t2 == 0) sts_u32(bar + 40, b * 4 + k + 18);
      if (++buf == 5) { buf = 0; par ^= 1; }
    }
    const int c0 = mod_col0(j, b);
    float v = gemv64_sum<8>(d, scr + 2048, t2);
    if (t2 < 64) {
      if (b < 0) st_tagged(hm->mod + c0 + t2, v);
      else {
        const int col = (c0 + t2) & 1023;
        uint8_t* dst = g_col + (col >> 7) * 1536;
        v = rbf(v);
        if (kind == 2) v = rbf(1.0f + v);
        const float vw = v * __bfloat162float(w_r[col]);
        dot += vw;
        if (kind == 2) {
          reinterpret_cast<bf16*>(dst)[col_pos(col & 127)] = __float2bfloat16_rn(vw);
          reinterpret_cast<bf16*>(dst)[128 + col_pos(col & 127)] = __float2bfloat16_rn(vw - rbf(vw));
        }
        reinterpret_cast<bf16*>(dst + 512 + (kind == 0 ? 0 : kind == 2 ? 256 : kind == 1 ? 512 : 768))[col_pos(col & 127)] = __float2bfloat16_rn(v);
      }
    }
  }
  #pragma unroll
  for (int o = 16; o > 0; o >>= 1) dot += __shfl_xor_sync(0xffffffffu, dot, o);
  if (t2 == 32) sts_f32(scr + 4096, dot);
  fence_proxy_async();
  named_bar_sync(5, 256);
  if (t2 == 0 && (kind == 1 || kind == 2)) g_scal[(kind == 2 ? 0 : 2) + (j & 1)] = dot + lds_f32(scr + 4096);
  sleep_until(t0, CLR_T);
  #pragma unroll 1
  for (int i = j * 256 + t2; i < (int)(sizeof(TailMail) / 16); i += 8 * 256) reinterpret_cast<uint4*>(&hm->mail)[i] = make_uint4(0u, 0u, 0u, 0u);
  named_bar_sync(5, 256);
  if (t2 == 0) red_release_add(&g_hcnt[0], 1u);
  sleep_until(t0, SGL_T);
}

constexpr int AT_NBLK = T_SEQ / 128;
constexpr float AT_HEAD = 7.0f;
#define WOL 12
constexpr int WO_LATE = WOL;
#define QSTG 3
constexpr int QP_STAG = QSTG;
constexpr int AT_SPLIT = 28, AT_PIN = 8, PINB = 4;
constexpr int AT_NFULL = 124;
constexpr int AT_PREG = 40, AT_CREG = 232;
constexpr uint32_t AT_SQ = 5 * 32768;
constexpr float AT_C = 0.08838834764831845f * 1.4426950408889634f;
constexpr float AT_RAW_LO = -16.0f, AT_RAW_HI = 24.0f;
constexpr float AT_RAW_SUM = 281474976710656.0f, AT_RAW_MIN = 9.094947017729282e-13f;
constexpr uint32_t AT_SBAR = AT_SQ + 65536 + 256;
constexpr uint32_t AT_SMEM = AT_SQ + 65536 + 3072;

__device__ __forceinline__ uint32_t ring_slot(uint32_t t) { return t - 5u * ((t * 205u) >> 10); }
__device__ __forceinline__ uint32_t qp_pos(uint32_t j, uint32_t it) { return 4u * it + (j & 3u) + ((j & 3u) == 3u ? it : 0u); }
__device__ __forceinline__ uint32_t ring_par(uint32_t t) { return ((t * 205u) >> 10) & 1u; }
__device__ __forceinline__ void softmax_rowmax(const float (&s)[64], float& mx0, float& mx1) {
  float a0 = fmaxf(s[0], s[1]), a1 = fmaxf(s[4], s[5]), a2 = fmaxf(s[8], s[9]), a3 = fmaxf(s[12], s[13]);
  float b0 = fmaxf(s[2], s[3]), b1 = fmaxf(s[6], s[7]), b2 = fmaxf(s[10], s[11]), b3 = fmaxf(s[14], s[15]);
  #pragma unroll
  for (int j = 4; j < 16; j += 4) {
    a0 = fmaxf(a0, fmaxf(s[4 * j + 0], s[4 * j + 1]));  b0 = fmaxf(b0, fmaxf(s[4 * j + 2], s[4 * j + 3]));
    a1 = fmaxf(a1, fmaxf(s[4 * j + 4], s[4 * j + 5]));  b1 = fmaxf(b1, fmaxf(s[4 * j + 6], s[4 * j + 7]));
    a2 = fmaxf(a2, fmaxf(s[4 * j + 8], s[4 * j + 9]));  b2 = fmaxf(b2, fmaxf(s[4 * j + 10], s[4 * j + 11]));
    a3 = fmaxf(a3, fmaxf(s[4 * j + 12], s[4 * j + 13])); b3 = fmaxf(b3, fmaxf(s[4 * j + 14], s[4 * j + 15]));
  }
  mx0 = fmaxf(fmaxf(a0, a1), fmaxf(a2, a3));
  mx1 = fmaxf(fmaxf(b0, b1), fmaxf(b2, b3));
  mx0 = fmaxf(mx0, __shfl_xor_sync(0xffffffffu, mx0, 1));
  mx1 = fmaxf(mx1, __shfl_xor_sync(0xffffffffu, mx1, 1));
  mx0 = fmaxf(mx0, __shfl_xor_sync(0xffffffffu, mx0, 2));
  mx1 = fmaxf(mx1, __shfl_xor_sync(0xffffffffu, mx1, 2));
}
__device__ __forceinline__ void softmax_sub(float (&s)[64], float mc0, float mc1) {
  #pragma unroll
  for (int j = 0; j < 16; j++) { s[4 * j] -= mc0; s[4 * j + 1] -= mc0; s[4 * j + 2] -= mc1; s[4 * j + 3] -= mc1; }
}
template <int LO, int HI>
__device__ __forceinline__ void softmax_exp(float (&s)[64]) {
  #pragma unroll
  for (int i = LO; i < HI; i++) s[i] = ex2_approx(s[i]);
}
__device__ __forceinline__ bool softmax_mode(const float (&s)[64], float& mc0, float& mc1) {
  softmax_rowmax(s, mc0, mc1);
  const bool raw = __all_sync(0xffffffffu, mc0 >= AT_RAW_LO && mc0 <= AT_RAW_HI && mc1 >= AT_RAW_LO && mc1 <= AT_RAW_HI);
  mc0 += AT_HEAD; mc1 += AT_HEAD;
  return raw;
}
__device__ __forceinline__ void rowsum_p(const uint32_t (&p)[32], uint32_t& t0, uint32_t& t1) {
  uint32_t a[16];
  #pragma unroll
  for (int i = 0; i < 8; i++) { a[2 * i] = badd2(p[4 * i], p[4 * i + 2]); a[2 * i + 1] = badd2(p[4 * i + 1], p[4 * i + 3]); }
  #pragma unroll
  for (int i = 0; i < 4; i++) { a[2 * i] = badd2(a[4 * i], a[4 * i + 2]); a[2 * i + 1] = badd2(a[4 * i + 1], a[4 * i + 3]); }
  t0 = badd2(badd2(a[0], a[2]), badd2(a[4], a[6]));
  t1 = badd2(badd2(a[1], a[3]), badd2(a[5], a[7]));
}
__device__ __forceinline__ void add_rowsum(const uint32_t (&p)[32], float& l0, float& l1) {
  uint32_t t0, t1;
  rowsum_p(p, t0, t1);
  l0 += bflo(t0) + bfhi(t0); l1 += bflo(t1) + bfhi(t1);
}
__device__ __forceinline__ void pack_p(uint32_t (&p)[32], const float (&s)[64]) {
  #pragma unroll
  for (int i = 0; i < 32; i++) p[i] = pack_bf16(s[2 * i], s[2 * i + 1]);
}
__device__ __noinline__ void attn_rows_exact(uint32_t sq, int warp, int lane, const bf16* __restrict__ kh, const bf16* __restrict__ vh) {
  #pragma unroll 1
  for (int r = 16 * warp; r < 16 * warp + 16; r++) {
    const uint32_t ad = (lane >> 4) * 16384 + r * 128 + ((((lane & 15) >> 1) ^ (r & 7)) << 4) + (lane & 1) * 8;
    uint2 qv; asm volatile("ld.shared.v2.u32 {%0, %1}, [%2];" : "=r"(qv.x), "=r"(qv.y) : "r"(sq + ad) : "memory");
    const float q0 = bflo(qv.x), q1 = bfhi(qv.x), q2 = bflo(qv.y), q3 = bfhi(qv.y);
    float m = -INFINITY, l = 0.f, o0 = 0.f, o1 = 0.f, o2 = 0.f, o3 = 0.f;
    #pragma unroll 1
    for (int key = 0; key < T_SEQ; key++) {
      const uint2 kv = *reinterpret_cast<const uint2*>(kh + (size_t)key * T_DH + lane * 4);
      const uint2 vv = *reinterpret_cast<const uint2*>(vh + (size_t)key * T_DH + lane * 4);
      float sc = (q0 * bflo(kv.x) + q1 * bfhi(kv.x)) + (q2 * bflo(kv.y) + q3 * bfhi(kv.y));
      #pragma unroll
      for (int o = 16; o > 0; o >>= 1) sc += __shfl_xor_sync(0xffffffffu, sc, o);
      const float mn = fmaxf(m, sc);
      const float al = (m == mn) ? 1.0f : ex2_approx(m - mn), p = rbf(ex2_approx(sc - mn));
      m = mn;
      l = fmaf(l, al, p);
      o0 = fmaf(o0, al, p * bflo(vv.x)); o1 = fmaf(o1, al, p * bfhi(vv.x));
      o2 = fmaf(o2, al, p * bflo(vv.y)); o3 = fmaf(o3, al, p * bfhi(vv.y));
    }
    const float inv = rcp_approx(l);
    asm volatile("st.shared.v2.u32 [%0], {%1, %2};" :: "r"(sq + ad), "r"(pack_bf16(o0 * inv, o1 * inv)), "r"(pack_bf16(o2 * inv, o3 * inv)) : "memory");
  }
}
__device__ __forceinline__ void issue_qk(float (&s)[64], const uint32_t (&q)[32], uint32_t k_lo) {
  wgmma_fence();
  wgmma_m64n128k16_rs<0>(s, q[0], q[1], q[2], q[3], k_lo, 0);
  wgmma_m64n128k16_rs<2>(s, q[4], q[5], q[6], q[7], k_lo, 1);
  wgmma_m64n128k16_rs<4>(s, q[8], q[9], q[10], q[11], k_lo, 1);
  wgmma_m64n128k16_rs<6>(s, q[12], q[13], q[14], q[15], k_lo, 1);
  wgmma_m64n128k16_rs<1024>(s, q[16], q[17], q[18], q[19], k_lo, 1);
  wgmma_m64n128k16_rs<1026>(s, q[20], q[21], q[22], q[23], k_lo, 1);
  wgmma_m64n128k16_rs<1028>(s, q[24], q[25], q[26], q[27], k_lo, 1);
  wgmma_m64n128k16_rs<1030>(s, q[28], q[29], q[30], q[31], k_lo, 1);
  wgmma_commit();
}
__device__ __forceinline__ void issue_pv(float (&o)[64], const uint32_t (&p)[32], uint32_t v_lo, int accumulate) {
  wgmma_fence();
  wgmma_m64n128k16_rs_tb<0>(o, p[0], p[1], p[2], p[3], v_lo, accumulate);
  wgmma_m64n128k16_rs_tb<128>(o, p[4], p[5], p[6], p[7], v_lo, 1);
  wgmma_m64n128k16_rs_tb<256>(o, p[8], p[9], p[10], p[11], v_lo, 1);
  wgmma_m64n128k16_rs_tb<384>(o, p[12], p[13], p[14], p[15], v_lo, 1);
  wgmma_m64n128k16_rs_tb<512>(o, p[16], p[17], p[18], p[19], v_lo, 1);
  wgmma_m64n128k16_rs_tb<640>(o, p[20], p[21], p[22], p[23], v_lo, 1);
  wgmma_m64n128k16_rs_tb<768>(o, p[24], p[25], p[26], p[27], v_lo, 1);
  wgmma_m64n128k16_rs_tb<896>(o, p[28], p[29], p[30], p[31], v_lo, 1);
  wgmma_commit();
}
__device__ __forceinline__ void rescale_o(float (&o)[64], float al0, float al1) {
  #pragma unroll
  for (int j = 0; j < 16; j++) { o[4 * j] *= al0; o[4 * j + 1] *= al0; o[4 * j + 2] *= al1; o[4 * j + 3] *= al1; }
}

__device__ __forceinline__ void stage_o(const float (&o)[64], float i0, float i1, uint32_t dst, int lane) {
  #pragma unroll
  for (int J = 0; J < 16; J += 2)
    stmatrix_x4(dst + (J >> 3) * 16384 + ((((J & 7) + (lane >> 4)) ^ (lane & 7)) << 4),
                pack_bf16(o[4 * J + 0] * i0, o[4 * J + 1] * i0), pack_bf16(o[4 * J + 2] * i1, o[4 * J + 3] * i1),
                pack_bf16(o[4 * J + 4] * i0, o[4 * J + 5] * i0), pack_bf16(o[4 * J + 6] * i1, o[4 * J + 7] * i1));
}
__device__ __forceinline__ bool finish_l(float& l0, float& l1) {
  l0 += __shfl_xor_sync(0xffffffffu, l0, 1); l1 += __shfl_xor_sync(0xffffffffu, l1, 1);
  l0 += __shfl_xor_sync(0xffffffffu, l0, 2); l1 += __shfl_xor_sync(0xffffffffu, l1, 2);
  const bool redo = __any_sync(0xffffffffu, !(l0 <= AT_RAW_SUM && l1 <= AT_RAW_SUM && l0 >= AT_RAW_MIN && l1 >= AT_RAW_MIN));
  const float r = rcp_approx(l0 * l1), i0 = r * l1;
  l1 = r * l0; l0 = i0;
  return redo;
}
__device__ __forceinline__ void stage_qregs(const uint32_t (&q)[32], uint32_t dst, int lane) {
  #pragma unroll
  for (int J = 0; J < 16; J += 2)
    stmatrix_x4(dst + (J >> 3) * 16384 + ((((J & 7) + (lane >> 4)) ^ (lane & 7)) << 4), q[2 * J], q[2 * J + 1], q[2 * J + 2], q[2 * J + 3]);
}
__device__ __forceinline__ void store_o(const CUtensorMap* tmO, uint32_t src, int head, int row) {
  tma_store_2d(tmO, src, head * T_DH, row);
  tma_store_2d(tmO, src + 16384, head * T_DH + 64, row);
  bulk_commit();
}
struct GemvSel { uint32_t lo0, hi0, lo1, hi1; };
__device__ __forceinline__ GemvSel gemv_sel(int lane) {
  const uint32_t lo = (lane & 8) ? 0x1044u : 0x4410u, hi = (lane & 8) ? 0x3244u : 0x4432u;
  GemvSel s; s.lo0 = (lane & 16) ? 0x4444u : lo; s.hi0 = (lane & 16) ? 0x4444u : hi; s.lo1 = (lane & 16) ? lo : 0x4444u; s.hi1 = (lane & 16) ? hi : 0x4444u;
  return s;
}
#define GEMV_B0(j, h, s) __byte_perm((j) < 2 ? (h).x : (h).y, 0u, ((j) & 1) ? (s).hi0 : (s).lo0)
#define GEMV_B1(j, h, s) __byte_perm((j) < 2 ? (h).x : (h).y, 0u, ((j) & 1) ? (s).hi1 : (s).lo1)
__device__ __forceinline__ float4 gemv_out(const float (&d)[4], int lane) {
  const bool tk = lane & 1;
  const float r0 = __shfl_xor_sync(0xffffffffu, tk ? d[0] : d[1], 1), r1 = __shfl_xor_sync(0xffffffffu, tk ? d[2] : d[3], 1);
  return tk ? make_float4(r0, d[1], r1, d[3]) : make_float4(d[0], r0, d[2], r1);
}
#define OG_NG 8
#define OG_GRP (64 / OG_NG)
constexpr int OG_ST = 5, OG_NKB = T_DQKV / 64, OG_MOE = T_F / 32;
constexpr int OG_POS = 7;
constexpr uint32_t OG_STAGE = 32768;
constexpr uint32_t OG_SWD = AT_SQ;
constexpr uint32_t OG_SCOL = AT_SBAR + 512;
constexpr uint32_t OG_SMISC = AT_SBAR + 2048;
constexpr uint32_t OG_XSLOT = ((OG_POS + OG_NKB) % OG_ST) * OG_STAGE;
constexpr uint32_t OG_OSLOT = ((OG_POS + OG_NKB + 1) % OG_ST) * OG_STAGE;
constexpr uint32_t OG_SH2 = ((OG_POS + OG_NKB + 2) % OG_ST) * OG_STAGE;
constexpr uint32_t OG_SRED = ((OG_POS + OG_NKB + 3) % OG_ST) * OG_STAGE;
constexpr uint32_t OG_SSTAT = OG_SRED + 16384;
constexpr uint32_t OG_SGU = OG_SRED + 8192;
constexpr uint32_t OG_SFIN = OG_SGU + 256;
#define OGM 2
#define OG_MT(b) ((((b) >> OGM) & 15) ^ (((b) & 64) ? 15 : 0))
#define OG_NT(b) (((b) & ((1 << OGM) - 1)) + (((b) >> (4 + OGM)) << OGM))
#define TAIL_SETUP \
  const uint32_t bar_full = sbase + AT_SBAR, bar_empty = bar_full + 40; \
  const uint32_t bar_wd = bar_full + 168, bar_col = bar_full + 176, bar_out = bar_full + 184, bar_end = bar_full + 192; \
  const uint32_t bar_key = bar_full + 200, bar_h2 = bar_full + 208, bar_sel = bar_full + 216; \
  const int mt = OG_MT(bx), nt = OG_NT(bx); \
  const int m0 = mt * 128, n0 = nt * 128; \
  const bool has_moe = (int)bx < OG_MOE; \
  (void)bar_empty; (void)bar_wd; (void)bar_col; (void)bar_out; (void)bar_end; (void)bar_key; (void)bar_h2; (void)bar_sel; (void)m0; (void)n0; (void)has_moe;

__device__ __forceinline__ void tail_producer(Scratch* hm, uint32_t bx, uint32_t sbase, uint32_t ph, uint32_t obpar, uint64_t pol, const CUtensorMap* tmA, const CUtensorMap* tmB,
                                              const CUtensorMap* tmX, const bf16* __restrict__ w_down) {
  TAIL_SETUP
  const uint32_t b_ob = bar_full + 96, b_acq = bar_full + 256;
  uint32_t stage = OG_ST, wdd = sbase + OG_SWD;
  int wdk = has_moe ? WD_0 : 99;
  const uint8_t* wdp = (const uint8_t*)w_down + (size_t)bx * 65536;
  if (has_moe) mbar_expect_tx(bar_wd, 65536);
  mbar_expect_tx(bar_col, 1536 + 16);
  #pragma unroll 1
  for (int kb = 0; kb <= OG_NKB; kb++) {
    const uint32_t fb = bar_full + (kb ? 8 * stage : 248), sa = sbase + stage * OG_STAGE, sb = sa + 16384;
    mbar_wait(bar_empty + 8 * stage, kb ? ph : obpar);
    mbar_expect_tx(fb, OG_STAGE);
    if (kb < OG_NKB) {
      tma_load_2d_hint(sb, tmB, n0, kb * 64, fb, pol);
      tma_load_2d_hint(sb + 8192, tmB, n0 + 64, kb * 64, fb, pol);
      if ((kb & 31) == 0) { mbar_wait(b_acq + (kb >> 2), 0); fence_proxy_async_global(); }
      tma_load_2d_hint(sa, tmA, kb * 64, m0, fb, pol);
    } else {
      tma_load_2d_hint(sa, tmX, n0, m0, fb, pol);
      tma_load_2d_hint(sb, tmX, n0 + 64, m0, fb, pol);
    }
    if (kb == 32) {
      bulk_load_hint(sbase + OG_SCOL, g_col + nt * 1536, 1536, bar_col, pol);
      bulk_load_hint(sbase + OG_SMISC, g_scal, 16, bar_col, pol);
    }
    if (kb == wdk && kb < WD_0 + 8 * WD_S) {
      if (kb == WD_0) mbar_wait(b_ob, obpar);
      bulk_load_hint(wdd, wdp, 8192, bar_wd, pol);
      wdp += 8192; wdd += 8224; wdk += WD_S;
    }
    if (++stage == OG_ST) { stage = 0; ph ^= 1; }
    if (kb == 0) stage = (OG_POS + 1) % OG_ST;
  }
}

__device__ __forceinline__ uint32_t out2(uint32_t x1, uint32_t mb2, uint32_t ih, uint32_t il, uint32_t c1, uint32_t sb, uint32_t gb) {
  const uint32_t d = bsub2(x1, mb2);
  return bfma2(gb, bfma2(bfma2(d, ih, bmul2(d, il)), c1, sb), x1);
}
__device__ __forceinline__ void tail_exchange(Scratch* hm, uint32_t bx, uint32_t sbase, int wid, uint32_t tx, const CUtensorMap* tmOut, bf16* __restrict__ out) {
    TAIL_SETUP
    mbar_wait(bar_end, 0);
    const int lane = tx & 31;
    TL_MARK2(22, lane == 0);
    if (tx == 96) PF(5);
    if (wid == 0) {
      uint32_t k1 = 0u, k2 = 0u;
      #pragma unroll 1
      for (unsigned int spin = 0; spin < (1u << 22); spin++) {
        if (k1 == 0u) asm volatile("ld.relaxed.gpu.global.u32 %0, [%1];" : "=r"(k1) : "l"(g_key + lane) : "memory");
        if (__all_sync(0xffffffffu, k1 != 0u)) break;
      }
      TS(6, lane == 0);
      warp_top2(k1, k2);
      if (lane == 0) {
        const uint32_t r1 = 0xffffu - (k1 & 0xffffu), r2 = 0xffffu - (k2 & 0xffffu);
        sts_u32x4(sbase + OG_SMISC + 64, k1, k2, (r1 >> 7) * 2, (r2 >> 7) * 2 + ((r1 >> 7) == (r2 >> 7)));
        mbar_arrive(bar_sel);
      }
    } else if (wid < 3) {
      const uint32_t ch = lane & 15, ca = sbase + OG_SCOL + 768 + (ch >> 2) * 64 + (ch & 3) * 4;
      const uint4 c1 = make_uint4(lds_u32(ca), lds_u32(ca + 16), lds_u32(ca + 32), lds_u32(ca + 48)), sh = make_uint4(lds_u32(ca + 256), lds_u32(ca + 272), lds_u32(ca + 288), lds_u32(ca + 304));
      float* dst = reinterpret_cast<float*>(g_cand + (mt * 2 + (lane >> 4)) * 256 + nt * 16 + ch);
      mbar_wait(bar_key, 0);
      const uint4 kk = lds_u32x4(sbase + OG_SSTAT + 1024 + lane * 16);
      uint32_t k1 = max(kk.x, kk.y), k2 = min(kk.x, kk.y);
      k2 = max(max(k2, min(kk.z, kk.w)), min(k1, max(kk.z, kk.w))); k1 = max(k1, max(kk.z, kk.w));
      warp_top2(k1, k2);
      if (wid == 1) {
        if (lane == 0 && nt == (mt & 7)) st_relaxed2(g_key + mt * 2, k1, k2);
        TS(4, lane == 0);
      } else {
        const uint32_t r = (~((lane & 16) ? k2 : k1)) & 127u;
        const uint2 st = lds_u32x2(sbase + OG_SSTAT + r * 8);
        const uint4 xc = lds_u32x4(sbase + OG_XSLOT + (ch >> 3) * 16384 + r * 128 + (((ch ^ r) & 7) << 4));
        const float inr = __uint_as_float(st.y);
        const float h0 = __uint_as_float(ln_mod2(xc.x, st.x, inr, c1.x, sh.x)), h1 = __uint_as_float(ln_mod2(xc.y, st.x, inr, c1.y, sh.y));
        const float h2 = __uint_as_float(ln_mod2(xc.z, st.x, inr, c1.z, sh.z)), h3 = __uint_as_float(ln_mod2(xc.w, st.x, inr, c1.w, sh.w));
        st_tagged4(dst + 512, h0, h1, h2, h3);
        st_tagged4(dst, __uint_as_float(xc.x), __uint_as_float(xc.y), __uint_as_float(xc.z), __uint_as_float(xc.w));
      }
    }
    mbar_wait(bar_sel, 0);
    mbar_wait(bar_out, 0);
    {
      const int sel0 = 0xffff - (lds_u32(sbase + OG_SMISC + 64) & 0xffffu), sel1 = 0xffff - (lds_u32(sbase + OG_SMISC + 68) & 0xffffu);
      if ((sel0 >> 7) == mt || (sel1 >> 7) == mt) {
        #pragma unroll 2
        for (int i = 0; i < 16; i++) {
          const int r = i * 8 + (tx >> 4), ch = tx & 15;
          if (m0 + r != sel0 && m0 + r != sel1)
            *reinterpret_cast<uint4*>(out + (size_t)(m0 + r) * T_D + n0 + ch * 8) =
                lds_u32x4(sbase + OG_OSLOT + (ch >> 3) * 16384 + r * 128 + (((ch & 7) ^ (r & 7)) << 4));
        }
      } else if (tx == 96) {
        tma_store_2d(tmOut, sbase + OG_OSLOT, n0, m0);
        tma_store_2d(tmOut, sbase + OG_OSLOT + 16384, n0 + 64, m0);
        bulk_commit();
      }
      __syncwarp();
    }
    {
      const int tk = bx >> 6, c0 = (bx & 63) * 16;
      const uint32_t gb2 = *reinterpret_cast<const uint32_t*>(g_col + (c0 >> 7) * 1536 + 512 + 768 + col_pos((c0 & 127) + (tx & 14)) * 2);
      const float* src = g_ypart + (size_t)((tx >> 2) * 2 + tk) * T_D + c0 + (tx & 3) * 4;
      const bool four = tx < (OG_MOE - 96) * 4;
      mbar_wait(bar_h2, 0);
      float fx = 0.f, fh = 0.f, rs = 0.f;
      bf16* op = out;
      if (wid == 1) {
        const uint32_t key = lds_u32(sbase + OG_SMISC + 64 + tk * 4);
        const uint32_t* xp = reinterpret_cast<const uint32_t*>(g_cand + lds_u32(sbase + OG_SMISC + 72 + tk * 4) * 256) + ((c0 + (tx & 14)) >> 1);
        uint32_t x2 = 0u;
        #pragma unroll 1
        for (unsigned int spin = 0; spin < (1u << 20); spin++) { asm volatile("ld.relaxed.gpu.global.u32 %0, [%1];" : "=r"(x2) : "l"(xp) : "memory"); if (__all_sync(0xffffffffu, x2 != 0u)) break; }
        const uint32_t h2p = lds_u32(sbase + OG_SH2 + tk * 2048 + (c0 + (tx & 14)) * 2);
        fx = (lane & 1) ? bfhi(x2) : bflo(x2); fh = (lane & 1) ? bfhi(h2p) : bflo(h2p);
        rs = rbf(sigmoid_f(bfhi((key & 0x80000000u) ? key ^ 0x80000000u : ~key)));
        op += (size_t)(0xffffu - (key & 0xffffu)) * T_D + c0 + (lane & 15);
      }
      if (bx == 0 && tx < 68) g_hcnt[32 * (tx >> 2) + (tx & 3)] = 0u;
      if (tx < 64) hm->modu[bx * 64 + tx] = 0.f;
      else if (tx < 96) hm->stat[bx * 32 + tx - 64] = make_float2(0.f, 0.f);
      else if (tx < 112) hm->mod[bx * 16 + tx - 96] = 0.f;
      else if (tx < 114 && bx < 66) hm->gkey[bx * 2 + tx - 112] = 0u;
      if (tx == 0) hint_wait(CNT_Y, (uint32_t)OG_MOE);
      named_bar_sync(10, 128);
      TS(11, lane == 0);
      float4 p0, p1, p2, p3;
      #pragma unroll 1
      for (unsigned int spin = 0; spin < (1u << 20); spin++) {
        p0 = ld_tagged4(src); p1 = ld_tagged4(src + 64 * T_D); p2 = ld_tagged4(src + 128 * T_D); p3 = ld_tagged4(four ? src + 192 * T_D : src);
        if (__all_sync(0xffffffffu, tagged4(p0) & tagged4(p1) & tagged4(p2) & tagged4(p3))) break;
      }
      if (four) { p2.x += p3.x; p2.y += p3.y; p2.z += p3.z; p2.w += p3.w; }
      p0.x = (p0.x + p1.x) + p2.x; p0.y = (p0.y + p1.y) + p2.y; p0.z = (p0.z + p1.z) + p2.z; p0.w = (p0.w + p1.w) + p2.w;
      #pragma unroll
      for (int o = 4; o <= 16; o <<= 1) {
        p0.x += __shfl_xor_sync(0xffffffffu, p0.x, o); p0.y += __shfl_xor_sync(0xffffffffu, p0.y, o);
        p0.z += __shfl_xor_sync(0xffffffffu, p0.z, o); p0.w += __shfl_xor_sync(0xffffffffu, p0.w, o);
      }
      if (lane < 4) sts_f32x4(sbase + OG_SFIN + (tx >> 5) * 64 + lane * 16, p0.x, p0.y, p0.z, p0.w);
      named_bar_sync(10, 128);
      TS(12, lane == 0);
      if (wid == 1 && lane < 16) {
        const uint32_t ya = sbase + OG_SFIN + lane * 4;
        const float y = rbf(rbf((lds_f32(ya) + lds_f32(ya + 64)) + (lds_f32(ya + 128) + lds_f32(ya + 192))) * rs);
        *op = __float2bfloat16_rn(fx + rbf(((lane & 1) ? bfhi(gb2) : bflo(gb2)) * rbf(fh + y)));
      }
      if (tx == 96) bulk_wait_read<0>();
    }
    TL_END(4, tx == 0);
    PS(6, tx == 32);
    TS(13, tx == 32);
}

__device__ __forceinline__ void tail_consumer(Scratch* hm, uint32_t bx, uint32_t sbase, int tid, int w8, const bf16* __restrict__ w_gate, const bf16* __restrict__ w_up) {
    TAIL_SETUP
    const int warp = w8 & 3, lane = tid & 31, cwg = w8 >> 2, t2 = cwg * 128 + tid;
    const uint32_t dbase = (sbase & 0x3FFFFu) >> 4;
    const uint32_t a_base = dbase + ((cwg * 8192) >> 4) + (1u << 16);
    const uint32_t b_base = dbase + (16384 >> 4) + (512u << 16);
    TL_MARK2(25, threadIdx.x == 128);
    const uint64_t pol = policy_evict_first();
    const bf16* pw = ((lane & 16) ? w_up : w_gate) + (size_t)(w8 * 128 + (lane & 3) * 4) * T_F + (has_moe ? bx : 0) * 32 + ((lane >> 2) & 3) * 8;
    uint4 wv[32];
    float acc[64];
    {
      uint32_t stage = (OG_POS + 1) % OG_ST, phase = ((OG_POS + 1) / OG_ST) & 1, prev = 12;
      #pragma unroll
      for (int i = 0; i < 64; i++) acc[i] = 0.f;
      mbar_wait(bar_full + 248, 0);
      wgmma_fence();
      wgmma_m64n128k16_ss_tb<0 + 5 * 2048, 0 + 5 * 2048>(acc, a_base, b_base, 0);
      wgmma_m64n128k16_ss_tb<2 + 5 * 2048, 128 + 5 * 2048>(acc, a_base, b_base, 1);
      wgmma_m64n128k16_ss_tb<4 + 5 * 2048, 256 + 5 * 2048>(acc, a_base, b_base, 1);
      wgmma_m64n128k16_ss_tb<6 + 5 * 2048, 384 + 5 * 2048>(acc, a_base, b_base, 1);
      wgmma_commit();
      #pragma unroll
      for (int g = OG_PRE ? -1 : 0; g < OG_NG; g++) {
        #pragma unroll
        for (int j = 0; j < 4; j++) if (g >= 0) wv[4 * g + j] = ldg_stream_v4(pw + (size_t)(16 * g + j) * T_F, pol);
        #pragma unroll 1
        for (int kb = g < 0 ? 1 : OG_PRE + g * OG_LEN; kb < (g == OG_NG - 1 ? OG_NKB : OG_PRE + (g + 1) * OG_LEN); kb++) {
          mbar_wait(bar_full + 8 * stage, phase);
          const uint32_t a_lo = a_base + stage * (OG_STAGE >> 4), b_lo = b_base + stage * (OG_STAGE >> 4);
          wgmma_fence();
          wgmma_m64n128k16_ss_tb<0, 0>(acc, a_lo, b_lo, 1);
          wgmma_m64n128k16_ss_tb<2, 128>(acc, a_lo, b_lo, 1);
          wgmma_m64n128k16_ss_tb<4, 256>(acc, a_lo, b_lo, 1);
          wgmma_m64n128k16_ss_tb<6, 384>(acc, a_lo, b_lo, 1);
          wgmma_commit();
          wgmma_wait<1>();
          if (tid == 0) mbar_arrive(bar_empty + 8 * prev);
          prev = stage;
          if (++stage == OG_ST) { stage = 0; phase ^= 1; }
        }
      }
    }
    const uint32_t frag = (64 * cwg + 16 * warp + (lane & 15)) * 128 + (((lane >> 4) ^ (lane & 7)) << 4);
    const uint32_t tcol = sbase + OG_SCOL + (lane & 3) * 16, g = lane >> 2;
    float* sdst = reinterpret_cast<float*>(g_part1 + ((mt * 8 + w8) * 8 + nt) * 16 + g + (lane & 1) * 8);
    uint32_t xr[32];
    uint4 ga[4], cw[4];
    auto ld_quarter = [&](int q, uint32_t dep) {
      #pragma unroll
      for (int i = 2 * q; i < 2 * q + 2; i++) ldmatrix_x4(sbase + OG_XSLOT + (i >> 2) * 16384 + (frag ^ ((i & 3) * 32)) + dep, xr[4 * i], xr[4 * i + 1], xr[4 * i + 2], xr[4 * i + 3]);
      ga[q] = lds_u32x4(tcol + 512 + q * 64 + dep);
      cw[q] = lds_u32x4((g ? tcol + (lane & 8) * 32 + q * 64 : sbase + OG_SMISC + 32) + dep);
    };
    mbar_wait(bar_col, 0);
    mbar_wait(bar_full + 8 * ((OG_POS + OG_NKB) % OG_ST), ((OG_POS + OG_NKB) / OG_ST) & 1);
    ld_quarter(0, 0);
    wgmma_wait<0>();
    fence_regs(acc);
    if (tid == 0) mbar_arrive(bar_end);
    TL_MARK2(9, lane == 0);
    TS(0, lane == 0);
    PS(5, threadIdx.x == 256);
    {
      float dl[4] = {0.f, 0.f, 0.f, 0.f}, da[4] = {0.f, 0.f, 0.f, 0.f}, db[4] = {0.f, 0.f, 0.f, 0.f};
      #pragma unroll
      for (int q = 0; q < 4; q++) {
        uint32_t pk[8];
        #pragma unroll
        for (int i = 0; i < 8; i++) pk[i] = pack_bf16(acc[16 * q + 2 * i], acc[16 * q + 2 * i + 1]);
        if (q < 3) ld_quarter(q + 1, 0u);
        #pragma unroll
        for (int i = 2 * q; i < 2 * q + 2; i++) {
          #pragma unroll
          for (int k = 0; k < 4; k++) xr[4 * i + k] = badd2(xr[4 * i + k], bmul2((i & 1) ? (k < 2 ? ga[q].z : ga[q].w) : (k < 2 ? ga[q].x : ga[q].y), pk[4 * (i & 1) + k]));
          mma_bf16(dl, xr[4 * i], xr[4 * i + 1], xr[4 * i + 2], xr[4 * i + 3], (i & 1) ? cw[q].z : cw[q].x, (i & 1) ? cw[q].w : cw[q].y);
          mma_bf16(da, xr[4 * i], xr[4 * i + 1], xr[4 * i + 2], xr[4 * i + 3], xr[4 * i], xr[4 * i + 2]);
          mma_bf16(db, xr[4 * i], xr[4 * i + 1], xr[4 * i + 2], xr[4 * i + 3], xr[4 * i + 1], xr[4 * i + 3]);
        }
      }
      {
        const int dsrc = (lane & ~3) + (g >> 1);
        const float qa = __shfl_sync(0xffffffffu, (g & 1) ? da[1] : da[0], dsrc), qb = __shfl_sync(0xffffffffu, (g & 1) ? db[3] : db[2], dsrc);
        const float e0 = __shfl_xor_sync(0xffffffffu, (lane & 1) ? dl[0] : dl[2], 1), e1 = __shfl_xor_sync(0xffffffffu, dl[3], 1);
        const bool hi = lane & 1;
        if ((lane & 3) < 2) st_tagged4(sdst, hi ? e0 : dl[0], hi ? qb : qa, hi ? e1 + dl[2] : dl[1] + e0, 1.0f);
      }
    }
    TL_MARK2(10, lane == 0);
    TS(1, lane == 0);
    uint4 tc[4], ts[4], tg[4];
    #pragma unroll
    for (int i = 0; i < 8; i++) stmatrix_x4(sbase + OG_XSLOT + (i >> 2) * 16384 + (frag ^ ((i & 3) * 32)), xr[4 * i], xr[4 * i + 1], xr[4 * i + 2], xr[4 * i + 3]);
    #pragma unroll
    for (int i = 0; i < 8; i++) ldmatrix_x4(sbase + OG_XSLOT + (i >> 2) * 16384 + (frag ^ ((i & 3) * 32)), xr[4 * i], xr[4 * i + 1], xr[4 * i + 2], xr[4 * i + 3]);
    #pragma unroll
    for (int i = 0; i < 2; i++) { tc[i] = lds_u32x4(tcol + 768 + i * 64); ts[i] = lds_u32x4(tcol + 1024 + i * 64); tg[i] = lds_u32x4(tcol + 1280 + i * 64); }
    {
      const float* src = reinterpret_cast<const float*>(g_part1 + ((mt * 8 + w8) * 8 + (lane & 1) * 4) * 16 + (lane >> 1));
      float4 v, v1, v2, v3;
      #pragma unroll 1
      for (unsigned int spin = 0; spin < (1u << 22); spin++) {
        v = ld_tagged4(src); v1 = ld_tagged4(src + 64); v2 = ld_tagged4(src + 128); v3 = ld_tagged4(src + 192);
        if (tagged4(v) & tagged4(v1) & tagged4(v2) & tagged4(v3)) break;
        __nanosleep(100);
      }
      __syncwarp();
      TL_MARK2(26, lane == 0);
    TS(2, lane == 0);
      v.x = (v.x + v1.x) + (v2.x + v3.x); v.y = (v.y + v1.y) + (v2.y + v3.y); v.z = (v.z + v1.z) + (v2.z + v3.z);
      v.x += __shfl_xor_sync(0xffffffffu, v.x, 1); v.y += __shfl_xor_sync(0xffffffffu, v.y, 1); v.z += __shfl_xor_sync(0xffffffffu, v.z, 1);
      const float mean = v.x * (1.0f / T_D);
      const float var = fmaxf(fmaf(-mean, mean, v.y * (1.0f / T_D)), 0.f);
      const uint32_t mb2 = pack_bf16(mean, mean);
      const float inv = rcp_approx(rbf(sqrt_approx(rbf(rbf(var) + 1e-05f))));
      {
        const uint4 sc = lds_u32x4(sbase + OG_SMISC);
        const uint32_t key = rank_key(rbf(fmaf(fmaf(-bflo(mb2), __uint_as_float(sc.x) + __uint_as_float(sc.y), v.z), inv, __uint_as_float(sc.z) + __uint_as_float(sc.w))), m0 + 16 * w8 + (lane >> 1));
        mbar_wait(bar_end, 0);
        if (lane & 1) sts_u32(sbase + OG_SSTAT + 1024 + (16 * w8 + (lane >> 1)) * 4, key);
        else sts_u32x2(sbase + OG_SSTAT + (16 * w8 + (lane >> 1)) * 8, mb2, __float_as_uint(inv));
        __syncwarp();
        TS(3, lane == 0);
        if (lane == 0) mbar_arrive(bar_key);
      }
      const uint32_t ih = pack_bf16(inv, inv), il = pack_bf16(inv - bflo(ih), inv - bflo(ih));
      const uint32_t mba = __shfl_sync(0xffffffffu, mb2, 2 * (lane >> 2)), mbb = __shfl_sync(0xffffffffu, mb2, 2 * (lane >> 2) + 16);
      const uint32_t iha = __shfl_sync(0xffffffffu, ih, 2 * (lane >> 2)), ihb = __shfl_sync(0xffffffffu, ih, 2 * (lane >> 2) + 16);
      const uint32_t ila = __shfl_sync(0xffffffffu, il, 2 * (lane >> 2)), ilb = __shfl_sync(0xffffffffu, il, 2 * (lane >> 2) + 16);
      #pragma unroll
      for (int i = 2; i < 4; i++) { tc[i] = lds_u32x4(tcol + 768 + i * 64); ts[i] = lds_u32x4(tcol + 1024 + i * 64); tg[i] = lds_u32x4(tcol + 1280 + i * 64); }
      #pragma unroll
      for (int i = 0; i < 8; i++) {
        const uint4 &c = tc[i >> 1], &s = ts[i >> 1], &b = tg[i >> 1];
        const bool u = i & 1;
        stmatrix_x4(sbase + OG_OSLOT + (i >> 2) * 16384 + (frag ^ ((i & 3) * 32)),
                    out2(xr[4 * i], mba, iha, ila, u ? c.z : c.x, u ? s.z : s.x, u ? b.z : b.x), out2(xr[4 * i + 1], mbb, ihb, ilb, u ? c.z : c.x, u ? s.z : s.x, u ? b.z : b.x),
                    out2(xr[4 * i + 2], mba, iha, ila, u ? c.w : c.y, u ? s.w : s.y, u ? b.w : b.y), out2(xr[4 * i + 3], mbb, ihb, ilb, u ? c.w : c.y, u ? s.w : s.y, u ? b.w : b.y));
      }
      fence_proxy_async();
      __syncwarp();
      if (lane == 0) mbar_arrive(bar_out);
      TL_MARK2(24, lane == 0);
    TS(5, lane == 0);
    }
    uint4 wd[16];
    {
      mbar_wait(bar_sel, 0);
      TL_MARK2(12, lane == 0);
    TS(7, lane == 0);
      const float* src = reinterpret_cast<const float*>(g_cand + lds_u32(sbase + OG_SMISC + 72 + cwg * 4) * 256 + 128 + tid);
      float4 hf = ld_tagged4(src);
      if (has_moe) mbar_wait(bar_wd, 0);
      #pragma unroll
      for (int i = 0; i < 16; i++) wd[i] = lds_u32x4(sbase + OG_SWD + (((i >> 2) & 1) * 4 + (lane & 3)) * 8224 + (i & 3) * 2048 + w8 * 256 + (i >> 3) * 128 + (lane >> 2) * 16);
      #pragma unroll 1
      for (unsigned int spin = 0; spin < (1u << 20) && !tagged4(hf); spin++) hf = ld_tagged4(src);
      const uint4 hv = make_uint4(__float_as_uint(hf.x), __float_as_uint(hf.y), __float_as_uint(hf.z), __float_as_uint(hf.w));
      sts_u32x4(sbase + OG_SH2 + t2 * 16, hv.x, hv.y, hv.z, hv.w);
    }
    named_bar_sync(9, 256);
    if (t2 == 0) mbar_arrive(bar_h2);
    TL_MARK2(13, lane == 0);
    TS(8, lane == 0);
    if (has_moe) {
      const GemvSel sel = gemv_sel(lane);
      {
        float d[4][4];
        #pragma unroll
        for (int c = 0; c < 4; c++) { d[c][0] = 0.f; d[c][1] = 0.f; d[c][2] = 0.f; d[c][3] = 0.f; }
        #pragma unroll
        for (int st = 0; st < 8; st++) {
          const uint2 hb = lds_u32x2(sbase + OG_SH2 + ((lane >> 2) & 1) * 2048 + (w8 * 128 + st * 16 + (lane & 3) * 4) * 2);
          #pragma unroll
          for (int j = 0; j < 4; j++) mma_bf16(d[j], wv[4 * st + j].x, wv[4 * st + j].y, wv[4 * st + j].z, wv[4 * st + j].w, GEMV_B0(j, hb, sel), GEMV_B1(j, hb, sel));
        }
        #pragma unroll
        for (int e = 0; e < 4; e++) d[0][e] = (d[0][e] + d[1][e]) + (d[2][e] + d[3][e]);
        const float4 r = gemv_out(d[0], lane);
        sts_f32x4(sbase + OG_SRED + w8 * 512 + (((lane >> 4) * 2 + (lane & 1)) * 32 + ((lane >> 2) & 3) * 8 + (lane & 2) * 2) * 4, r.x, r.y, r.z, r.w);
      }
      named_bar_sync(9, 256);
      if (t2 < 64) {
        float gp[8], up[8];
        #pragma unroll
        for (int w = 0; w < 8; w++) { gp[w] = lds_f32(sbase + OG_SRED + w * 512 + t2 * 4); up[w] = lds_f32(sbase + OG_SRED + w * 512 + 256 + t2 * 4); }
        const float gs = ((gp[0] + gp[1]) + (gp[2] + gp[3])) + ((gp[4] + gp[5]) + (gp[6] + gp[7]));
        const float us = ((up[0] + up[1]) + (up[2] + up[3])) + ((up[4] + up[5]) + (up[6] + up[7]));
        asm volatile("st.shared.u16 [%0], %1;" :: "r"(sbase + OG_SGU + t2 * 2), "h"((uint16_t)pack_bf16(silu_bf(rbf(gs)) * rbf(us), 0.f)) : "memory");
      }
      named_bar_sync(9, 256);
      TS(9, lane == 0);
      float d[4][4];
      #pragma unroll
      for (int c = 0; c < 4; c++) { d[c][0] = 0.f; d[c][1] = 0.f; d[c][2] = 0.f; d[c][3] = 0.f; }
      #pragma unroll
      for (int st = 0; st < 2; st++) {
        const uint2 g = lds_u32x2(sbase + OG_SGU + ((lane >> 2) & 1) * 64 + st * 32 + (lane & 3) * 8);
        #pragma unroll
        for (int j = 0; j < 4; j++) {
          const uint32_t b0 = GEMV_B0(j, g, sel), b1 = GEMV_B1(j, g, sel);
          mma_bf16(d[j & 1], wd[4 * st + j].x, wd[4 * st + j].y, wd[4 * st + j].z, wd[4 * st + j].w, b0, b1);
          mma_bf16(d[2 + (j & 1)], wd[8 + 4 * st + j].x, wd[8 + 4 * st + j].y, wd[8 + 4 * st + j].z, wd[8 + 4 * st + j].w, b0, b1);
        }
      }
      #pragma unroll
      for (int e = 0; e < 4; e++) { d[0][e] += d[1][e]; d[2][e] += d[3][e]; }
      const float4 y0 = gemv_out(d[0], lane), y1 = gemv_out(d[2], lane);
      float* yp = g_ypart + (size_t)(bx * 2 + (lane & 1)) * T_D + w8 * 128 + (lane >> 2) * 8 + (lane & 2) * 2;
      st_tagged4(yp, y0.x, y0.y, y0.z, y0.w);
      st_tagged4(yp + 64, y1.x, y1.y, y1.z, y1.w);
      named_bar_sync(9, 256);
      if (t2 == 0) hint_arrive(CNT_Y);
    }
    TS(10, lane == 0);
    TL_CLK(4, 1, threadIdx.x == 128);
}

__device__ __forceinline__ void store_warp(Scratch* hm, uint32_t sbase, const CUtensorMap* tmO, int item0, int n_items) {
  if (elect_one()) {
    const uint32_t bars = sbase + AT_SBAR, b_q0 = bars + 80, b_ob = bars + 96, b_ordy = bars + 104, b_acq = bars + 256;
    mbar_wait(bars + 232, 0);
    const uint32_t bx = lds_u32(bars + 240);
    const unsigned int* cnt = &g_hcnt[32 * (1 + OG_MT(bx)) + 2];
    #pragma unroll 1
    for (int q = 0; q < 4 * n_items; q++) {
      const int item = item0 + (q >> 2) * 128, h = (q >> 1) & 1, w = q & 1;
      const bool last = (q >> 2) == n_items - 1;
      mbar_wait(b_ordy + 8 * (q & 3), q >> 2);
      if (q == 4 && item < 192) spin_until(&g_hcnt[32 * (1 + (item & 15)) + 1], (item & 15) < 12 ? 8u : 7u);
      store_o(tmO, (h ? (last ? sbase + AT_SQ + 32768 : sbase + 2 * 32768) : sbase + AT_SQ) + w * 8192, (item >> 4) * 2 + h, (item & 15) * 128 + w * 64);
      if (w) {
        PF(1 + (q >> 1));
        bulk_wait_read<0>();
        mbar_arrive(h ? b_ob : b_q0);
        bulk_wait<0>();
        fence_proxy_async_global();
        red_release_add(&g_hcnt[32 * (1 + (item & 15)) + 2 + (item >> 7)], 1u);
        if (bx < 128 && q == (n_items == 2 ? 5 : 3)) { spin_until(cnt, 16u); mbar_arrive(b_acq); }
      }
    }
    if (bx < 128) { spin_until(&g_hcnt[0], 8u); spin_until(cnt + 1, 16u); mbar_arrive(b_acq + 8); }
  }
}

#define TUNE_PARAM
__device__ __forceinline__ int h_first(int item, int c) { const int j = (item >> 4) + 3 * c; return j >= 7 ? j - 7 : j; }
__global__ void __launch_bounds__(384, 1)
fused_kernel(const bf16* __restrict__ x, const bf16* __restrict__ cvec, const bf16* __restrict__ w_mod, Scratch* hm, uint32_t zero, TUNE_PARAM
            const uint8_t* __restrict__ pf_wo, const bf16* __restrict__ kc, const bf16* __restrict__ vc, const bf16* __restrict__ w_r,
            const bf16* __restrict__ w_gate, const bf16* __restrict__ w_up, const bf16* __restrict__ w_down, bf16* __restrict__ out,
            const __grid_constant__ CUtensorMap tmM, const __grid_constant__ CUtensorMap tmW, const __grid_constant__ CUtensorMap tmK,
            const __grid_constant__ CUtensorMap tmV, const __grid_constant__ CUtensorMap tmO, const __grid_constant__ CUtensorMap tmOl, const __grid_constant__ CUtensorMap tmWo,
            const __grid_constant__ CUtensorMap tmX, const __grid_constant__ CUtensorMap tmOut)
{
  extern __shared__ __align__(1024) uint8_t smem_raw[];
  const uint32_t sbase = smem_u32(smem_raw);
  const uint32_t bars = sbase + AT_SBAR;
  const uint32_t b_full = bars, b_empty = bars + 40;
  const uint32_t b_q0 = bars + 80, b_q1 = bars + 88;
  const uint32_t b_ob = bars + 96;
  const uint32_t b_ordy = bars + 104;
  const uint32_t b_pin = bars + 136;
  const uint32_t b_a0 = bars + 144;
  const uint32_t b_x = bars + 160;
  const uint32_t b_w = bars + 152, b_go = bars + 224;
  const uint32_t b_bx = bars + 232, s_bx = bars + 240;
  const uint32_t b_hs = bars + 464;
  const uint32_t b_tab = bars + 272;
  const int wid = __shfl_sync(0xffffffffu, threadIdx.x >> 5, 0), wg = wid >> 2;
  const bool single = blockIdx.x >= AT_NFULL;
  const int item0 = __shfl_sync(0xffffffffu, blockIdx.x < 128 ? (int)blockIdx.x : (int)blockIdx.x + 124, 0), n_items = __shfl_sync(0xffffffffu, single ? 1 : 2, 0);
  const uint32_t t0 = clock_lo();
  TL_START(3);
  HS(0);
  if (threadIdx.x == 0) {
    if (sbase & 1023u) __trap();
    for (int i = 0; i < 5; i++) { mbar_init(b_full + 8 * i, 1); mbar_init(b_empty + 8 * i, 2); mbar_init(b_hs + 8 * i, i < 2 && !single ? 4 : 1); }
    sts_u32(bars + 504, 5u);
    mbar_init(b_q0, 1); mbar_init(b_q1, 8); mbar_init(b_ob, 1);
    for (int i = 0; i < 4; i++) mbar_init(b_ordy + 8 * i, 4);
    mbar_init(b_pin, 1); mbar_init(b_a0, 8); mbar_init(b_x, 1); mbar_init(b_w, 1); mbar_init(b_go, 1); mbar_init(b_bx, 1);
    for (int i = 0; i < 8; i++) mbar_init(b_tab + 8 * i, i < 2 ? 1 : 2);
    mbar_init(bars + 168, 1); mbar_init(bars + 176, 1); mbar_init(bars + 184, 8); mbar_init(bars + 192, 2);
    mbar_init(bars + 200, 8); mbar_init(bars + 208, 1); mbar_init(bars + 216, 1); mbar_init(bars + 248, 1); mbar_init(bars + 256, 1); mbar_init(bars + 264, 1);
    sts_u32x4(sbase + OG_SMISC + 32, 0x3F803F80u, 0x3F803F80u, 0x3F803F80u, 0x3F803F80u);
    fence_mbar_init();
    if (blockIdx.x < 128) {
      HS(1);
      wait_clock(t0, XDLY);
      mbar_expect_tx(b_x, 32768);
      bulk_load_hint(sbase + 3 * 32768, x + (size_t)blockIdx.x * 16 * T_D, 32768, b_x, pol_normal());
    }
    mbar_arrive(b_tab); mbar_arrive(b_tab + 8);
  }

  if (wg == 0) {
    reg_dealloc<AT_PREG>();
    if (wid == 0) { __syncwarp(); named_bar_arrive(6, 128); named_bar_arrive(11, 160); named_bar_arrive(12, 160); }
    if (wid >= 2) {
      named_bar_sync(6, 128);
      wait_clock(t0, GDLY2);
      gather_table(hm, sbase + 4 * 32768, b_tab, wid & 1, threadIdx.x & 31);
      if (threadIdx.x == 64) PF(0);
      if (threadIdx.x == 96 && !single) { sleep_until(t0, 40000); spin_until(&g_hcnt[32 * (1 + (item0 & 15))], 7u); mbar_arrive(b_w); }
    } else if (wid == 1) {
      named_bar_sync(6, 128);
      if (item0 < 112) {
        const int lane = threadIdx.x & 31;
        #pragma unroll 1
        for (int j0 = h_first(item0, 0), j1 = h_first(item0, 1); j0 < 16 || j1 < 16;) {
          const int c = j1 < j0, j = c ? j1 : j0;
          bf16* hg = hm->o + (size_t)((item0 & 15) * 128 + c * 64 + (lane >> 3)) * O_LD + O_H + (lane & 7) * 8 + j * 64;
          uint32_t src = sbase + AT_SQ - 16384 + c * 8192 + (lane >> 3) * 128 + (((lane ^ (lane >> 3)) & 7) << 4);
          mbar_wait(b_hs + 8 * c, j >= 7 && j < 14);
          #pragma unroll 1
          for (int i = 0; i < 4; i++, hg += 16 * O_LD, src += 2048) {
            uint4 v[4];
            #pragma unroll
            for (int k = 0; k < 4; k++) v[k] = lds_u32x4((src ^ ((k & 1) * 64)) + k * 512);
            #pragma unroll
            for (int k = 0; k < 4; k++) *reinterpret_cast<uint4*>(hg + k * 4 * O_LD) = v[k];
          }
          __syncwarp();
          if (lane == 0) mbar_arrive(b_hs + 16 + 8 * c);
          if (c) j1 += 7; else j0 += 7;
        }
        if (lane == 0) mbar_arrive(b_go);
        if (lane == 0) red_release_add(&g_hcnt[32 * (1 + (item0 & 15))], 1u);
      }
      sleep_until(t0, 26000);
      const uint32_t v = assign_tile(hm, t0, threadIdx.x & 31);
      if (threadIdx.x == 32) { sts_u32(s_bx, v); mbar_arrive(b_bx); }
      __syncwarp();
      store_warp(hm, sbase, &tmO, item0, n_items);
      __syncwarp();
    } else {
     if (elect_one()) {
      const uint64_t pol = policy_evict_first();
      prefetch_tmap(&tmW); prefetch_tmap(&tmX); prefetch_tmap(&tmWo); prefetch_tmap(&tmOl);
      if (single) {
        prefetch_tmap(&tmM);
        #pragma unroll 1
        for (uint32_t i = 0, buf = 0; i < 44; i++) {
          wait_clock(t0, i < 12 ? (blockIdx.x < 128 ? WDLY + W_OFF : WDLY) + (i & 3) * W_GAP + (i >> 2) * W_RND : W_LATE);
          #pragma unroll 1
          for (uint32_t spin = 0, n = 0; spin < (1u << 24) && n <= i; spin++) asm volatile("ld.volatile.shared.u32 %0, [%1];" : "=r"(n) : "r"(bars + 504) : "memory");
          mbar_expect_tx(bars + 464 + buf * 8, 32768);
          tma_load_2d_hint(sbase + (buf + (buf > 2 ? 2 : 0)) * 32768, &tmM, mod_col0(blockIdx.x - AT_NFULL, (int)(i >> 2) - 3), (i & 3) * 256, bars + 464 + buf * 8, pol);
          if (++buf == 5) buf = 0;
        }
        mbar_wait(b_go, 0);
      }
      {
        #pragma unroll 1
        for (int j = 0; j < T_D / 64; j++) {
          const uint32_t fb = b_full + 8 * (j & 3);
          mbar_wait(b_empty + 8 * (j & 3), ((j >> 2) & 1) ^ 1);
          mbar_expect_tx(fb, j == 0 ? 65536 : j == T_D / 64 - 1 ? 32768 : 49152);
          if (j < 2) wait_clock(t0, j ? ST1_T : PRE_T);
          if (j == 3) mbar_wait(b_a0, 0);
          if (j < 4) HS(2 + j);
          tma_load_3d_hint(sbase + (j & 3) * 32768, &tmW, j * 64, (item0 >> 4) * 4, fb, pol);
          if (j == 0) { wait_clock(t0, A_T); tma_load_2d_hint(sbase + AT_SQ, &tmX, 0, (item0 & 15) * 128, fb, pol); }
          if (j < T_D / 64 - 1) tma_load_2d_hint(sbase + AT_SQ + ((j + 1) & 3) * 16384, &tmX, (j + 1) * 64, (item0 & 15) * 128, fb, pol);
        }
      }
      uint32_t slot = 0, ph = 1;
      #pragma unroll 1
      for (int it = 0; it < n_items; it++) {
        const int item = item0 + it * 128, hp = item >> 4, qt = item & 15;
        const bool first = it == 0;
        if (!first) {
          #pragma unroll 1
          for (int j = 0; j < T_D / 64; j++) {
            const uint32_t sl = ring_slot(qp_pos(j, 1)), fb = b_full + 8 * sl;
            mbar_wait(b_empty + 8 * sl, ring_par(qp_pos(j, 1)) ^ ((j >> 2) & 1) ^ 1);
            mbar_expect_tx(fb, 49152);
            tma_load_3d_hint(sbase + sl * 32768, &tmW, j * 64, hp * 4, fb, pol);
            if (j == 0) { mbar_wait(b_q0, 0); mbar_wait(b_q1, 0); mbar_wait(b_w, 0); fence_proxy_async_global(); }
            tma_load_2d_hint(sbase + AT_SQ + (j & 3) * 16384, &tmOl, O_H + j * 64, qt * 128, fb, pol);
          }
        }
        #pragma unroll 1
        for (int j = 0; j < 4 * AT_NBLK; j++) {
          const bool isv = (j > 0 && !(j & 1)) || j == 4 * AT_NBLK - 1;
          const int row = hp * 2 * T_SEQ + (isv ? (j - 1) >> 1 : (j + 1) >> 1) * 128;
          const uint32_t fb = b_full + 8 * slot;
          mbar_wait(b_empty + 8 * slot, ph);
          if (!first && j == 3) mbar_wait(b_ob, 0);
          if (!first && j == 4) hint_arrive(&g_hcnt[32 * (1 + qt) + 1]);
          if (first && j == 4 && item0 < 112) mbar_wait(b_go, 0);
          mbar_expect_tx(fb, 32768);
          tma_load_2d_hint(sbase + slot * 32768, isv ? &tmV : &tmK, 0, row, fb, pol);
          tma_load_2d_hint(sbase + slot * 32768 + 16384, isv ? &tmV : &tmK, 64, row, fb, pol);
          if (it == 1 && isv && j >= 2 * WO_LATE && j < 2 * WO_LATE + 32 && blockIdx.x < 64)
            l2_prefetch_bulk(pf_wo + (size_t)blockIdx.x * 131072 + ((j >> 1) - WO_LATE) * 8192, 8192);
          if (++slot == 5) { slot = 0; ph ^= 1; }
        }
      }
      mbar_wait(b_bx, 0);
      const uint32_t bx = lds_u32(s_bx);
      if (bx < 128) {
        if (single) mbar_wait(b_go, 1);
        tail_producer(hm, bx, sbase, 0, n_items - 1, pol, &tmOl, &tmWo, &tmX, w_down);
      }
     }
    }
    __syncwarp();
    PSV(0, threadIdx.x == 96, t0);
    mbar_wait(b_bx, 0);
    const uint32_t bx = __shfl_sync(0xffffffffu, lds_u32(s_bx), 0);
    if (bx < 128) tail_exchange(hm, bx, sbase, wid, __shfl_sync(0xffffffffu, threadIdx.x, threadIdx.x), &tmOut, out);
  } else {
    if (wg == 1 && blockIdx.x < 128) head_first(hm, sbase + 4 * 32768 + 4096, threadIdx.x - 128, cvec, w_mod);
    named_bar_sync(10 + wg, 160);
    if (wg == 2 && blockIdx.x < 128) head_stats(hm, sbase + 3 * 32768, b_x, threadIdx.x - 256);
    if (single) {
      mod_rest(hm, t0, sbase, bars + 464, threadIdx.x - 128, (int)blockIdx.x - AT_NFULL, cvec, w_r);
      named_bar_sync(5, 256);
      if (threadIdx.x == 128) mbar_arrive(b_go);
    }
    if (wg == 1) { wait_clock(t0, GDLY); head_gather(hm, sbase + 4 * 32768, threadIdx.x - 128); }
    reg_alloc<AT_CREG>();
    const int cwg = wg - 1;
    const int tid = __shfl_sync(0xffffffffu, threadIdx.x, threadIdx.x) & 127;
    const int warp = wid & 3, lane = tid & 31;
    const uint32_t dbase = (sbase & 0x3FFFFu) >> 4;
    const uint32_t k_base = dbase + (1u << 16);
    const uint32_t v_base = dbase + (1024u << 16);
    const uint32_t w_base = dbase + (512u << 16);
    const uint32_t frag = cwg * 8192 + (16 * warp + (lane & 7) + 8 * ((lane >> 3) & 1)) * 128;
    if (cwg == 1) named_bar_arrive(1, 256);
    bool raw = false;
    constexpr int nkb = T_D / 64;
    float acc[128], c0, c1;
    {
      FS(0, 0);
      uint32_t af[2][16], rw[16];
      uint4 tb[4];
      uint32_t xa[4];
      #pragma unroll
      for (int st = 0; st < 4; st++) xa[st] = __shfl_sync(0xffffffffu, (sbase + AT_SQ + frag + (((lane >> 4) ^ (lane & 7)) << 4)) ^ (st * 32), lane);
      const uint32_t xt = __shfl_sync(0xffffffffu, sbase + 4 * 32768 + (lane & 3) * 16, lane);
      auto qp_fetch = [&](int j) {
        #pragma unroll
        for (int st = 0; st < 4; st++) {
          ldmatrix_x4(xa[st] + (j & 3) * 16384, rw[4 * st], rw[4 * st + 1], rw[4 * st + 2], rw[4 * st + 3]);
          tb[st] = lds_u32x4(xt + (j & 15) * 256 + st * 64);
        }
      };
      zero_regs(acc);
      #pragma unroll
      for (int i = 0; i < 16; i++) af[1][i] = 0u;
      const float2* stp = hm->stat + (item0 & 15) * 256 + (cwg * 4 + warp) * 32 + (lane & 3) * 8 + (lane >> 2);
      HS(4);
      wait_clock(t0, SDLY);
      float2 sv = ld_tagged2(stp);
      named_bar_sync(5, 256);
      mbar_wait(b_full, 0);
      HS(5);
      qp_fetch(0);
      #pragma unroll 1
      for (unsigned int spin = 0; spin < (1u << 22); spin++) {
        if (__all_sync(0xffffffffu, (__float_as_uint(sv.x) != 0u) & (__float_as_uint(sv.y) != 0u))) break;
        sv = ld_tagged2(stp);
      }
      HS(6);
      if (lane == 0) mbar_arrive(b_a0 + (rw[3] & rw[7] & rw[11] & rw[15] & zero));
      const uint32_t st = ln_stat(sv.x + __shfl_xor_sync(0xffffffffu, sv.x, 1), sv.y + __shfl_xor_sync(0xffffffffu, sv.y, 1)), so = __shfl_xor_sync(0xffffffffu, st, 2);
      const uint32_t sta = (lane & 2) ? so : st, stb = (lane & 2) ? st : so;
      const uint32_t mean_a = __byte_perm(sta, 0u, 0x1010), mean_b = __byte_perm(stb, 0u, 0x1010), sd_a = __byte_perm(sta, 0u, 0x3232), sd_b = __byte_perm(stb, 0u, 0x3232);
      c0 = AT_C * rcp_approx(bfhi(sta)); c1 = AT_C * rcp_approx(bfhi(stb));
      sts_u32(sbase + OG_SMISC + 256 + (cwg * 4 + warp) * 64 + (lane & 28) + (lane & 2) * 16, __float_as_uint((lane & 2) ? c1 : c0));
      int jst = item0 < 112 ? h_first(item0, cwg) : 99;
      #pragma unroll 1
      for (int j2 = 0; j2 < nkb; j2 += 2) {
        #pragma unroll
        for (int u = 0; u < 2; u++) {
          const int j = j2 + u;
          const uint32_t bt = b_tab + 4 * ((j + 1) & 15);
          if (u == 1) {
            #pragma unroll 1
            for (uint32_t z = 0; z < zero; z++)
              #pragma unroll
              for (int i = 0; i < 16; i += 4) sts_u32x4(xt + i * 4, af[1][i], af[1][i + 1], af[1][i + 2], af[1][i + 3]);
          }
          bool ok = mbar_test(b_full + 8 * (j & 3), (j >> 2) & 1);
          if (u == 1) ok &= mbar_test(bt, 0);
          #pragma unroll
          for (int st = 0; st < 4; st++) {
            af[u][4 * st + 0] = bfma2(bsub2(rw[4 * st + 0], mean_a), tb[st].x, bmul2(tb[st].z, sd_a));
            af[u][4 * st + 1] = bfma2(bsub2(rw[4 * st + 1], mean_b), tb[st].x, bmul2(tb[st].z, sd_b));
            af[u][4 * st + 2] = bfma2(bsub2(rw[4 * st + 2], mean_a), tb[st].y, bmul2(tb[st].w, sd_a));
            af[u][4 * st + 3] = bfma2(bsub2(rw[4 * st + 3], mean_b), tb[st].y, bmul2(tb[st].w, sd_b));
          }
          if (!ok || j == jst) {
            if (!ok) { mbar_wait(b_full + 8 * (j & 3), (j >> 2) & 1); if (u == 1) mbar_wait(bt, 0); }
            if (j == jst) {
              if (j >= 7) mbar_wait(b_hs + 16 + 8 * cwg, j >= 14);
              #pragma unroll
              for (int st = 0; st < 4; st++) stmatrix_x4(xa[st] - 16384, af[u][4 * st], af[u][4 * st + 1], af[u][4 * st + 2], af[u][4 * st + 3]);
              __syncwarp();
              if (lane == 0) mbar_arrive(b_hs + 8 * cwg);
              jst += 7;
            }
          }
          qp_fetch(j + 1);
          if (cwg == 1 && j == nkb - 1) named_bar_sync(7, 256);
          const uint32_t b_lo = w_base + (j & 3) * 2048;
          wgmma_fence();
          wgmma_m64n256k16_rs_tb<0>(acc, af[u][0], af[u][1], af[u][2], af[u][3], b_lo, 1);
          wgmma_m64n256k16_rs_tb<128>(acc, af[u][4], af[u][5], af[u][6], af[u][7], b_lo, 1);
          wgmma_m64n256k16_rs_tb<256>(acc, af[u][8], af[u][9], af[u][10], af[u][11], b_lo, 1);
          wgmma_m64n256k16_rs_tb<384>(acc, af[u][12], af[u][13], af[u][14], af[u][15], b_lo, 1);
          wgmma_commit();
          if (cwg == 0 && j == nkb - 1) named_bar_arrive(7, 256);
          if (j == 0) HS(7);
          wgmma_wait<1>();
          if (tid == 0) mbar_arrive(j > 0 ? b_empty + 8 * ((j - 1) & 3) : b_pin);
        }
      }
      wgmma_wait<0>();
      fence_regs(acc);
    }
    uint32_t bx;
    #pragma unroll 1
    for (int it = 0;;) {
      const int item = item0 + it * 128, hp = item >> 4;
      const bool more = it + 1 < n_items;
      const int ta = __shfl_sync(0xffffffffu, 4 * it, 0);
      FS(2 * it, 1);
      PS(1 + 2 * it, threadIdx.x == 256);
      if (tid == 0) mbar_arrive(b_empty + 24);
      float o[64], s[64];
      uint32_t p[32], q[32];
      #pragma unroll
      for (int i = 0; i < 32; i++) q[i] = pack_bf16(acc[2 * i] * ((i & 1) ? c1 : c0), acc[2 * i + 1] * ((i & 1) ? c1 : c0));
      zero_regs(s);
      const uint32_t sq = sbase + AT_SQ + cwg * 8192;
      const bool last_wg1 = cwg == 1 && !more;
      float mc0, mc1, al0 = 1.0f, al1 = 1.0f, l0 = 0.f, l1 = 0.f;
      bool redo0 = false;
      FS(2 * it, 2);
      mbar_wait(b_full + 8 * ring_slot(ta), ring_par(ta));
      named_bar_sync(1 + cwg, 256);
      FS(2 * it, 3);
      issue_qk(s, q, k_base + ring_slot(ta) * 2048);
      named_bar_arrive(1 + (cwg ^ 1), 256);
      const uint32_t rdy = (uint32_t)mbar_test(b_full + 8 * ring_slot(ta + 1), ring_par(ta + 1));
      bool ready = rdy & mbar_test(b_full + 8 * ring_slot(ta + 2), ring_par(ta + 2));
      stage_o(*reinterpret_cast<const float (*)[64]>(&acc[64]), c0, c1, sbase + AT_SQ + 32768 + frag, lane);
      wgmma_wait<0>();
      fence_regs(s);
      if (tid == 0) mbar_arrive(b_empty + 8 * ring_slot(ta));
      mc0 = 0.f; mc1 = 0.f;
      if (it == 0) raw = __all_sync(0xffffffffu, fmaxf(fmaxf(fmaxf(fabsf(s[0]), fabsf(s[10])), fmaxf(fabsf(s[17]), fabsf(s[27]))),
                                                       fmaxf(fmaxf(fabsf(s[36]), fabsf(s[46])), fmaxf(fabsf(s[53]), fabsf(s[63])))) <= 16.0f);
      if (!raw) {
        raw = softmax_mode(s, mc0, mc1);
        if (__builtin_expect(!raw, 0)) softmax_sub(s, mc0, mc1);
      }
      softmax_exp<0, 64>(s);
      stage_qregs(q, sbase + AT_SQ + frag, lane);
      pack_p(p, s);
      zero_regs(o);
      FS(2 * it, 4);
      uint32_t ks = ring_slot(ta + 1), vs = ring_slot(ta + 2), kp = ring_par(ta + 1), vp = ring_par(ta + 2);
      if (!ready) { mbar_wait(b_full + 8 * ks, kp); mbar_wait(b_full + 8 * vs, vp); }
      #pragma unroll 1
      for (int n = 1; n < 2 * AT_NBLK; n++) {
        named_bar_sync(1 + cwg, 256);
        issue_qk(s, q, k_base + ks * 2048);
        if (n == AT_NBLK + 1) {
          if (!redo0) stage_o(o, 1.0f, 1.0f, sbase + AT_SQ + frag, lane);
        }
        issue_pv(o, p, v_base + vs * 2048, (n & 15) != 1);
        if (!(last_wg1 && n == 2 * AT_NBLK - 1)) named_bar_arrive(1 + (cwg ^ 1), 256);
        wgmma_wait<1>();
        fence_regs(s);
        if (tid == 0) mbar_arrive(b_empty + 8 * ks);
        if (__builtin_expect(!raw || (n + 1) >> 1 == AT_NBLK / 2, 0)) {
          if (n == AT_NBLK - 1) {
            #pragma unroll
            for (int J = 0; J < 16; J += 2)
              ldmatrix_x4(sbase + AT_SQ + 32768 + frag + (J >> 3) * 16384 + ((((J & 7) + (lane >> 4)) ^ (lane & 7)) << 4), q[2 * J], q[2 * J + 1], q[2 * J + 2], q[2 * J + 3]);
          }
          if (n == AT_NBLK && lane == 0) mbar_arrive(b_q1);
          if (!raw) {
            const float m0 = mc0, m1 = mc1;
            const bool ok = softmax_mode(s, mc0, mc1);
            if (n == AT_NBLK) raw = ok;
            else {
              mc0 = mc0 - AT_HEAD > m0 ? mc0 : m0; mc1 = mc1 - AT_HEAD > m1 ? mc1 : m1;
              al0 = ex2_approx(m0 - mc0); al1 = ex2_approx(m1 - mc1);
            }
            if (!raw) softmax_sub(s, mc0, mc1);
          }
        }
        softmax_exp<0, AT_SPLIT>(s);
        add_rowsum(p, l0, l1);
        if (tid == 0) {
          uint32_t dep = zero & __float_as_uint(l0) & __float_as_uint(l1);
          #pragma unroll
          for (int i = AT_SPLIT - AT_PIN - PINB; i < AT_SPLIT - PINB; i += 2) dep &= __float_as_uint(s[i]) & __float_as_uint(s[i + 1]);
          mbar_arrive(b_pin + dep);
        }
        wgmma_wait<0>();
        fence_regs(o);
        if (tid == 0) mbar_arrive(b_empty + 8 * vs);
        ks += 2; if (ks >= 5) { ks -= 5; kp ^= 1; }
        vs += 2; if (vs >= 5) { vs -= 5; vp ^= 1; }
        ready = mbar_test(b_full + 8 * ks, kp) & mbar_test(b_full + 8 * vs, vp);
        if (__builtin_expect(n == AT_NBLK, 0)) {
          redo0 = finish_l(l0, l1);
          softmax_exp<AT_SPLIT, 64>(s);
          rescale_o(o, l0, l1);
          pack_p(p, s);
          l0 = 0.f; l1 = 0.f;
        } else {
          softmax_exp<AT_SPLIT, 64>(s);
          pack_p(p, s);
        }
        if (__builtin_expect(!raw || !ready || n == AT_NBLK + 1, 0)) {
        if (n == AT_NBLK + 1 && !redo0) { fence_proxy_async(); __syncwarp(); if (lane == 0) mbar_arrive(b_ordy + 8 * cwg); }
        if (!raw && __any_sync(0xffffffffu, al0 != 1.0f || al1 != 1.0f)) {
          rescale_o(o, al0, al1);
          l0 *= al0; l1 *= al1;
          al0 = 1.0f; al1 = 1.0f;
        }
        if (!ready && n < 2 * AT_NBLK - 1) {
          mbar_wait(b_full + 8 * ks, kp);
          mbar_wait(b_full + 8 * vs, vp);
        }
        }
      }
      FS(2 * it + 1, 5);
      const uint32_t vl = ring_slot(ta + 63);
      vs = ring_slot(ta + 62);
      const uint32_t ob = more ? sbase + vs * 32768 : sbase + AT_SQ + 32768;
      mbar_wait(b_full + 8 * vl, ring_par(ta + 63));
      issue_pv(o, p, v_base + vl * 2048, 1);
      add_rowsum(p, l0, l1);
      #pragma unroll 1
      for (uint32_t z = 0; z < zero; z++) mbar_arrive(b_pin + __float_as_uint(l0) + __float_as_uint(l1));
      const bool overflow = finish_l(l0, l1);
      mbar_wait(b_bx, 0);
      bx = __shfl_sync(0xffffffffu, lds_u32(s_bx), 0);
      mbar_wait(b_empty + 8 * vs, ring_par(ta + 62));
      wgmma_wait<0>();
      fence_regs(o);
      if (tid == 0) mbar_arrive(b_empty + 8 * vl);
      FS(2 * it + 1, 6);
      if (overflow) stage_qregs(q, ob + frag, lane);
      else stage_o(o, l0, l1, ob + frag, lane);
      if (__builtin_expect(overflow || redo0, 0)) {
        __syncwarp();
        #pragma unroll 1
        for (int h = redo0 ? 0 : 1; h < (overflow ? 2 : 1); h++)
          attn_rows_exact(h ? ob + cwg * 8192 : sq, warp, lane, kc + (size_t)(hp * 2 + h) * T_SEQ * T_DH, vc + (size_t)(hp * 2 + h) * T_SEQ * T_DH);
        fence_proxy_async();
        __syncwarp();
        if (lane == 0 && redo0) mbar_arrive(b_ordy + 8 * cwg);
        raw = false;
      }
      fence_proxy_async();
      __syncwarp();
      if (lane == 0) mbar_arrive(b_ordy + 16 + 8 * cwg);
      named_bar_sync(3 + cwg, 128);
      FS(2 * it + 1, 7);
      PS(2 + 2 * it, threadIdx.x == 256);
      if (++it == n_items) break;
      FS(2 * it, 0);
      zero_regs(acc);
      auto ss_step = [&](int j, int accumulate) {
        const uint32_t slot = ring_slot(qp_pos(j, 1));
        mbar_wait(b_full + 8 * slot, ring_par(qp_pos(j, 1)) ^ ((j >> 2) & 1));
        if (cwg == 1 && j == nkb - QP_STAG) named_bar_sync(7, 256);
        const uint32_t a_lo = dbase + ((AT_SQ + cwg * 8192) >> 4) + (1u << 16) + (j & 3) * 1024, b_lo = w_base + slot * 2048;
        wgmma_fence();
        wgmma_m64n256k16_ss_tb<0, 0>(acc, a_lo, b_lo, accumulate);
        wgmma_m64n256k16_ss_tb<2, 128>(acc, a_lo, b_lo, 1);
        wgmma_m64n256k16_ss_tb<4, 256>(acc, a_lo, b_lo, 1);
        wgmma_m64n256k16_ss_tb<6, 384>(acc, a_lo, b_lo, 1);
        wgmma_commit();
        return b_empty + 8 * slot;
      };
      uint32_t prev = ss_step(0, 0);
      c0 = lds_f32(sbase + OG_SMISC + 256 + (cwg * 4 + warp) * 64 + (lane & 28)); c1 = lds_f32(sbase + OG_SMISC + 288 + (cwg * 4 + warp) * 64 + (lane & 28));
      #pragma unroll 1
      for (int j = 1; j < nkb; j++) {
        if (cwg == 1 && j == nkb - QP_STAG) {
          wgmma_wait<0>();
          if (tid == 0) mbar_arrive(prev);
          prev = b_pin;
        }
        const uint32_t cur = ss_step(j, 1);
        if (cwg == 0 && j == nkb - 1) named_bar_arrive(7, 256);
        wgmma_wait<1>();
        if (tid == 0) mbar_arrive(prev);
        prev = cur;
      }
      wgmma_wait<0>();
      fence_regs(acc);
    }
    if (n_items == 1) {
      named_bar_sync(5, 256);
      if (threadIdx.x == 128) {
        #pragma unroll 1
        for (int i = 4; i < 8; i++) {
          mbar_arrive(b_full + 8 * ring_slot(i));
          mbar_arrive(b_empty + 8 * ring_slot(i)); mbar_arrive(b_empty + 8 * ring_slot(i));
        }
        mbar_arrive(b_go);
      }
      named_bar_sync(5, 256);
    }
    TL_CLK(3, 1, threadIdx.x == 128);
    TL_CTA(1, threadIdx.x == 256);
    TL_END(3, tid == 0);
    __syncwarp();
    QDUMP();
    TL_MARK2(19, tid == 0 && !single);
    if (bx < 128) {
      tail_consumer(hm, bx, sbase, tid, wid - 4, w_gate, w_up);
    }
  }
}

typedef CUresult (*PFN_encodeTiled)(CUtensorMap*, CUtensorMapDataType, cuuint32_t, void*, const cuuint64_t*, const cuuint64_t*,
                                    const cuuint32_t*, const cuuint32_t*, CUtensorMapInterleave, CUtensorMapSwizzle,
                                    CUtensorMapL2promotion, CUtensorMapFloatOOBfill);

CUtensorMap make_map_2d(PFN_encodeTiled enc, const void* ptr, uint64_t inner, uint64_t outer, uint64_t stride_bytes, uint32_t box_inner, uint32_t box_outer) {
  CUtensorMap m;
  cuuint64_t gd[2] = {inner, outer}; cuuint64_t gs[1] = {stride_bytes};
  cuuint32_t bx[2] = {box_inner, box_outer}; cuuint32_t es[2] = {1, 1};
  enc(&m, CU_TENSOR_MAP_DATA_TYPE_BFLOAT16, 2, const_cast<void*>(ptr), gd, gs, bx, es, CU_TENSOR_MAP_INTERLEAVE_NONE,
      CU_TENSOR_MAP_SWIZZLE_128B, CU_TENSOR_MAP_L2_PROMOTION_L2_128B, CU_TENSOR_MAP_FLOAT_OOB_FILL_NONE);
  return m;
}

CUtensorMap make_map_3d(PFN_encodeTiled enc, const void* ptr, uint64_t cols, uint64_t rows, uint32_t box_rows, uint32_t chunks) {
  CUtensorMap m;
  cuuint64_t gd[3] = {64, rows, cols / 64}; cuuint64_t gs[2] = {cols * 2, 128};
  cuuint32_t bx[3] = {64, box_rows, chunks}; cuuint32_t es[3] = {1, 1, 1};
  enc(&m, CU_TENSOR_MAP_DATA_TYPE_BFLOAT16, 3, const_cast<void*>(ptr), gd, gs, bx, es, CU_TENSOR_MAP_INTERLEAVE_NONE,
      CU_TENSOR_MAP_SWIZZLE_128B, CU_TENSOR_MAP_L2_PROMOTION_L2_128B, CU_TENSOR_MAP_FLOAT_OOB_FILL_NONE);
  return m;
}

}

extern "C" void kernel_launch(void* const* d_in, const int* in_sizes, int n_in, void* d_out, int out_size) {
  const bf16* x      = (const bf16*)d_in[0];
  const bf16* kc     = (const bf16*)d_in[1];
  const bf16* vc     = (const bf16*)d_in[2];
  const bf16* wq     = (const bf16*)d_in[3];
  const bf16* wo     = (const bf16*)d_in[4];
  const bf16* w_r    = (const bf16*)d_in[6];
  const bf16* w_gate = (const bf16*)d_in[7];
  const bf16* w_up   = (const bf16*)d_in[8];
  const bf16* w_down = (const bf16*)d_in[9];
  const bf16* cvec   = (const bf16*)d_in[10];
  const bf16* w_mod  = (const bf16*)d_in[11];
  bf16* out = (bf16*)d_out;

  static PFN_encodeTiled enc = nullptr;
  static void* p_hm = nullptr;
  if (!enc) {
    void* fn = nullptr; cudaDriverEntryPointQueryResult qres;
    cudaGetDriverEntryPoint("cuTensorMapEncodeTiled", &fn, cudaEnableDefault, &qres);
    enc = (PFN_encodeTiled)fn;
    cudaGetSymbolAddress(&p_hm, g_scr);
    cudaFuncSetAttribute(fused_kernel, cudaFuncAttributeMaxDynamicSharedMemorySize, (int)AT_SMEM);
  }
  const CUtensorMap tm_m   = make_map_2d(enc, w_mod, 6 * T_D, T_D, 6 * T_D * 2, 64, 256);
  const CUtensorMap tm_wq  = make_map_3d(enc, wq, T_DQKV, T_D, 64, 4);
  const CUtensorMap tm_k   = make_map_2d(enc, kc, T_DH, (uint64_t)T_NH * T_SEQ, T_DH * 2, 64, 128);
  const CUtensorMap tm_v   = make_map_2d(enc, vc, T_DH, (uint64_t)T_NH * T_SEQ, T_DH * 2, 64, 128);
  const CUtensorMap tm_ost = make_map_2d(enc, ((Scratch*)p_hm)->o, O_LD, T_SEQ, O_LD * 2, 64, 64);
  const CUtensorMap tm_old = make_map_2d(enc, ((Scratch*)p_hm)->o, O_LD, T_SEQ, O_LD * 2, 64, 128);
  const CUtensorMap tm_wo  = make_map_2d(enc, wo, T_D, T_DQKV, T_D * 2, 64, 64);
  const CUtensorMap tm_x   = make_map_2d(enc, x, T_D, T_SEQ, T_D * 2, 64, 128);
  const CUtensorMap tm_out = make_map_2d(enc, out, T_D, T_SEQ, T_D * 2, 64, 128);

#define TUNE_ARG
  fused_kernel<<<132, 384, AT_SMEM, cudaStreamPerThread>>>(x, cvec, w_mod, (Scratch*)p_hm, 0u, TUNE_ARG (const uint8_t*)wo, kc, vc, w_r, w_gate, w_up, w_down, out,
             tm_m, tm_wq, tm_k, tm_v, tm_ost, tm_old, tm_wo, tm_x, tm_out);
}
```

```cpp
#include <cuda_runtime.h>
#include <cuda_bf16.h>
#include <cuda.h>
#include <stdint.h>

namespace {

typedef __nv_bfloat16 bf16;

constexpr int T_SEQ = 2048, T_D = 1024, T_NH = 32, T_DH = 128, T_DQKV = 4096, T_F = 3584;

struct __align__(2048) TailMail {
  float4 part1[T_SEQ * 8];
  uint32_t key[512];
  uint4 cand[16 * 2 * 2 * 128];
  uint32_t cnt[32];
  float ypart[(T_F / 32) * 2 * T_D];
};
constexpr int O_LD = T_DQKV, O_H = 16 * T_DH;
struct __align__(2048) Scratch {
  TailMail mail;
  float mod[2 * T_D];
  float modu[16 * 512];
  float2 stat[T_SEQ * 2];
  uint32_t gkey[160];
  uint8_t col[8 * 1536];
  unsigned int hcnt[17 * 32];
  float scal[4];
  __align__(1024) bf16 o[T_SEQ * O_LD];
};
__device__ Scratch g_scr;
#define g_part1 hm->mail.part1
#define g_key hm->mail.key
#define g_cand hm->mail.cand
#define CNT_Y hm->mail.cnt
#define g_ypart hm->mail.ypart
#define g_col hm->col
#define g_scal hm->scal
#define g_hcnt hm->hcnt

__device__ __forceinline__ uint32_t smem_u32(const void* p) { return (uint32_t)__cvta_generic_to_shared(p); }
__device__ __forceinline__ void mbar_init(uint32_t bar, uint32_t cnt) { asm volatile("mbarrier.init.shared::cta.b64 [%0], %1;" :: "r"(bar), "r"(cnt)); }
__device__ __forceinline__ void mbar_expect_tx(uint32_t bar, uint32_t bytes) { asm volatile("mbarrier.arrive.expect_tx.shared::cta.b64 _, [%0], %1;" :: "r"(bar), "r"(bytes) : "memory"); }
__device__ __forceinline__ void mbar_arrive(uint32_t bar) { asm volatile("mbarrier.arrive.shared::cta.b64 _, [%0];" :: "r"(bar) : "memory"); }
__device__ __forceinline__ void mbar_wait(uint32_t bar, uint32_t parity) {
  asm volatile("{\n.reg .pred p;\nLAB_WAIT:\nmbarrier.try_wait.parity.shared::cta.b64 p, [%0], %1;\n@!p bra LAB_WAIT;\n}\n" :: "r"(bar), "r"(parity) : "memory");
}
__device__ __forceinline__ bool mbar_test(uint32_t bar, uint32_t parity) {
  uint32_t r; asm volatile("{\n.reg .pred p;\nmbarrier.test_wait.parity.shared::cta.b64 p, [%1], %2;\nselp.u32 %0, 1, 0, p;\n}\n" : "=r"(r) : "r"(bar), "r"(parity) : "memory");
  return r != 0;
}
__device__ __forceinline__ void fence_mbar_init() { asm volatile("fence.mbarrier_init.release.cluster;" ::: "memory"); }
__device__ __forceinline__ uint64_t policy_evict_first() {
  uint64_t p; asm volatile("createpolicy.fractional.L2::evict_first.b64 %0, 1.0;" : "=l"(p)); return p;
}
__device__ __forceinline__ void tma_load_2d_hint(uint32_t dst, const CUtensorMap* map, int c0, int c1, uint32_t bar, uint64_t pol) {
  asm volatile("cp.async.bulk.tensor.2d.shared::cluster.global.mbarrier::complete_tx::bytes.L2::cache_hint [%0], [%1, {%3, %4}], [%2], %5;"
    :: "r"(dst), "l"(map), "r"(bar), "r"(c0), "r"(c1), "l"(pol) : "memory");
}
__device__ __forceinline__ void tma_load_3d_hint(uint32_t dst, const CUtensorMap* map, int c1, int c2, uint32_t bar, uint64_t pol) {
  asm volatile("cp.async.bulk.tensor.3d.shared::cluster.global.mbarrier::complete_tx::bytes.L2::cache_hint [%0], [%1, {%6, %3, %4}], [%2], %5;"
    :: "r"(dst), "l"(map), "r"(bar), "r"(c1), "r"(c2), "l"(pol), "r"(0) : "memory");
}
__device__ __forceinline__ void tma_store_2d(const CUtensorMap* map, uint32_t src, int c0, int c1) {
  asm volatile("cp.async.bulk.tensor.2d.global.shared::cta.bulk_group [%0, {%2, %3}], [%1];" :: "l"(map), "r"(src), "r"(c0), "r"(c1) : "memory");
}
__device__ __forceinline__ void prefetch_tmap(const CUtensorMap* map) { asm volatile("prefetch.tensormap [%0];" :: "l"(map) : "memory"); }
__device__ __forceinline__ void l2_prefetch_bulk(const void* p, uint32_t bytes) {
  asm volatile("cp.async.bulk.prefetch.L2.global [%0], %1;" :: "l"(p), "r"(bytes) : "memory");
}
__device__ __forceinline__ void bulk_commit() { asm volatile("cp.async.bulk.commit_group;" ::: "memory"); }
template<int N> __device__ __forceinline__ void bulk_wait_read() { asm volatile("cp.async.bulk.wait_group.read %0;" :: "n"(N) : "memory"); }
template<int N> __device__ __forceinline__ void bulk_wait() { asm volatile("cp.async.bulk.wait_group %0;" :: "n"(N) : "memory"); }
__device__ __forceinline__ void named_bar_sync(int id, int nthreads) { asm volatile("bar.sync %0, %1;" :: "r"(id), "r"(nthreads) : "memory"); }
__device__ __forceinline__ void named_bar_arrive(int id, int nthreads) { asm volatile("bar.arrive %0, %1;" :: "r"(id), "r"(nthreads) : "memory"); }
__device__ __forceinline__ void wgmma_fence() { asm volatile("wgmma.fence.sync.aligned;" ::: "memory"); }
__device__ __forceinline__ void wgmma_commit() { asm volatile("wgmma.commit_group.sync.aligned;" ::: "memory"); }
template<int N> __device__ __forceinline__ void wgmma_wait() { asm volatile("wgmma.wait_group.sync.aligned %0;" :: "n"(N) : "memory"); }
template<int R> __device__ __forceinline__ void reg_alloc() { asm volatile("setmaxnreg.inc.sync.aligned.u32 %0;" :: "n"(R)); }
template<int R> __device__ __forceinline__ void reg_dealloc() { asm volatile("setmaxnreg.dec.sync.aligned.u32 %0;" :: "n"(R)); }
__device__ __forceinline__ bool elect_one() {
  uint32_t pred; asm volatile("{\n.reg .pred p;\nelect.sync _|p, 0xffffffff;\nselp.u32 %0, 1, 0, p;\n}\n" : "=r"(pred)); return pred != 0;
}
__device__ __forceinline__ uint32_t pack_bf16(float lo, float hi) {
  uint32_t r; asm("cvt.rn.bf16x2.f32 %0, %1, %2;" : "=r"(r) : "f"(hi), "f"(lo)); return r;
}
__device__ __forceinline__ void stmatrix_x4(uint32_t addr, uint32_t r0, uint32_t r1, uint32_t r2, uint32_t r3) {
  asm volatile("stmatrix.sync.aligned.m8n8.x4.shared.b16 [%0], {%1, %2, %3, %4};" :: "r"(addr), "r"(r0), "r"(r1), "r"(r2), "r"(r3) : "memory");
}
__device__ __forceinline__ void fence_proxy_async() { asm volatile("fence.proxy.async.shared::cta;" ::: "memory"); }
__device__ __forceinline__ float ex2_approx(float x) { float y; asm("ex2.approx.ftz.f32 %0, %1;" : "=f"(y) : "f"(x)); return y; }
template<int N> __device__ __forceinline__ void fence_regs(float (&r)[N]) {
  #pragma unroll
  for (int i = 0; i < N; i++) asm volatile("" : "+f"(r[i]) :: "memory");
}
template<int N> __device__ __forceinline__ void zero_regs(float (&r)[N]) {
  #pragma unroll
  for (int i = 0; i < N; i += 2) asm volatile("mov.b64 {%0, %1}, 0;" : "=f"(r[i]), "=f"(r[i + 1]));
}
__device__ __forceinline__ float rbf(float x) { return __uint_as_float(pack_bf16(0.f, x)); }
__device__ __forceinline__ float bflo(uint32_t v) { return __uint_as_float(v << 16); }
__device__ __forceinline__ float bfhi(uint32_t v) { return __uint_as_float(v & 0xffff0000u); }

#define TL_START(k) do {} while (0)
#define TL_END(k, cond) do {} while (0)
#define TL_CTA(i, cond) do {} while (0)
#define FS(slot, k) do {} while (0)
#define QS(idx) do {} while (0)
#define QDUMP() do {} while (0)
#define TL_MARK2(k, cond) do {} while (0)
#define TL_CLK(k, i, cond) do {} while (0)

#define HS(k) do {} while (0)
#define HSD(k, dep) do {} while (0)
#define HSDUMP() do {} while (0)
#define PS(k, cond) do {} while (0)
#define PSV(k, cond, v) do {} while (0)
#define PF(k) do {} while (0)
#define TS(k, cond) do {} while (0)
template <int OFFA, int OFFB>
__device__ __forceinline__ void wgmma_m64n256k16_ss_tb(float (&d)[128], uint32_t a_lo, uint32_t b_lo, int scaleD) {
  asm volatile("{\n.reg .pred p;\n.reg .b32 ta, tb;\n.reg .b64 da, db;\nsetp.ne.b32 p, %130, 0;\n"
    "add.u32 ta, %128, %131;\nadd.u32 tb, %129, %132;\n"
    "mov.b64 da, {ta, 0x40000040};\nmov.b64 db, {tb, 0x40000040};\n"
    "wgmma.mma_async.sync.aligned.m64n256k16.f32.bf16.bf16 "
    "{%0, %1, %2, %3, %4, %5, %6, %7, %8, %9, %10, %11, %12, %13, %14, %15, %16, %17, %18, %19, %20, %21, %22, %23, %24, %25, %26, %27, %28, %29, %30, %31, %32, %33, %34, %35, %36, %37, %38, %39, %40, %41, %42, %43, %44, %45, %46, %47, %48, %49, %50, %51, %52, %53, %54, %55, %56, %57, %58, %59, %60, %61, %62, %63, %64, %65, %66, %67, %68, %69, %70, %71, %72, %73, %74, %75, %76, %77, %78, %79, %80, %81, %82, %83, %84, %85, %86, %87, %88, %89, %90, %91, %92, %93, %94, %95, %96, %97, %98, %99, %100, %101, %102, %103, %104, %105, %106, %107, %108, %109, %110, %111, %112, %113, %114, %115, %116, %117, %118, %119, %120, %121, %122, %123, %124, %125, %126, %127}, "
    "da, db, p, 1, 1, 0, 1;\n}\n"
    : "+f"(d[0]), "+f"(d[1]), "+f"(d[2]), "+f"(d[3]), "+f"(d[4]), "+f"(d[5]), "+f"(d[6]), "+f"(d[7]), "+f"(d[8]), "+f"(d[9]), "+f"(d[10]), "+f"(d[11]), "+f"(d[12]), "+f"(d[13]), "+f"(d[14]), "+f"(d[15]), "+f"(d[16]), "+f"(d[17]), "+f"(d[18]), "+f"(d[19]), "+f"(d[20]), "+f"(d[21]), "+f"(d[22]), "+f"(d[23]), "+f"(d[24]), "+f"(d[25]), "+f"(d[26]), "+f"(d[27]), "+f"(d[28]), "+f"(d[29]), "+f"(d[30]), "+f"(d[31]), "+f"(d[32]), "+f"(d[33]), "+f"(d[34]), "+f"(d[35]), "+f"(d[36]), "+f"(d[37]), "+f"(d[38]), "+f"(d[39]), "+f"(d[40]), "+f"(d[41]), "+f"(d[42]), "+f"(d[43]), "+f"(d[44]), "+f"(d[45]), "+f"(d[46]), "+f"(d[47]), "+f"(d[48]), "+f"(d[49]), "+f"(d[50]), "+f"(d[51]), "+f"(d[52]), "+f"(d[53]), "+f"(d[54]), "+f"(d[55]), "+f"(d[56]), "+f"(d[57]), "+f"(d[58]), "+f"(d[59]), "+f"(d[60]), "+f"(d[61]), "+f"(d[62]), "+f"(d[63]), "+f"(d[64]), "+f"(d[65]), "+f"(d[66]), "+f"(d[67]), "+f"(d[68]), "+f"(d[69]), "+f"(d[70]), "+f"(d[71]), "+f"(d[72]), "+f"(d[73]), "+f"(d[74]), "+f"(d[75]), "+f"(d[76]), "+f"(d[77]), "+f"(d[78]), "+f"(d[79]), "+f"(d[80]), "+f"(d[81]), "+f"(d[82]), "+f"(d[83]), "+f"(d[84]), "+f"(d[85]), "+f"(d[86]), "+f"(d[87]), "+f"(d[88]), "+f"(d[89]), "+f"(d[90]), "+f"(d[91]), "+f"(d[92]), "+f"(d[93]), "+f"(d[94]), "+f"(d[95]), "+f"(d[96]), "+f"(d[97]), "+f"(d[98]), "+f"(d[99]), "+f"(d[100]), "+f"(d[101]), "+f"(d[102]), "+f"(d[103]), "+f"(d[104]), "+f"(d[105]), "+f"(d[106]), "+f"(d[107]), "+f"(d[108]), "+f"(d[109]), "+f"(d[110]), "+f"(d[111]), "+f"(d[112]), "+f"(d[113]), "+f"(d[114]), "+f"(d[115]), "+f"(d[116]), "+f"(d[117]), "+f"(d[118]), "+f"(d[119]), "+f"(d[120]), "+f"(d[121]), "+f"(d[122]), "+f"(d[123]), "+f"(d[124]), "+f"(d[125]), "+f"(d[126]), "+f"(d[127])
    : "r"(a_lo), "r"(b_lo), "r"(scaleD), "n"(OFFA), "n"(OFFB));
}

template <int OFFA, int OFFB>
__device__ __forceinline__ void wgmma_m64n128k16_ss_tb(float (&d)[64], uint32_t a_lo, uint32_t b_lo, int scaleD) {
  asm volatile("{\n.reg .pred p;\n.reg .b32 ta, tb;\n.reg .b64 da, db;\nsetp.ne.b32 p, %66, 0;\n"
    "add.u32 ta, %64, %67;\nadd.u32 tb, %65, %68;\n"
    "mov.b64 da, {ta, 0x40000040};\nmov.b64 db, {tb, 0x40000040};\n"
    "wgmma.mma_async.sync.aligned.m64n128k16.f32.bf16.bf16 "
    "{%0, %1, %2, %3, %4, %5, %6, %7, %8, %9, %10, %11, %12, %13, %14, %15, %16, %17, %18, %19, %20, %21, %22, %23, %24, %25, %26, %27, %28, %29, %30, %31, %32, %33, %34, %35, %36, %37, %38, %39, %40, %41, %42, %43, %44, %45, %46, %47, %48, %49, %50, %51, %52, %53, %54, %55, %56, %57, %58, %59, %60, %61, %62, %63}, "
    "da, db, p, 1, 1, 0, 1;\n}\n"
    : "+f"(d[0]), "+f"(d[1]), "+f"(d[2]), "+f"(d[3]), "+f"(d[4]), "+f"(d[5]), "+f"(d[6]), "+f"(d[7]), "+f"(d[8]), "+f"(d[9]), "+f"(d[10]), "+f"(d[11]), "+f"(d[12]), "+f"(d[13]), "+f"(d[14]), "+f"(d[15]), "+f"(d[16]), "+f"(d[17]), "+f"(d[18]), "+f"(d[19]), "+f"(d[20]), "+f"(d[21]), "+f"(d[22]), "+f"(d[23]), "+f"(d[24]), "+f"(d[25]), "+f"(d[26]), "+f"(d[27]), "+f"(d[28]), "+f"(d[29]), "+f"(d[30]), "+f"(d[31]), "+f"(d[32]), "+f"(d[33]), "+f"(d[34]), "+f"(d[35]), "+f"(d[36]), "+f"(d[37]), "+f"(d[38]), "+f"(d[39]), "+f"(d[40]), "+f"(d[41]), "+f"(d[42]), "+f"(d[43]), "+f"(d[44]), "+f"(d[45]), "+f"(d[46]), "+f"(d[47]), "+f"(d[48]), "+f"(d[49]), "+f"(d[50]), "+f"(d[51]), "+f"(d[52]), "+f"(d[53]), "+f"(d[54]), "+f"(d[55]), "+f"(d[56]), "+f"(d[57]), "+f"(d[58]), "+f"(d[59]), "+f"(d[60]), "+f"(d[61]), "+f"(d[62]), "+f"(d[63])
    : "r"(a_lo), "r"(b_lo), "r"(scaleD), "n"(OFFA), "n"(OFFB));
}

template <int OFFB>
__device__ __forceinline__ void wgmma_m64n256k16_rs_tb(float (&d)[128], uint32_t a0, uint32_t a1, uint32_t a2, uint32_t a3, uint32_t b_lo, int scaleD) {
  asm volatile("{\n.reg .pred p;\n.reg .b32 tb;\n.reg .b64 db;\nsetp.ne.b32 p, %133, 0;\n"
    "add.u32 tb, %132, %134;\n"
    "mov.b64 db, {tb, 0x40000040};\n"
    "wgmma.mma_async.sync.aligned.m64n256k16.f32.bf16.bf16 "
    "{%0, %1, %2, %3, %4, %5, %6, %7, %8, %9, %10, %11, %12, %13, %14, %15, %16, %17, %18, %19, %20, %21, %22, %23, %24, %25, %26, %27, %28, %29, %30, %31, %32, %33, %34, %35, %36, %37, %38, %39, %40, %41, %42, %43, %44, %45, %46, %47, %48, %49, %50, %51, %52, %53, %54, %55, %56, %57, %58, %59, %60, %61, %62, %63, %64, %65, %66, %67, %68, %69, %70, %71, %72, %73, %74, %75, %76, %77, %78, %79, %80, %81, %82, %83, %84, %85, %86, %87, %88, %89, %90, %91, %92, %93, %94, %95, %96, %97, %98, %99, %100, %101, %102, %103, %104, %105, %106, %107, %108, %109, %110, %111, %112, %113, %114, %115, %116, %117, %118, %119, %120, %121, %122, %123, %124, %125, %126, %127}, "
    "{%128, %129, %130, %131}, db, p, 1, 1, 1;\n}\n"
    : "+f"(d[0]), "+f"(d[1]), "+f"(d[2]), "+f"(d[3]), "+f"(d[4]), "+f"(d[5]), "+f"(d[6]), "+f"(d[7]), "+f"(d[8]), "+f"(d[9]), "+f"(d[10]), "+f"(d[11]), "+f"(d[12]), "+f"(d[13]), "+f"(d[14]), "+f"(d[15]), "+f"(d[16]), "+f"(d[17]), "+f"(d[18]), "+f"(d[19]), "+f"(d[20]), "+f"(d[21]), "+f"(d[22]), "+f"(d[23]), "+f"(d[24]), "+f"(d[25]), "+f"(d[26]), "+f"(d[27]), "+f"(d[28]), "+f"(d[29]), "+f"(d[30]), "+f"(d[31]), "+f"(d[32]), "+f"(d[33]), "+f"(d[34]), "+f"(d[35]), "+f"(d[36]), "+f"(d[37]), "+f"(d[38]), "+f"(d[39]), "+f"(d[40]), "+f"(d[41]), "+f"(d[42]), "+f"(d[43]), "+f"(d[44]), "+f"(d[45]), "+f"(d[46]), "+f"(d[47]), "+f"(d[48]), "+f"(d[49]), "+f"(d[50]), "+f"(d[51]), "+f"(d[52]), "+f"(d[53]), "+f"(d[54]), "+f"(d[55]), "+f"(d[56]), "+f"(d[57]), "+f"(d[58]), "+f"(d[59]), "+f"(d[60]), "+f"(d[61]), "+f"(d[62]), "+f"(d[63]), "+f"(d[64]), "+f"(d[65]), "+f"(d[66]), "+f"(d[67]), "+f"(d[68]), "+f"(d[69]), "+f"(d[70]), "+f"(d[71]), "+f"(d[72]), "+f"(d[73]), "+f"(d[74]), "+f"(d[75]), "+f"(d[76]), "+f"(d[77]), "+f"(d[78]), "+f"(d[79]), "+f"(d[80]), "+f"(d[81]), "+f"(d[82]), "+f"(d[83]), "+f"(d[84]), "+f"(d[85]), "+f"(d[86]), "+f"(d[87]), "+f"(d[88]), "+f"(d[89]), "+f"(d[90]), "+f"(d[91]), "+f"(d[92]), "+f"(d[93]), "+f"(d[94]), "+f"(d[95]), "+f"(d[96]), "+f"(d[97]), "+f"(d[98]), "+f"(d[99]), "+f"(d[100]), "+f"(d[101]), "+f"(d[102]), "+f"(d[103]), "+f"(d[104]), "+f"(d[105]), "+f"(d[106]), "+f"(d[107]), "+f"(d[108]), "+f"(d[109]), "+f"(d[110]), "+f"(d[111]), "+f"(d[112]), "+f"(d[113]), "+f"(d[114]), "+f"(d[115]), "+f"(d[116]), "+f"(d[117]), "+f"(d[118]), "+f"(d[119]), "+f"(d[120]), "+f"(d[121]), "+f"(d[122]), "+f"(d[123]), "+f"(d[124]), "+f"(d[125]), "+f"(d[126]), "+f"(d[127])
    : "r"(a0), "r"(a1), "r"(a2), "r"(a3), "r"(b_lo), "r"(scaleD), "n"(OFFB));
}

template <int OFFB>
__device__ __forceinline__ void wgmma_m64n128k16_rs_tb(float (&d)[64], uint32_t a0, uint32_t a1, uint32_t a2, uint32_t a3, uint32_t b_lo, int scaleD) {
  asm volatile("{\n.reg .pred p;\n.reg .b32 tb;\n.reg .b64 db;\nsetp.ne.b32 p, %69, 0;\n"
    "add.u32 tb, %68, %70;\n"
    "mov.b64 db, {tb, 0x40000040};\n"
    "wgmma.mma_async.sync.aligned.m64n128k16.f32.bf16.bf16 "
    "{%0, %1, %2, %3, %4, %5, %6, %7, %8, %9, %10, %11, %12, %13, %14, %15, %16, %17, %18, %19, %20, %21, %22, %23, %24, %25, %26, %27, %28, %29, %30, %31, %32, %33, %34, %35, %36, %37, %38, %39, %40, %41, %42, %43, %44, %45, %46, %47, %48, %49, %50, %51, %52, %53, %54, %55, %56, %57, %58, %59, %60, %61, %62, %63}, "
    "{%64, %65, %66, %67}, db, p, 1, 1, 1;\n}\n"
    : "+f"(d[0]), "+f"(d[1]), "+f"(d[2]), "+f"(d[3]), "+f"(d[4]), "+f"(d[5]), "+f"(d[6]), "+f"(d[7]), "+f"(d[8]), "+f"(d[9]), "+f"(d[10]), "+f"(d[11]), "+f"(d[12]), "+f"(d[13]), "+f"(d[14]), "+f"(d[15]), "+f"(d[16]), "+f"(d[17]), "+f"(d[18]), "+f"(d[19]), "+f"(d[20]), "+f"(d[21]), "+f"(d[22]), "+f"(d[23]), "+f"(d[24]), "+f"(d[25]), "+f"(d[26]), "+f"(d[27]), "+f"(d[28]), "+f"(d[29]), "+f"(d[30]), "+f"(d[31]), "+f"(d[32]), "+f"(d[33]), "+f"(d[34]), "+f"(d[35]), "+f"(d[36]), "+f"(d[37]), "+f"(d[38]), "+f"(d[39]), "+f"(d[40]), "+f"(d[41]), "+f"(d[42]), "+f"(d[43]), "+f"(d[44]), "+f"(d[45]), "+f"(d[46]), "+f"(d[47]), "+f"(d[48]), "+f"(d[49]), "+f"(d[50]), "+f"(d[51]), "+f"(d[52]), "+f"(d[53]), "+f"(d[54]), "+f"(d[55]), "+f"(d[56]), "+f"(d[57]), "+f"(d[58]), "+f"(d[59]), "+f"(d[60]), "+f"(d[61]), "+f"(d[62]), "+f"(d[63])
    : "r"(a0), "r"(a1), "r"(a2), "r"(a3), "r"(b_lo), "r"(scaleD), "n"(OFFB));
}

template <int OFFB>
__device__ __forceinline__ void wgmma_m64n128k16_rs(float (&d)[64], uint32_t a0, uint32_t a1, uint32_t a2, uint32_t a3, uint32_t b_lo, int scaleD) {
  asm volatile("{\n.reg .pred p;\n.reg .b32 tb;\n.reg .b64 db;\nsetp.ne.b32 p, %69, 0;\n"
    "add.u32 tb, %68, %70;\n"
    "mov.b64 db, {tb, 0x40000040};\n"
    "wgmma.mma_async.sync.aligned.m64n128k16.f32.bf16.bf16 "
    "{%0, %1, %2, %3, %4, %5, %6, %7, %8, %9, %10, %11, %12, %13, %14, %15, %16, %17, %18, %19, %20, %21, %22, %23, %24, %25, %26, %27, %28, %29, %30, %31, %32, %33, %34, %35, %36, %37, %38, %39, %40, %41, %42, %43, %44, %45, %46, %47, %48, %49, %50, %51, %52, %53, %54, %55, %56, %57, %58, %59, %60, %61, %62, %63}, "
    "{%64, %65, %66, %67}, db, p, 1, 1, 0;\n}\n"
    : "+f"(d[0]), "+f"(d[1]), "+f"(d[2]), "+f"(d[3]), "+f"(d[4]), "+f"(d[5]), "+f"(d[6]), "+f"(d[7]), "+f"(d[8]), "+f"(d[9]), "+f"(d[10]), "+f"(d[11]), "+f"(d[12]), "+f"(d[13]), "+f"(d[14]), "+f"(d[15]), "+f"(d[16]), "+f"(d[17]), "+f"(d[18]), "+f"(d[19]), "+f"(d[20]), "+f"(d[21]), "+f"(d[22]), "+f"(d[23]), "+f"(d[24]), "+f"(d[25]), "+f"(d[26]), "+f"(d[27]), "+f"(d[28]), "+f"(d[29]), "+f"(d[30]), "+f"(d[31]), "+f"(d[32]), "+f"(d[33]), "+f"(d[34]), "+f"(d[35]), "+f"(d[36]), "+f"(d[37]), "+f"(d[38]), "+f"(d[39]), "+f"(d[40]), "+f"(d[41]), "+f"(d[42]), "+f"(d[43]), "+f"(d[44]), "+f"(d[45]), "+f"(d[46]), "+f"(d[47]), "+f"(d[48]), "+f"(d[49]), "+f"(d[50]), "+f"(d[51]), "+f"(d[52]), "+f"(d[53]), "+f"(d[54]), "+f"(d[55]), "+f"(d[56]), "+f"(d[57]), "+f"(d[58]), "+f"(d[59]), "+f"(d[60]), "+f"(d[61]), "+f"(d[62]), "+f"(d[63])
    : "r"(a0), "r"(a1), "r"(a2), "r"(a3), "r"(b_lo), "r"(scaleD), "n"(OFFB));
}

__device__ __forceinline__ uint4 ldg_nc_v4(const void* p) {
  uint4 v;
    asm volatile("{\n.reg .b64 pol;\ncreatepolicy.fractional.L2::evict_first.b64 pol, 1.0;\n"
                 "ld.global.nc.L1::no_allocate.L2::cache_hint.v4.u32 {%0, %1, %2, %3}, [%4], pol;\n}\n" : "=r"(v.x), "=r"(v.y), "=r"(v.z), "=r"(v.w) : "l"(p));
  return v;
}
__device__ __forceinline__ uint64_t pol_normal() {
  uint64_t p; asm volatile("createpolicy.fractional.L2::evict_normal.b64 %0, 1.0;" : "=l"(p)); return p;
}
__device__ __forceinline__ float rcp_approx(float x) { float y; asm("rcp.approx.ftz.f32 %0, %1;" : "=f"(y) : "f"(x)); return y; }
__device__ __forceinline__ float sigmoid_f(float v) { return rcp_approx(1.0f + ex2_approx(v * -1.4426950408889634f)); }
__device__ __forceinline__ float silu_bf(float v) { return rbf(v * sigmoid_f(v)); }
__device__ __forceinline__ uint32_t rank_key(float r, int idx) {
  const uint32_t b = __float_as_uint(r) >> 16;
  const uint32_t u = (r != r) ? 0u : ((b & 0x8000u) ? (~b & 0xffffu) : (b | 0x8000u));
  return (u << 16) | (0xffffu - (uint32_t)idx);
}
__device__ __forceinline__ void warp_top2(uint32_t& k1, uint32_t& k2) {
  const uint32_t m1 = __reduce_max_sync(0xffffffffu, k1);
  k2 = __reduce_max_sync(0xffffffffu, k1 == m1 ? k2 : k1);
  k1 = m1;
}
__device__ __forceinline__ uint32_t bmul2(uint32_t a, uint32_t b) { uint32_t r; asm("mul.rn.bf16x2 %0, %1, %2;" : "=r"(r) : "r"(a), "r"(b)); return r; }
__device__ __forceinline__ uint32_t badd2(uint32_t a, uint32_t b) { uint32_t r; asm("add.rn.bf16x2 %0, %1, %2;" : "=r"(r) : "r"(a), "r"(b)); return r; }
__device__ __forceinline__ uint32_t bsub2(uint32_t a, uint32_t b) { uint32_t r; asm("sub.rn.bf16x2 %0, %1, %2;" : "=r"(r) : "r"(a), "r"(b)); return r; }
__device__ __forceinline__ float sqrt_approx(float x) { float y; asm("sqrt.approx.f32 %0, %1;" : "=f"(y) : "f"(x)); return y; }
__device__ __forceinline__ uint32_t ln_norm2(uint32_t x1, uint32_t mb2, float inv) {
  const uint32_t d = bsub2(x1, mb2);
  return pack_bf16(bflo(d) * inv, bfhi(d) * inv);
}
__device__ __forceinline__ uint32_t ln_mod2(uint32_t x1, uint32_t mb2, float inv, uint32_t c1, uint32_t sb) { return badd2(bmul2(ln_norm2(x1, mb2, inv), c1), sb); }
__device__ __forceinline__ void ldmatrix_x4(uint32_t addr, uint32_t& r0, uint32_t& r1, uint32_t& r2, uint32_t& r3) {
  asm volatile("ldmatrix.sync.aligned.m8n8.x4.shared.b16 {%0, %1, %2, %3}, [%4];" : "=r"(r0), "=r"(r1), "=r"(r2), "=r"(r3) : "r"(addr) : "memory");
}
__device__ __forceinline__ uint4 ldg_stream_v4(const void* p, uint64_t pol) {
  uint4 v; asm volatile("ld.global.nc.L1::no_allocate.L2::cache_hint.L2::128B.v4.u32 {%0, %1, %2, %3}, [%4], %5;" : "=r"(v.x), "=r"(v.y), "=r"(v.z), "=r"(v.w) : "l"(p), "l"(pol)); return v;
}
__device__ __forceinline__ void bulk_load_hint(uint32_t dst, const void* src, uint32_t bytes, uint32_t bar, uint64_t pol) {
  asm volatile("cp.async.bulk.shared::cluster.global.mbarrier::complete_tx::bytes.L2::cache_hint [%0], [%1], %2, [%3], %4;"
    :: "r"(dst), "l"(src), "r"(bytes), "r"(bar), "l"(pol) : "memory");
}
__device__ __forceinline__ void red_release_add(unsigned int* p, unsigned int v) { asm volatile("red.release.gpu.global.add.u32 [%0], %1;" :: "l"(p), "r"(v) : "memory"); }
__device__ __forceinline__ unsigned int ld_acquire(const unsigned int* p) { unsigned int v; asm volatile("ld.acquire.gpu.global.u32 %0, [%1];" : "=r"(v) : "l"(p) : "memory"); return v; }
__device__ __forceinline__ void spin_until(const unsigned int* p, unsigned int target) {
  #pragma unroll 1
  for (unsigned int i = 0; i < (1u << 22); i++) { if (ld_acquire(p) >= target) return; }
}
__device__ __forceinline__ float lds_f32(uint32_t a) { float v; asm volatile("ld.shared.f32 %0, [%1];" : "=f"(v) : "r"(a) : "memory"); return v; }
__device__ __forceinline__ uint2 lds_u32x2(uint32_t a) { uint2 v; asm volatile("ld.shared.v2.u32 {%0, %1}, [%2];" : "=r"(v.x), "=r"(v.y) : "r"(a) : "memory"); return v; }
__device__ __forceinline__ uint32_t lds_u32(uint32_t a) { uint32_t v; asm volatile("ld.shared.u32 %0, [%1];" : "=r"(v) : "r"(a) : "memory"); return v; }
__device__ __forceinline__ void sts_u32(uint32_t a, uint32_t v) { asm volatile("st.shared.u32 [%0], %1;" :: "r"(a), "r"(v) : "memory"); }
__device__ __forceinline__ void sts_u32x2(uint32_t a, uint32_t x, uint32_t y) { asm volatile("st.shared.v2.u32 [%0], {%1, %2};" :: "r"(a), "r"(x), "r"(y) : "memory"); }
__device__ __forceinline__ void sts_f32(uint32_t a, float v) { asm volatile("st.shared.f32 [%0], %1;" :: "r"(a), "f"(v) : "memory"); }
__device__ __forceinline__ void sts_f32x4(uint32_t a, float x, float y, float z, float w) { asm volatile("st.shared.v4.f32 [%0], {%1, %2, %3, %4};" :: "r"(a), "f"(x), "f"(y), "f"(z), "f"(w) : "memory"); }

__device__ __forceinline__ uint4 lds_u32x4(uint32_t a) { uint4 v; asm volatile("ld.shared.v4.u32 {%0, %1, %2, %3}, [%4];" : "=r"(v.x), "=r"(v.y), "=r"(v.z), "=r"(v.w) : "r"(a) : "memory"); return v; }
__device__ __forceinline__ void sts_u32x4(uint32_t a, uint32_t x, uint32_t y, uint32_t z, uint32_t w) { asm volatile("st.shared.v4.u32 [%0], {%1, %2, %3, %4};" :: "r"(a), "r"(x), "r"(y), "r"(z), "r"(w) : "memory"); }
__device__ __forceinline__ void st_tagged(float* p, float v) {
  const uint32_t b = __float_as_uint(v);
  asm volatile("st.relaxed.gpu.global.u32 [%0], %1;" :: "l"(p), "r"(b == 0u ? 0x80000000u : b) : "memory");
}
__device__ __forceinline__ void st_tagged4(float* p, float x, float y, float z, float w) {
  const uint32_t a = __float_as_uint(x), b = __float_as_uint(y), c = __float_as_uint(z), d = __float_as_uint(w);
  asm volatile("st.relaxed.gpu.global.v4.u32 [%0], {%1, %2, %3, %4};" :: "l"(p), "r"(a == 0u ? 0x80000000u : a), "r"(b == 0u ? 0x80000000u : b),
               "r"(c == 0u ? 0x80000000u : c), "r"(d == 0u ? 0x80000000u : d) : "memory");
}
__device__ __forceinline__ void st_relaxed2(void* p, uint32_t a, uint32_t b) { asm volatile("st.relaxed.gpu.global.v2.u32 [%0], {%1, %2};" :: "l"(p), "r"(a), "r"(b) : "memory"); }
__device__ __forceinline__ float4 ld_tagged4(const float* p) {
  float4 v; asm volatile("ld.relaxed.gpu.global.v4.f32 {%0, %1, %2, %3}, [%4];" : "=f"(v.x), "=f"(v.y), "=f"(v.z), "=f"(v.w) : "l"(p) : "memory"); return v;
}
__device__ __forceinline__ bool tagged4(const float4& v) {
  return __float_as_uint(v.x) != 0u && __float_as_uint(v.y) != 0u && __float_as_uint(v.z) != 0u && __float_as_uint(v.w) != 0u;
}
__device__ __forceinline__ void hint_arrive(uint32_t* p) { asm volatile("red.relaxed.gpu.global.add.u32 [%0], 1;" :: "l"(p) : "memory"); }
__device__ __forceinline__ void hint_wait(const uint32_t* p, uint32_t target) {
  uint32_t v = 0u;
  #pragma unroll 1
  for (unsigned int i = 0; i < (1u << 22) && v < target; i++) asm volatile("ld.relaxed.gpu.global.u32 %0, [%1];" : "=r"(v) : "l"(p) : "memory");
}
__device__ __forceinline__ void fence_proxy_async_global() { asm volatile("fence.proxy.async.global;" ::: "memory"); }

__device__ __forceinline__ void mma_bf16(float (&d)[4], uint32_t a0, uint32_t a1, uint32_t a2, uint32_t a3, uint32_t b0, uint32_t b1) {
  asm volatile("mma.sync.aligned.m16n8k16.row.col.f32.bf16.bf16.f32 {%0, %1, %2, %3}, {%4, %5, %6, %7}, {%8, %9}, {%0, %1, %2, %3};"
               : "+f"(d[0]), "+f"(d[1]), "+f"(d[2]), "+f"(d[3]) : "r"(a0), "r"(a1), "r"(a2), "r"(a3), "r"(b0), "r"(b1));
}
__device__ __forceinline__ uint32_t bfma2(uint32_t a, uint32_t b, uint32_t c) { uint32_t r; asm("fma.rn.bf16x2 %0, %1, %2, %3;" : "=r"(r) : "r"(a), "r"(b), "r"(c)); return r; }
#define XDLY 1000
#define PRE_T 1000
#define GDLY 4150
#define A_T 4800
#define SDLY 5800
#define ST1_T 6000
#define GDLY2 8000
#define WDLY 3800
#define W_OFF 2000
#define W_GAP 300
#define W_RND 3600
#define W_LATE 27000
#define CLR_T 70000
#define SGL_T 79000
#define OG_PRE 12
#define OG_LEN 6
#define WD_0 16
#define WD_S 6
#define YD 2900
#define NDUM 16
__device__ __forceinline__ uint32_t clock_lo() { uint32_t c; asm volatile("mov.u32 %0, %%clock;" : "=r"(c) :: "memory"); return c; }
__device__ __forceinline__ void wait_clock(uint32_t t0, uint32_t n) {
  #pragma unroll 1
  while (clock_lo() - t0 < n) {}
}
__device__ __forceinline__ void sleep_until(uint32_t t0, uint32_t n) {
  #pragma unroll 1
  while (clock_lo() - t0 < n) __nanosleep(500);
}
__device__ __forceinline__ float2 ld_tagged2(const float2* p) {
  float2 v; asm volatile("ld.relaxed.gpu.global.v2.f32 {%0, %1}, [%2];" : "=f"(v.x), "=f"(v.y) : "l"(p) : "memory"); return v;
}
template <int N>
__device__ __forceinline__ void gemv64(float (&d)[2][4], const uint4 (&w)[N], const uint32_t (&sv)[N / 2], int lane) {
  const int g = lane >> 2;
  const uint32_t lo = (g & 1) ? 0x1044u : 0x4410u, hi = (g & 1) ? 0x3244u : 0x4432u;
  const uint32_t lo0 = g < 2 ? lo : 0x4444u, hi0 = g < 2 ? hi : 0x4444u, lo1 = (g & 6) == 2 ? lo : 0x4444u, hi1 = (g & 6) == 2 ? hi : 0x4444u;
  #pragma unroll
  for (int i = 0; i < N; i++)
    mma_bf16(d[i & 1], w[i].x, w[i].y, w[i].z, w[i].w, __byte_perm(sv[i >> 1], 0u, (i & 1) ? hi0 : lo0), __byte_perm(sv[i >> 1], 0u, (i & 1) ? hi1 : lo1));
}
template <int NW>
__device__ __forceinline__ float gemv64_sum(const float (&d)[2][4], uint32_t scr, int t2) {
  if ((t2 & 2) == 0) sts_f32x4(scr + (t2 >> 2) * 32 + (t2 & 1) * 16, d[0][0] + d[1][0], d[0][1] + d[1][1], d[0][2] + d[1][2], d[0][3] + d[1][3]);
  named_bar_sync(NW == 8 ? 5 : 3, NW * 32);
  float sum = 0.f;
  #pragma unroll
  for (int i = 0; i < NW; i += 2) sum += lds_f32(scr + i * 256 + (t2 & 63) * 4) + lds_f32(scr + i * 256 + 256 + (t2 & 63) * 4);
  return sum;
}
__device__ __forceinline__ uint32_t silu2(uint32_t c) { return pack_bf16(silu_bf(bflo(c)), silu_bf(bfhi(c))); }
__device__ __forceinline__ void head_first(Scratch* hm, uint32_t scr, int t2, const bf16* __restrict__ cvec, const bf16* __restrict__ w_mod) {
  const int row = (blockIdx.x >> 3) * 64 + (t2 >> 5) * 16 + (t2 & 3) * 4;
  const bf16* wp = w_mod + (size_t)row * (6 * T_D) + (blockIdx.x & 4) * 256 + (blockIdx.x & 3) * 64 + (t2 & 28) * 2;
  uint4 w[4];
  #pragma unroll
  for (int i = 0; i < 4; i++) w[i] = ldg_nc_v4(wp + i * 6 * T_D);
  const uint2 c = *reinterpret_cast<const uint2*>(cvec + row);
  const uint32_t sv[2] = {silu2(c.x), silu2(c.y)};
  float d[2][4] = {{0.f, 0.f, 0.f, 0.f}, {0.f, 0.f, 0.f, 0.f}};
  gemv64<4>(d, w, sv, t2 & 31);
  const float sum = gemv64_sum<4>(d, scr, t2);
  if (t2 < 64) st_tagged(hm->modu + (blockIdx.x >> 3) * 512 + (blockIdx.x & 7) * 64 + t2, sum);
  HS(1);
}
__device__ __forceinline__ void head_stats(Scratch* hm, uint32_t xs, uint32_t b_x, int tid) {
  const int lane = tid & 31, w = tid >> 5, g = lane >> 2;
  float d[4][4] = {{0.f, 0.f, 0.f, 0.f}, {0.f, 0.f, 0.f, 0.f}, {0.f, 0.f, 0.f, 0.f}, {0.f, 0.f, 0.f, 0.f}};
  const uint32_t xa = xs + ((w & 1) * 8 + g) * 2048 + (w >> 1) * 1024 + (g & 1) * 64 + (lane & 3) * 16;
  float2* dst = hm->stat + ((blockIdx.x * 2 + (w & 1)) * 2 + (w >> 1)) * 8 + g;
  mbar_wait(b_x, 0);
  #pragma unroll
  for (int j = 0; j < 16; j++) {
    const uint4 v = lds_u32x4((xa ^ ((j & 1) * 64)) + (j >> 1) * 128);
    mma_bf16(d[2 * (j & 1)], v.x, 0x3F803F80u, v.y, 0x3F803F80u, v.x, v.y);
    mma_bf16(d[2 * (j & 1) + 1], v.z, 0x3F803F80u, v.w, 0x3F803F80u, v.z, v.w);
  }
  #pragma unroll
  for (int e = 0; e < 4; e++) d[0][e] = (d[0][e] + d[1][e]) + (d[2][e] + d[3][e]);
  const uint32_t sm = __float_as_uint((g & 1) ? d[0][3] : d[0][2]), sq = __float_as_uint((g & 1) ? d[0][1] : d[0][0]);
  if ((lane & 3) == (g >> 1)) st_relaxed2(dst, sm == 0u ? 0x80000000u : sm, sq == 0u ? 0x80000000u : sq);
  HSD(3, sm);
}
__device__ __forceinline__ void put_table(uint32_t tab, int l, bool ca, const float4& v) {
  uint32_t m0 = pack_bf16(v.x, v.y), m1 = pack_bf16(v.z, v.w);
  if (ca) { m0 = badd2(m0, 0x3F803F80u); m1 = badd2(m1, 0x3F803F80u); }
  tab += (l >> 2) * 64 + (l & 1) * 32 + (l & 2) * 2 + (ca ? 0 : 8);
  sts_u32(tab, m0); sts_u32(tab + 16, m1);
}
__device__ __forceinline__ void head_gather(Scratch* hm, uint32_t tab, int tid) {
  float4 p[16];
  #pragma unroll 1
  for (unsigned int spin = 0; spin < (1u << 22); spin++) {
    uint32_t m = 0xffffffffu;
    #pragma unroll
    for (int k = 0; k < 16; k++) p[k] = ld_tagged4(hm->modu + k * 512 + tid * 4);
    #pragma unroll
    for (int k = 0; k < 16; k++) m = min(min(m, min(__float_as_uint(p[k].x), __float_as_uint(p[k].y))), min(__float_as_uint(p[k].z), __float_as_uint(p[k].w)));
    if (m != 0u) break;
  }
  #pragma unroll
  for (int o = 1; o < 16; o <<= 1)
    #pragma unroll
    for (int k = 0; k < 16; k += 2 * o) { p[k].x += p[k + o].x; p[k].y += p[k + o].y; p[k].z += p[k + o].z; p[k].w += p[k + o].w; }
  put_table(tab, tid & 63, tid >= 64, p[0]);
  __syncwarp();
  HS(2);
}
__device__ __forceinline__ uint32_t ln_stat(float sm, float sq) {
  const float mean = sm * (1.0f / T_D), var = fmaxf(fmaf(-mean, mean, sq * (1.0f / T_D)), 0.f);
  return pack_bf16(mean, sqrt_approx(rbf(rbf(var) + 1e-05f)));
}
__device__ __forceinline__ void gather_table(Scratch* hm, uint32_t tab0, uint32_t b_tab, int a, int lane) {
  #pragma unroll 1
  for (int r = 2; r < 8; r++) {
    float4 v;
    #pragma unroll 1
    for (unsigned int spin = 0; spin < (1u << 22); spin++) {
      v = ld_tagged4(hm->mod + a * T_D + r * 128 + lane * 4);
      if (__all_sync(0xffffffffu, tagged4(v))) break;
      __nanosleep(50);
    }
    put_table(tab0 + r * 512, lane, a, v);
    __syncwarp();
    if (lane == 0) mbar_arrive(b_tab + 8 * r);
    if (r < 6) HS(2 + r);
  }
}

__device__ __forceinline__ uint32_t assign_tile(Scratch* hm, uint32_t t0, int lane) {
  uint32_t me; asm("mov.u32 %0, %%smid;" : "=r"(me));
  me = (me & 255u) + 1u;
  if (lane == 0) asm volatile("st.relaxed.gpu.global.u32 [%0], %1;" :: "l"(hm->gkey + blockIdx.x), "r"((t0 & ~511u) | me) : "memory");
  uint32_t k[5];
  #pragma unroll 1
  for (unsigned int spin = 0; spin < (1u << 20); spin++) {
    __nanosleep(200);
    #pragma unroll
    for (int m = 0; m < 5; m++) asm volatile("ld.relaxed.gpu.global.u32 %0, [%1];" : "=r"(k[m]) : "l"(hm->gkey + m * 32 + lane) : "memory");
    if (__all_sync(0xffffffffu, k[0] != 0u && k[1] != 0u && k[2] != 0u && k[3] != 0u && (k[4] != 0u || lane >= 4))) break;
  }
  uint32_t sz = 0u, g = 0u, rank = 0u, w[5];
  #pragma unroll
  for (int m = 0; m < 5; m++) w[m] = k[m] == 0u ? 0u : (k[m] & 511u) < me ? 257u : (k[m] & 511u) == me ? 65537u : 1u;
  #pragma unroll 1
  for (int i = 0; i < 16; i++) {
    const uint32_t v = __reduce_max_sync(0xffffffffu, max(max(max(k[0], k[1]), max(k[2], k[3])), k[4])), lo = (i == 15 || v < 2048u) ? 0u : v - 2048u;
    uint32_t n = 0u;
    #pragma unroll
    for (int m = 0; m < 5; m++) { const bool in = k[m] >= lo; n += in ? w[m] : 0u; w[m] = in ? 0u : w[m]; k[m] = in ? 0u : k[m]; }
    n = __reduce_add_sync(0xffffffffu, n);
    if (lane == i) sz = n & 255u;
    if (n >> 16) { g = i; rank = (n >> 8) & 255u; }
  }
  #pragma unroll 1
  for (int d = 0; d < 4; d += 2)
    if ((__reduce_max_sync(0xffffffffu, sz * 32u + lane) & 31u) == (uint32_t)lane) sz -= 2;
  const uint32_t gs = __shfl_sync(0xffffffffu, sz, g);
  const uint32_t off = __reduce_add_sync(0xffffffffu, (sz != 16u) * 32u + lane < (gs != 16u) * 32u + g ? sz : 0u);
  return rank < gs ? off + rank : 128u;
}

__device__ __forceinline__ int col_pos(int c) { return (c & ~31) + ((c >> 1) & 3) * 8 + ((c >> 3) & 3) * 2 + (c & 1); }
__device__ __forceinline__ int mod_col0(int j, int b) { return b < 0 ? (j & 1) * T_D + (b + 4) * 256 + ((j >> 1) ^ 2) * 64 : 2 * T_D + j * 512 + b * 64; }
__device__ __noinline__ void mod_rest(Scratch* hm, uint32_t t0, uint32_t sbase, uint32_t bar, int t2, int j, const bf16* __restrict__ cvec, const bf16* __restrict__ w_r) {
  const uint32_t scr = sbase + 4 * 32768 + 8192;
  const int kind = j >> 1;
  const uint2 c4 = *reinterpret_cast<const uint2*>(cvec + t2 * 4);
  sts_u32x2(scr + t2 * 8, silu2(c4.x), silu2(c4.y));
  const int w8 = t2 >> 5, t = t2 & 3, g = (t2 >> 2) & 7;
  float dot = 0.f;
  uint32_t buf = 0, par = 0;
  named_bar_sync(5, 256);
  #pragma unroll 1
  for (int b = -3; b < 8; b++) {
    float d[2][4] = {{0.f, 0.f, 0.f, 0.f}, {0.f, 0.f, 0.f, 0.f}};
    #pragma unroll 1
    for (int k = 0; k < 4; k++) {
      const uint32_t wa = sbase + (buf + (buf > 2 ? 2 : 0)) * 32768 + w8 * 4096 + t * 256;
      uint4 w[8];
      uint32_t sv[4];
      #pragma unroll
      for (int i = 0; i < 4; i++) sv[i] = lds_u32(scr + k * 512 + w8 * 64 + i * 16 + t * 4);
      mbar_wait(bar + buf * 8, par);
      #pragma unroll
      for (int i = 0; i < 8; i++) w[i] = lds_u32x4(wa + (i >> 1) * 1024 + (i & 1) * 128 + ((g ^ (t * 2 + (i & 1))) << 4));
      gemv64<8>(d, w, sv, t2 & 31);
      named_bar_sync(5, 256);
      if (t2 == 0) sts_u32(bar + 40, b * 4 + k + 18);
      if (++buf == 5) { buf = 0; par ^= 1; }
    }
    const int c0 = mod_col0(j, b);
    float v = gemv64_sum<8>(d, scr + 2048, t2);
    if (t2 < 64) {
      if (b < 0) st_tagged(hm->mod + c0 + t2, v);
      else {
        const int col = (c0 + t2) & 1023;
        uint8_t* dst = g_col + (col >> 7) * 1536;
        v = rbf(v);
        if (kind == 2) v = rbf(1.0f + v);
        const float vw = v * __bfloat162float(w_r[col]);
        dot += vw;
        if (kind == 2) {
          reinterpret_cast<bf16*>(dst)[col_pos(col & 127)] = __float2bfloat16_rn(vw);
          reinterpret_cast<bf16*>(dst)[128 + col_pos(col & 127)] = __float2bfloat16_rn(vw - rbf(vw));
        }
        reinterpret_cast<bf16*>(dst + 512 + (kind == 0 ? 0 : kind == 2 ? 256 : kind == 1 ? 512 : 768))[col_pos(col & 127)] = __float2bfloat16_rn(v);
      }
    }
  }
  #pragma unroll
  for (int o = 16; o > 0; o >>= 1) dot += __shfl_xor_sync(0xffffffffu, dot, o);
  if (t2 == 32) sts_f32(scr + 4096, dot);
  fence_proxy_async();
  named_bar_sync(5, 256);
  if (t2 == 0 && (kind == 1 || kind == 2)) g_scal[(kind == 2 ? 0 : 2) + (j & 1)] = dot + lds_f32(scr + 4096);
  sleep_until(t0, CLR_T);
  #pragma unroll 1
  for (int i = j * 256 + t2; i < (int)(sizeof(TailMail) / 16); i += 8 * 256) reinterpret_cast<uint4*>(&hm->mail)[i] = make_uint4(0u, 0u, 0u, 0u);
  named_bar_sync(5, 256);
  if (t2 == 0) red_release_add(&g_hcnt[0], 1u);
  sleep_until(t0, SGL_T);
}

constexpr int AT_NBLK = T_SEQ / 128;
constexpr float AT_HEAD = 7.0f;
#define WOL 12
constexpr int WO_LATE = WOL;
#define QSTG 3
constexpr int QP_STAG = QSTG;
constexpr int AT_SPLIT = 28, AT_PIN = 8, PINB = 4;
constexpr int AT_NFULL = 124;
constexpr int AT_PREG = 40, AT_CREG = 232;
constexpr uint32_t AT_SQ = 5 * 32768;
constexpr float AT_C = 0.08838834764831845f * 1.4426950408889634f;
constexpr float AT_RAW_LO = -16.0f, AT_RAW_HI = 24.0f;
constexpr float AT_RAW_SUM = 281474976710656.0f, AT_RAW_MIN = 9.094947017729282e-13f;
constexpr uint32_t AT_SBAR = AT_SQ + 65536 + 256;
constexpr uint32_t AT_SMEM = AT_SQ + 65536 + 3072;

__device__ __forceinline__ uint32_t ring_slot(uint32_t t) { return t - 5u * ((t * 205u) >> 10); }
__device__ __forceinline__ uint32_t qp_pos(uint32_t j, uint32_t it) { return 4u * it + (j & 3u) + ((j & 3u) == 3u ? it : 0u); }
__device__ __forceinline__ uint32_t ring_par(uint32_t t) { return ((t * 205u) >> 10) & 1u; }
__device__ __forceinline__ void softmax_rowmax(const float (&s)[64], float& mx0, float& mx1) {
  float a0 = fmaxf(s[0], s[1]), a1 = fmaxf(s[4], s[5]), a2 = fmaxf(s[8], s[9]), a3 = fmaxf(s[12], s[13]);
  float b0 = fmaxf(s[2], s[3]), b1 = fmaxf(s[6], s[7]), b2 = fmaxf(s[10], s[11]), b3 = fmaxf(s[14], s[15]);
  #pragma unroll
  for (int j = 4; j < 16; j += 4) {
    a0 = fmaxf(a0, fmaxf(s[4 * j + 0], s[4 * j + 1]));  b0 = fmaxf(b0, fmaxf(s[4 * j + 2], s[4 * j + 3]));
    a1 = fmaxf(a1, fmaxf(s[4 * j + 4], s[4 * j + 5]));  b1 = fmaxf(b1, fmaxf(s[4 * j + 6], s[4 * j + 7]));
    a2 = fmaxf(a2, fmaxf(s[4 * j + 8], s[4 * j + 9]));  b2 = fmaxf(b2, fmaxf(s[4 * j + 10], s[4 * j + 11]));
    a3 = fmaxf(a3, fmaxf(s[4 * j + 12], s[4 * j + 13])); b3 = fmaxf(b3, fmaxf(s[4 * j + 14], s[4 * j + 15]));
  }
  mx0 = fmaxf(fmaxf(a0, a1), fmaxf(a2, a3));
  mx1 = fmaxf(fmaxf(b0, b1), fmaxf(b2, b3));
  mx0 = fmaxf(mx0, __shfl_xor_sync(0xffffffffu, mx0, 1));
  mx1 = fmaxf(mx1, __shfl_xor_sync(0xffffffffu, mx1, 1));
  mx0 = fmaxf(mx0, __shfl_xor_sync(0xffffffffu, mx0, 2));
  mx1 = fmaxf(mx1, __shfl_xor_sync(0xffffffffu, mx1, 2));
}
__device__ __forceinline__ void softmax_sub(float (&s)[64], float mc0, float mc1) {
  #pragma unroll
  for (int j = 0; j < 16; j++) { s[4 * j] -= mc0; s[4 * j + 1] -= mc0; s[4 * j + 2] -= mc1; s[4 * j + 3] -= mc1; }
}
template <int LO, int HI>
__device__ __forceinline__ void softmax_exp(float (&s)[64]) {
  #pragma unroll
  for (int i = LO; i < HI; i++) s[i] = ex2_approx(s[i]);
}
__device__ __forceinline__ bool softmax_mode(const float (&s)[64], float& mc0, float& mc1) {
  softmax_rowmax(s, mc0, mc1);
  const bool raw = __all_sync(0xffffffffu, mc0 >= AT_RAW_LO && mc0 <= AT_RAW_HI && mc1 >= AT_RAW_LO && mc1 <= AT_RAW_HI);
  mc0 += AT_HEAD; mc1 += AT_HEAD;
  return raw;
}
__device__ __forceinline__ void rowsum_p(const uint32_t (&p)[32], uint32_t& t0, uint32_t& t1) {
  uint32_t a[16];
  #pragma unroll
  for (int i = 0; i < 8; i++) { a[2 * i] = badd2(p[4 * i], p[4 * i + 2]); a[2 * i + 1] = badd2(p[4 * i + 1], p[4 * i + 3]); }
  #pragma unroll
  for (int i = 0; i < 4; i++) { a[2 * i] = badd2(a[4 * i], a[4 * i + 2]); a[2 * i + 1] = badd2(a[4 * i + 1], a[4 * i + 3]); }
  t0 = badd2(badd2(a[0], a[2]), badd2(a[4], a[6]));
  t1 = badd2(badd2(a[1], a[3]), badd2(a[5], a[7]));
}
__device__ __forceinline__ void add_rowsum(const uint32_t (&p)[32], float& l0, float& l1) {
  uint32_t t0, t1;
  rowsum_p(p, t0, t1);
  l0 += bflo(t0) + bfhi(t0); l1 += bflo(t1) + bfhi(t1);
}
__device__ __forceinline__ void pack_p(uint32_t (&p)[32], const float (&s)[64]) {
  #pragma unroll
  for (int i = 0; i < 32; i++) p[i] = pack_bf16(s[2 * i], s[2 * i + 1]);
}
__device__ __noinline__ void attn_rows_exact(uint32_t sq, int warp, int lane, const bf16* __restrict__ kh, const bf16* __restrict__ vh) {
  #pragma unroll 1
  for (int r = 16 * warp; r < 16 * warp + 16; r++) {
    const uint32_t ad = (lane >> 4) * 16384 + r * 128 + ((((lane & 15) >> 1) ^ (r & 7)) << 4) + (lane & 1) * 8;
    uint2 qv; asm volatile("ld.shared.v2.u32 {%0, %1}, [%2];" : "=r"(qv.x), "=r"(qv.y) : "r"(sq + ad) : "memory");
    const float q0 = bflo(qv.x), q1 = bfhi(qv.x), q2 = bflo(qv.y), q3 = bfhi(qv.y);
    float m = -INFINITY, l = 0.f, o0 = 0.f, o1 = 0.f, o2 = 0.f, o3 = 0.f;
    #pragma unroll 1
    for (int key = 0; key < T_SEQ; key++) {
      const uint2 kv = *reinterpret_cast<const uint2*>(kh + (size_t)key * T_DH + lane * 4);
      const uint2 vv = *reinterpret_cast<const uint2*>(vh + (size_t)key * T_DH + lane * 4);
      float sc = (q0 * bflo(kv.x) + q1 * bfhi(kv.x)) + (q2 * bflo(kv.y) + q3 * bfhi(kv.y));
      #pragma unroll
      for (int o = 16; o > 0; o >>= 1) sc += __shfl_xor_sync(0xffffffffu, sc, o);
      const float mn = fmaxf(m, sc);
      const float al = (m == mn) ? 1.0f : ex2_approx(m - mn), p = rbf(ex2_approx(sc - mn));
      m = mn;
      l = fmaf(l, al, p);
      o0 = fmaf(o0, al, p * bflo(vv.x)); o1 = fmaf(o1, al, p * bfhi(vv.x));
      o2 = fmaf(o2, al, p * bflo(vv.y)); o3 = fmaf(o3, al, p * bfhi(vv.y));
    }
    const float inv = rcp_approx(l);
    asm volatile("st.shared.v2.u32 [%0], {%1, %2};" :: "r"(sq + ad), "r"(pack_bf16(o0 * inv, o1 * inv)), "r"(pack_bf16(o2 * inv, o3 * inv)) : "memory");
  }
}
__device__ __forceinline__ void issue_qk(float (&s)[64], const uint32_t (&q)[32], uint32_t k_lo) {
  wgmma_fence();
  wgmma_m64n128k16_rs<0>(s, q[0], q[1], q[2], q[3], k_lo, 0);
  wgmma_m64n128k16_rs<2>(s, q[4], q[5], q[6], q[7], k_lo, 1);
  wgmma_m64n128k16_rs<4>(s, q[8], q[9], q[10], q[11], k_lo, 1);
  wgmma_m64n128k16_rs<6>(s, q[12], q[13], q[14], q[15], k_lo, 1);
  wgmma_m64n128k16_rs<1024>(s, q[16], q[17], q[18], q[19], k_lo, 1);
  wgmma_m64n128k16_rs<1026>(s, q[20], q[21], q[22], q[23], k_lo, 1);
  wgmma_m64n128k16_rs<1028>(s, q[24], q[25], q[26], q[27], k_lo, 1);
  wgmma_m64n128k16_rs<1030>(s, q[28], q[29], q[30], q[31], k_lo, 1);
  wgmma_commit();
}
__device__ __forceinline__ void issue_pv(float (&o)[64], const uint32_t (&p)[32], uint32_t v_lo, int accumulate) {
  wgmma_fence();
  wgmma_m64n128k16_rs_tb<0>(o, p[0], p[1], p[2], p[3], v_lo, accumulate);
  wgmma_m64n128k16_rs_tb<128>(o, p[4], p[5], p[6], p[7], v_lo, 1);
  wgmma_m64n128k16_rs_tb<256>(o, p[8], p[9], p[10], p[11], v_lo, 1);
  wgmma_m64n128k16_rs_tb<384>(o, p[12], p[13], p[14], p[15], v_lo, 1);
  wgmma_m64n128k16_rs_tb<512>(o, p[16], p[17], p[18], p[19], v_lo, 1);
  wgmma_m64n128k16_rs_tb<640>(o, p[20], p[21], p[22], p[23], v_lo, 1);
  wgmma_m64n128k16_rs_tb<768>(o, p[24], p[25], p[26], p[27], v_lo, 1);
  wgmma_m64n128k16_rs_tb<896>(o, p[28], p[29], p[30], p[31], v_lo, 1);
  wgmma_commit();
}
__device__ __forceinline__ void rescale_o(float (&o)[64], float al0, float al1) {
  #pragma unroll
  for (int j = 0; j < 16; j++) { o[4 * j] *= al0; o[4 * j + 1] *= al0; o[4 * j + 2] *= al1; o[4 * j + 3] *= al1; }
}

__device__ __forceinline__ void stage_o(const float (&o)[64], float i0, float i1, uint32_t dst, int lane) {
  #pragma unroll
  for (int J = 0; J < 16; J += 2)
    stmatrix_x4(dst + (J >> 3) * 16384 + ((((J & 7) + (lane >> 4)) ^ (lane & 7)) << 4),
                pack_bf16(o[4 * J + 0] * i0, o[4 * J + 1] * i0), pack_bf16(o[4 * J + 2] * i1, o[4 * J + 3] * i1),
                pack_bf16(o[4 * J + 4] * i0, o[4 * J + 5] * i0), pack_bf16(o[4 * J + 6] * i1, o[4 * J + 7] * i1));
}
__device__ __forceinline__ bool finish_l(float& l0, float& l1) {
  l0 += __shfl_xor_sync(0xffffffffu, l0, 1); l1 += __shfl_xor_sync(0xffffffffu, l1, 1);
  l0 += __shfl_xor_sync(0xffffffffu, l0, 2); l1 += __shfl_xor_sync(0xffffffffu, l1, 2);
  const bool redo = __any_sync(0xffffffffu, !(l0 <= AT_RAW_SUM && l1 <= AT_RAW_SUM && l0 >= AT_RAW_MIN && l1 >= AT_RAW_MIN));
  const float r = rcp_approx(l0 * l1), i0 = r * l1;
  l1 = r * l0; l0 = i0;
  return redo;
}
__device__ __forceinline__ void stage_qregs(const uint32_t (&q)[32], uint32_t dst, int lane) {
  #pragma unroll
  for (int J = 0; J < 16; J += 2)
    stmatrix_x4(dst + (J >> 3) * 16384 + ((((J & 7) + (lane >> 4)) ^ (lane & 7)) << 4), q[2 * J], q[2 * J + 1], q[2 * J + 2], q[2 * J + 3]);
}
__device__ __forceinline__ void store_o(const CUtensorMap* tmO, uint32_t src, int head, int row) {
  tma_store_2d(tmO, src, head * T_DH, row);
  tma_store_2d(tmO, src + 16384, head * T_DH + 64, row);
  bulk_commit();
}
struct GemvSel { uint32_t lo0, hi0, lo1, hi1; };
__device__ __forceinline__ GemvSel gemv_sel(int lane) {
  const uint32_t lo = (lane & 8) ? 0x1044u : 0x4410u, hi = (lane & 8) ? 0x3244u : 0x4432u;
  GemvSel s; s.lo0 = (lane & 16) ? 0x4444u : lo; s.hi0 = (lane & 16) ? 0x4444u : hi; s.lo1 = (lane & 16) ? lo : 0x4444u; s.hi1 = (lane & 16) ? hi : 0x4444u;
  return s;
}
#define GEMV_B0(j, h, s) __byte_perm((j) < 2 ? (h).x : (h).y, 0u, ((j) & 1) ? (s).hi0 : (s).lo0)
#define GEMV_B1(j, h, s) __byte_perm((j) < 2 ? (h).x : (h).y, 0u, ((j) & 1) ? (s).hi1 : (s).lo1)
__device__ __forceinline__ float4 gemv_out(const float (&d)[4], int lane) {
  const bool tk = lane & 1;
  const float r0 = __shfl_xor_sync(0xffffffffu, tk ? d[0] : d[1], 1), r1 = __shfl_xor_sync(0xffffffffu, tk ? d[2] : d[3], 1);
  return tk ? make_float4(r0, d[1], r1, d[3]) : make_float4(d[0], r0, d[2], r1);
}
#define OG_NG 8
#define OG_GRP (64 / OG_NG)
constexpr int OG_ST = 5, OG_NKB = T_DQKV / 64, OG_MOE = T_F / 32;
constexpr int OG_POS = 7;
constexpr uint32_t OG_STAGE = 32768;
constexpr uint32_t OG_SWD = AT_SQ;
constexpr uint32_t OG_SCOL = AT_SBAR + 512;
constexpr uint32_t OG_SMISC = AT_SBAR + 2048;
constexpr uint32_t OG_XSLOT = ((OG_POS + OG_NKB) % OG_ST) * OG_STAGE;
constexpr uint32_t OG_OSLOT = ((OG_POS + OG_NKB + 1) % OG_ST) * OG_STAGE;
constexpr uint32_t OG_SH2 = ((OG_POS + OG_NKB + 2) % OG_ST) * OG_STAGE;
constexpr uint32_t OG_SRED = ((OG_POS + OG_NKB + 3) % OG_ST) * OG_STAGE;
constexpr uint32_t OG_SSTAT = OG_SRED + 16384;
constexpr uint32_t OG_SGU = OG_SRED + 8192;
constexpr uint32_t OG_SFIN = OG_SGU + 256;
#define OGM 2
#define OG_MT(b) ((((b) >> OGM) & 15) ^ (((b) & 64) ? 15 : 0))
#define OG_NT(b) (((b) & ((1 << OGM) - 1)) + (((b) >> (4 + OGM)) << OGM))
#define TAIL_SETUP \
  const uint32_t bar_full = sbase + AT_SBAR, bar_empty = bar_full + 40; \
  const uint32_t bar_wd = bar_full + 168, bar_col = bar_full + 176, bar_out = bar_full + 184, bar_end = bar_full + 192; \
  const uint32_t bar_key = bar_full + 200, bar_h2 = bar_full + 208, bar_sel = bar_full + 216; \
  const int mt = OG_MT(bx), nt = OG_NT(bx); \
  const int m0 = mt * 128, n0 = nt * 128; \
  const bool has_moe = (int)bx < OG_MOE; \
  (void)bar_empty; (void)bar_wd; (void)bar_col; (void)bar_out; (void)bar_end; (void)bar_key; (void)bar_h2; (void)bar_sel; (void)m0; (void)n0; (void)has_moe;

__device__ __forceinline__ void tail_producer(Scratch* hm, uint32_t bx, uint32_t sbase, uint32_t ph, uint32_t obpar, uint64_t pol, const CUtensorMap* tmA, const CUtensorMap* tmB,
                                              const CUtensorMap* tmX, const bf16* __restrict__ w_down) {
  TAIL_SETUP
  const uint32_t b_ob = bar_full + 96, b_acq = bar_full + 256;
  uint32_t stage = OG_ST, wdd = sbase + OG_SWD;
  int wdk = has_moe ? WD_0 : 99;
  const uint8_t* wdp = (const uint8_t*)w_down + (size_t)bx * 65536;
  if (has_moe) mbar_expect_tx(bar_wd, 65536);
  mbar_expect_tx(bar_col, 1536 + 16);
  #pragma unroll 1
  for (int kb = 0; kb <= OG_NKB; kb++) {
    const uint32_t fb = bar_full + (kb ? 8 * stage : 248), sa = sbase + stage * OG_STAGE, sb = sa + 16384;
    mbar_wait(bar_empty + 8 * stage, kb ? ph : obpar);
    mbar_expect_tx(fb, OG_STAGE);
    if (kb < OG_NKB) {
      tma_load_2d_hint(sb, tmB, n0, kb * 64, fb, pol);
      tma_load_2d_hint(sb + 8192, tmB, n0 + 64, kb * 64, fb, pol);
      if ((kb & 31) == 0) { mbar_wait(b_acq + (kb >> 2), 0); fence_proxy_async_global(); }
      tma_load_2d_hint(sa, tmA, kb * 64, m0, fb, pol);
    } else {
      tma_load_2d_hint(sa, tmX, n0, m0, fb, pol);
      tma_load_2d_hint(sb, tmX, n0 + 64, m0, fb, pol);
    }
    if (kb == 32) {
      bulk_load_hint(sbase + OG_SCOL, g_col + nt * 1536, 1536, bar_col, pol);
      bulk_load_hint(sbase + OG_SMISC, g_scal, 16, bar_col, pol);
    }
    if (kb == wdk && kb < WD_0 + 8 * WD_S) {
      if (kb == WD_0) mbar_wait(b_ob, obpar);
      bulk_load_hint(wdd, wdp, 8192, bar_wd, pol);
      wdp += 8192; wdd += 8224; wdk += WD_S;
    }
    if (++stage == OG_ST) { stage = 0; ph ^= 1; }
    if (kb == 0) stage = (OG_POS + 1) % OG_ST;
  }
}

__device__ __forceinline__ uint32_t out2(uint32_t x1, uint32_t mb2, uint32_t ih, uint32_t il, uint32_t c1, uint32_t sb, uint32_t gb) {
  const uint32_t d = bsub2(x1, mb2);
  return bfma2(gb, bfma2(bfma2(d, ih, bmul2(d, il)), c1, sb), x1);
}
__device__ __forceinline__ void tail_exchange(Scratch* hm, uint32_t bx, uint32_t sbase, int wid, uint32_t tx, const CUtensorMap* tmOut, bf16* __restrict__ out) {
    TAIL_SETUP
    named_bar_sync(10, 128);
    mbar_wait(bar_end, 0);
    const int lane = tx & 31;
    TL_MARK2(22, lane == 0);
    if (tx == 96) PF(5);
    if (wid == 0) {
      uint32_t k1 = 0u, k2 = 0u;
      mbar_wait(bar_key, 0);
      #pragma unroll 1
      for (unsigned int spin = 0; spin < (1u << 22); spin++) {
        if (k1 == 0u) asm volatile("ld.relaxed.gpu.global.u32 %0, [%1];" : "=r"(k1) : "l"(g_key + (lane >> 1) * 32 + (lane & 1)) : "memory");
        if (__all_sync(0xffffffffu, k1 != 0u)) break;
      }
      TS(6, lane == 0);
      warp_top2(k1, k2);
      if (lane == 0) {
        const uint32_t r1 = 0xffffu - (k1 & 0xffffu), r2 = 0xffffu - (k2 & 0xffffu);
        sts_u32x4(sbase + OG_SMISC + 64, k1, k2, (r1 >> 7) * 2, (r2 >> 7) * 2 + ((r1 >> 7) == (r2 >> 7)));
        sts_u32(sbase + OG_SMISC + 80, clock_lo());
        mbar_arrive(bar_sel);
      }
    } else if (wid < 3) {
      const uint32_t ch = lane & 15, ca = sbase + OG_SCOL + 768 + (ch >> 2) * 64 + (ch & 3) * 4;
      const uint4 c1 = make_uint4(lds_u32(ca), lds_u32(ca + 16), lds_u32(ca + 32), lds_u32(ca + 48)), sh = make_uint4(lds_u32(ca + 256), lds_u32(ca + 272), lds_u32(ca + 288), lds_u32(ca + 304));
      float* dst = wid == 1 ? reinterpret_cast<float*>(g_key + mt * 32) : reinterpret_cast<float*>(g_cand + (mt * 2 + (lane >> 4)) * 256 + nt * 16 + ch);
      mbar_wait(bar_key, 0);
      const uint4 kk = lds_u32x4(sbase + OG_SSTAT + 1024 + lane * 16);
      uint32_t k1 = max(kk.x, kk.y), k2 = min(kk.x, kk.y);
      k2 = max(max(k2, min(kk.z, kk.w)), min(k1, max(kk.z, kk.w))); k1 = max(k1, max(kk.z, kk.w));
      warp_top2(k1, k2);
      if (wid == 1) {
        if (lane == 0 && nt == (mt & 7)) st_relaxed2(dst, k1, k2);
        TS(4, lane == 0);
      } else {
        const uint32_t r = (~((lane & 16) ? k2 : k1)) & 127u;
        const uint2 st = lds_u32x2(sbase + OG_SSTAT + r * 8);
        const uint4 xc = lds_u32x4(sbase + OG_XSLOT + (ch >> 3) * 16384 + r * 128 + (((ch ^ r) & 7) << 4));
        const float inr = __uint_as_float(st.y);
        const float h0 = __uint_as_float(ln_mod2(xc.x, st.x, inr, c1.x, sh.x)), h1 = __uint_as_float(ln_mod2(xc.y, st.x, inr, c1.y, sh.y));
        const float h2 = __uint_as_float(ln_mod2(xc.z, st.x, inr, c1.z, sh.z)), h3 = __uint_as_float(ln_mod2(xc.w, st.x, inr, c1.w, sh.w));
        st_tagged4(dst + 512, h0, h1, h2, h3);
        st_tagged4(dst, __uint_as_float(xc.x), __uint_as_float(xc.y), __uint_as_float(xc.z), __uint_as_float(xc.w));
      }
    }
    mbar_wait(bar_sel, 0);
    mbar_wait(bar_out, 0);
    {
      const int sel0 = 0xffff - (lds_u32(sbase + OG_SMISC + 64) & 0xffffu), sel1 = 0xffff - (lds_u32(sbase + OG_SMISC + 68) & 0xffffu);
      if ((sel0 >> 7) == mt || (sel1 >> 7) == mt) {
        #pragma unroll 2
        for (int i = 0; i < 16; i++) {
          const int r = i * 8 + (tx >> 4), ch = tx & 15;
          if (m0 + r != sel0 && m0 + r != sel1)
            *reinterpret_cast<uint4*>(out + (size_t)(m0 + r) * T_D + n0 + ch * 8) =
                lds_u32x4(sbase + OG_OSLOT + (ch >> 3) * 16384 + r * 128 + (((ch & 7) ^ (r & 7)) << 4));
        }
      } else if (tx == 96) {
        tma_store_2d(tmOut, sbase + OG_OSLOT, n0, m0);
        tma_store_2d(tmOut, sbase + OG_OSLOT + 16384, n0 + 64, m0);
        bulk_commit();
      }
      __syncwarp();
    }
    {
      const int tk = bx >> 6, c0 = (bx & 63) * 16;
      const uint32_t gb2 = *reinterpret_cast<const uint32_t*>(g_col + (c0 >> 7) * 1536 + 512 + 768 + col_pos((c0 & 127) + (tx & 14)) * 2);
      const float* src = g_ypart + (size_t)((tx >> 2) * 2 + tk) * T_D + c0 + (tx & 3) * 4;
      const bool four = tx < (OG_MOE - 96) * 4;
      mbar_wait(bar_h2, 0);
      const uint32_t ts = lds_u32(sbase + OG_SMISC + 80);
      float fx = 0.f, fh = 0.f, rs = 0.f;
      bf16* op = out;
      if (wid == 1) {
        const uint32_t key = lds_u32(sbase + OG_SMISC + 64 + tk * 4);
        const uint32_t* xp = reinterpret_cast<const uint32_t*>(g_cand + lds_u32(sbase + OG_SMISC + 72 + tk * 4) * 256) + ((c0 + (tx & 14)) >> 1);
        uint32_t x2 = 0u;
        #pragma unroll 1
        for (unsigned int spin = 0; spin < (1u << 20); spin++) { asm volatile("ld.relaxed.gpu.global.u32 %0, [%1];" : "=r"(x2) : "l"(xp) : "memory"); if (__all_sync(0xffffffffu, x2 != 0u)) break; }
        const uint32_t h2p = lds_u32(sbase + OG_SH2 + tk * 2048 + (c0 + (tx & 14)) * 2);
        fx = (lane & 1) ? bfhi(x2) : bflo(x2); fh = (lane & 1) ? bfhi(h2p) : bflo(h2p);
        rs = rbf(sigmoid_f(bfhi((key & 0x80000000u) ? key ^ 0x80000000u : ~key)));
        op += (size_t)(0xffffu - (key & 0xffffu)) * T_D + c0 + (lane & 15);
      }
      if (bx == 0 && tx < 68) g_hcnt[32 * (tx >> 2) + (tx & 3)] = 0u;
      if (tx < 64) hm->modu[bx * 64 + tx] = 0.f;
      else if (tx < 96) hm->stat[bx * 32 + tx - 64] = make_float2(0.f, 0.f);
      else if (tx < 112) hm->mod[bx * 16 + tx - 96] = 0.f;
      else if (tx < 114 && bx < 66) hm->gkey[bx * 2 + tx - 112] = 0u;
      if (YD) wait_clock(ts, YD);
      else { if (tx == 0) hint_wait(CNT_Y, (uint32_t)OG_MOE); named_bar_sync(10, 128); }
      TS(11, lane == 0);
      float4 p0, p1, p2, p3;
      #pragma unroll 1
      for (unsigned int spin = 0; spin < (1u << 20); spin++) {
        p0 = ld_tagged4(src); p1 = ld_tagged4(src + 64 * T_D); p2 = ld_tagged4(src + 128 * T_D); p3 = ld_tagged4(four ? src + 192 * T_D : src);
        if (__all_sync(0xffffffffu, tagged4(p0) & tagged4(p1) & tagged4(p2) & tagged4(p3))) break;
      }
      if (four) { p2.x += p3.x; p2.y += p3.y; p2.z += p3.z; p2.w += p3.w; }
      p0.x = (p0.x + p1.x) + p2.x; p0.y = (p0.y + p1.y) + p2.y; p0.z = (p0.z + p1.z) + p2.z; p0.w = (p0.w + p1.w) + p2.w;
      #pragma unroll
      for (int o = 4; o <= 16; o <<= 1) {
        p0.x += __shfl_xor_sync(0xffffffffu, p0.x, o); p0.y += __shfl_xor_sync(0xffffffffu, p0.y, o);
        p0.z += __shfl_xor_sync(0xffffffffu, p0.z, o); p0.w += __shfl_xor_sync(0xffffffffu, p0.w, o);
      }
      if (lane < 4) sts_f32x4(sbase + OG_SFIN + (tx >> 5) * 64 + lane * 16, p0.x, p0.y, p0.z, p0.w);
      named_bar_sync(10, 128);
      TS(12, lane == 0);
      if (wid == 1 && lane < 16) {
        const uint32_t ya = sbase + OG_SFIN + lane * 4;
        const float y = rbf(rbf((lds_f32(ya) + lds_f32(ya + 64)) + (lds_f32(ya + 128) + lds_f32(ya + 192))) * rs);
        *op = __float2bfloat16_rn(fx + rbf(((lane & 1) ? bfhi(gb2) : bflo(gb2)) * rbf(fh + y)));
      }
      if (tx == 96) bulk_wait_read<0>();
    }
    TL_END(4, tx == 0);
    PS(6, tx == 32);
    TS(13, tx == 32);
}

__device__ __forceinline__ void tail_consumer(Scratch* hm, uint32_t bx, uint32_t sbase, int tid, int w8, const bf16* __restrict__ w_gate, const bf16* __restrict__ w_up) {
    TAIL_SETUP
    const int warp = w8 & 3, lane = tid & 31, cwg = w8 >> 2, t2 = cwg * 128 + tid;
    const uint32_t dbase = (sbase & 0x3FFFFu) >> 4;
    const uint32_t a_base = dbase + ((cwg * 8192) >> 4) + (1u << 16);
    const uint32_t b_base = dbase + (16384 >> 4) + (512u << 16);
    TL_MARK2(25, threadIdx.x == 128);
    const uint64_t pol = policy_evict_first();
    const bf16* pw = ((lane & 16) ? w_up : w_gate) + (size_t)(w8 * 128 + (lane & 3) * 4) * T_F + (has_moe ? bx : 0) * 32 + ((lane >> 2) & 3) * 8;
    uint4 wv[32];
    float acc[64];
    {
      uint32_t stage = (OG_POS + 1) % OG_ST, phase = ((OG_POS + 1) / OG_ST) & 1, prev = 12;
      #pragma unroll
      for (int i = 0; i < 64; i++) acc[i] = 0.f;
      mbar_wait(bar_full + 248, 0);
      wgmma_fence();
      wgmma_m64n128k16_ss_tb<0 + 5 * 2048, 0 + 5 * 2048>(acc, a_base, b_base, 0);
      wgmma_m64n128k16_ss_tb<2 + 5 * 2048, 128 + 5 * 2048>(acc, a_base, b_base, 1);
      wgmma_m64n128k16_ss_tb<4 + 5 * 2048, 256 + 5 * 2048>(acc, a_base, b_base, 1);
      wgmma_m64n128k16_ss_tb<6 + 5 * 2048, 384 + 5 * 2048>(acc, a_base, b_base, 1);
      wgmma_commit();
      #pragma unroll
      for (int g = OG_PRE ? -1 : 0; g < OG_NG; g++) {
        #pragma unroll
        for (int j = 0; j < 4; j++) if (g >= 0) wv[4 * g + j] = ldg_stream_v4(pw + (size_t)(16 * g + j) * T_F, pol);
        #pragma unroll 1
        for (int kb = g < 0 ? 1 : OG_PRE + g * OG_LEN; kb < (g == OG_NG - 1 ? OG_NKB : OG_PRE + (g + 1) * OG_LEN); kb++) {
          mbar_wait(bar_full + 8 * stage, phase);
          const uint32_t a_lo = a_base + stage * (OG_STAGE >> 4), b_lo = b_base + stage * (OG_STAGE >> 4);
          wgmma_fence();
          wgmma_m64n128k16_ss_tb<0, 0>(acc, a_lo, b_lo, 1);
          wgmma_m64n128k16_ss_tb<2, 128>(acc, a_lo, b_lo, 1);
          wgmma_m64n128k16_ss_tb<4, 256>(acc, a_lo, b_lo, 1);
          wgmma_m64n128k16_ss_tb<6, 384>(acc, a_lo, b_lo, 1);
          wgmma_commit();
          wgmma_wait<1>();
          if (tid == 0) mbar_arrive(bar_empty + 8 * prev);
          prev = stage;
          if (++stage == OG_ST) { stage = 0; phase ^= 1; }
        }
      }
    }
    const uint32_t frag = (64 * cwg + 16 * warp + (lane & 15)) * 128 + (((lane >> 4) ^ (lane & 7)) << 4);
    const uint32_t tcol = sbase + OG_SCOL + (lane & 3) * 16, g = lane >> 2;
    float* sdst = reinterpret_cast<float*>(g_part1 + ((mt * 8 + w8) * 8 + nt) * 16 + g + (lane & 1) * 8);
    uint32_t xr[32];
    uint4 ga[4], cw[4];
    auto ld_quarter = [&](int q, uint32_t dep) {
      #pragma unroll
      for (int i = 2 * q; i < 2 * q + 2; i++) ldmatrix_x4(sbase + OG_XSLOT + (i >> 2) * 16384 + (frag ^ ((i & 3) * 32)) + dep, xr[4 * i], xr[4 * i + 1], xr[4 * i + 2], xr[4 * i + 3]);
      ga[q] = lds_u32x4(tcol + 512 + q * 64 + dep);
      cw[q] = lds_u32x4((g ? tcol + (lane & 8) * 32 + q * 64 : sbase + OG_SMISC + 32) + dep);
    };
    mbar_wait(bar_col, 0);
    mbar_wait(bar_full + 8 * ((OG_POS + OG_NKB) % OG_ST), ((OG_POS + OG_NKB) / OG_ST) & 1);
    ld_quarter(0, 0);
    wgmma_wait<0>();
    fence_regs(acc);
    if (tid == 0) mbar_arrive(bar_end);
    TL_MARK2(9, lane == 0);
    TS(0, lane == 0);
    PS(5, threadIdx.x == 256);
    {
      float dl[4] = {0.f, 0.f, 0.f, 0.f}, da[4] = {0.f, 0.f, 0.f, 0.f}, db[4] = {0.f, 0.f, 0.f, 0.f};
      #pragma unroll
      for (int q = 0; q < 4; q++) {
        uint32_t pk[8];
        #pragma unroll
        for (int i = 0; i < 8; i++) pk[i] = pack_bf16(acc[16 * q + 2 * i], acc[16 * q + 2 * i + 1]);
        if (q < 3) ld_quarter(q + 1, 0u);
        #pragma unroll
        for (int i = 2 * q; i < 2 * q + 2; i++) {
          #pragma unroll
          for (int k = 0; k < 4; k++) xr[4 * i + k] = badd2(xr[4 * i + k], bmul2((i & 1) ? (k < 2 ? ga[q].z : ga[q].w) : (k < 2 ? ga[q].x : ga[q].y), pk[4 * (i & 1) + k]));
          mma_bf16(dl, xr[4 * i], xr[4 * i + 1], xr[4 * i + 2], xr[4 * i + 3], (i & 1) ? cw[q].z : cw[q].x, (i & 1) ? cw[q].w : cw[q].y);
          mma_bf16(da, xr[4 * i], xr[4 * i + 1], xr[4 * i + 2], xr[4 * i + 3], xr[4 * i], xr[4 * i + 2]);
          mma_bf16(db, xr[4 * i], xr[4 * i + 1], xr[4 * i + 2], xr[4 * i + 3], xr[4 * i + 1], xr[4 * i + 3]);
        }
      }
      {
        const int dsrc = (lane & ~3) + (g >> 1);
        const float qa = __shfl_sync(0xffffffffu, (g & 1) ? da[1] : da[0], dsrc), qb = __shfl_sync(0xffffffffu, (g & 1) ? db[3] : db[2], dsrc);
        const float e0 = __shfl_xor_sync(0xffffffffu, (lane & 1) ? dl[0] : dl[2], 1), e1 = __shfl_xor_sync(0xffffffffu, dl[3], 1);
        const bool hi = lane & 1;
        if ((lane & 3) < 2) st_tagged4(sdst, hi ? e0 : dl[0], hi ? qb : qa, hi ? e1 + dl[2] : dl[1] + e0, 1.0f);
      }
    }
    TL_MARK2(10, lane == 0);
    TS(1, lane == 0);
    uint4 tc[4], ts[4], tg[4];
    #pragma unroll
    for (int i = 0; i < 8; i++) stmatrix_x4(sbase + OG_XSLOT + (i >> 2) * 16384 + (frag ^ ((i & 3) * 32)), xr[4 * i], xr[4 * i + 1], xr[4 * i + 2], xr[4 * i + 3]);
    #pragma unroll
    for (int i = 0; i < 8; i++) ldmatrix_x4(sbase + OG_XSLOT + (i >> 2) * 16384 + (frag ^ ((i & 3) * 32)), xr[4 * i], xr[4 * i + 1], xr[4 * i + 2], xr[4 * i + 3]);
    #pragma unroll
    for (int i = 0; i < 2; i++) { tc[i] = lds_u32x4(tcol + 768 + i * 64); ts[i] = lds_u32x4(tcol + 1024 + i * 64); tg[i] = lds_u32x4(tcol + 1280 + i * 64); }
    {
      const float* src = reinterpret_cast<const float*>(g_part1 + ((mt * 8 + w8) * 8 + (lane & 1) * 4) * 16 + (lane >> 1));
      float4 v, v1, v2, v3;
      #pragma unroll 1
      for (unsigned int spin = 0; spin < (1u << 22); spin++) {
        v = ld_tagged4(src); v1 = ld_tagged4(src + 64); v2 = ld_tagged4(src + 128); v3 = ld_tagged4(src + 192);
        if (__all_sync(0xffffffffu, tagged4(v) & tagged4(v1) & tagged4(v2) & tagged4(v3))) break;
        __nanosleep(100);
      }
      TL_MARK2(26, lane == 0);
    TS(2, lane == 0);
      v.x = (v.x + v1.x) + (v2.x + v3.x); v.y = (v.y + v1.y) + (v2.y + v3.y); v.z = (v.z + v1.z) + (v2.z + v3.z);
      v.x += __shfl_xor_sync(0xffffffffu, v.x, 1); v.y += __shfl_xor_sync(0xffffffffu, v.y, 1); v.z += __shfl_xor_sync(0xffffffffu, v.z, 1);
      const float mean = v.x * (1.0f / T_D);
      const float var = fmaxf(fmaf(-mean, mean, v.y * (1.0f / T_D)), 0.f);
      const uint32_t mb2 = pack_bf16(mean, mean);
      const float inv = rcp_approx(rbf(sqrt_approx(rbf(rbf(var) + 1e-05f))));
      {
        const uint4 sc = lds_u32x4(sbase + OG_SMISC);
        const uint32_t key = rank_key(rbf(fmaf(fmaf(-bflo(mb2), __uint_as_float(sc.x) + __uint_as_float(sc.y), v.z), inv, __uint_as_float(sc.z) + __uint_as_float(sc.w))), m0 + 16 * w8 + (lane >> 1));
        mbar_wait(bar_end, 0);
        if (lane & 1) sts_u32(sbase + OG_SSTAT + 1024 + (16 * w8 + (lane >> 1)) * 4, key);
        else sts_u32x2(sbase + OG_SSTAT + (16 * w8 + (lane >> 1)) * 8, mb2, __float_as_uint(inv));
        __syncwarp();
        TS(3, lane == 0);
        if (lane == 0) mbar_arrive(bar_key);
      }
      const uint32_t ih = pack_bf16(inv, inv), il = pack_bf16(inv - bflo(ih), inv - bflo(ih));
      const uint32_t mba = __shfl_sync(0xffffffffu, mb2, 2 * (lane >> 2)), mbb = __shfl_sync(0xffffffffu, mb2, 2 * (lane >> 2) + 16);
      const uint32_t iha = __shfl_sync(0xffffffffu, ih, 2 * (lane >> 2)), ihb = __shfl_sync(0xffffffffu, ih, 2 * (lane >> 2) + 16);
      const uint32_t ila = __shfl_sync(0xffffffffu, il, 2 * (lane >> 2)), ilb = __shfl_sync(0xffffffffu, il, 2 * (lane >> 2) + 16);
      #pragma unroll
      for (int i = 2; i < 4; i++) { tc[i] = lds_u32x4(tcol + 768 + i * 64); ts[i] = lds_u32x4(tcol + 1024 + i * 64); tg[i] = lds_u32x4(tcol + 1280 + i * 64); }
      #pragma unroll
      for (int i = 0; i < 8; i++) {
        const uint4 &c = tc[i >> 1], &s = ts[i >> 1], &b = tg[i >> 1];
        const bool u = i & 1;
        stmatrix_x4(sbase + OG_OSLOT + (i >> 2) * 16384 + (frag ^ ((i & 3) * 32)),
                    out2(xr[4 * i], mba, iha, ila, u ? c.z : c.x, u ? s.z : s.x, u ? b.z : b.x), out2(xr[4 * i + 1], mbb, ihb, ilb, u ? c.z : c.x, u ? s.z : s.x, u ? b.z : b.x),
                    out2(xr[4 * i + 2], mba, iha, ila, u ? c.w : c.y, u ? s.w : s.y, u ? b.w : b.y), out2(xr[4 * i + 3], mbb, ihb, ilb, u ? c.w : c.y, u ? s.w : s.y, u ? b.w : b.y));
      }
      fence_proxy_async();
      __syncwarp();
      if (lane == 0) mbar_arrive(bar_out);
      TL_MARK2(24, lane == 0);
    TS(5, lane == 0);
    }
    uint4 wd[16];
    {
      mbar_wait(bar_sel, 0);
      TL_MARK2(12, lane == 0);
    TS(7, lane == 0);
      const float* src = reinterpret_cast<const float*>(g_cand + lds_u32(sbase + OG_SMISC + 72 + cwg * 4) * 256 + 128 + tid);
      float4 hf = ld_tagged4(src);
      if (has_moe) mbar_wait(bar_wd, 0);
      #pragma unroll
      for (int i = 0; i < 16; i++) wd[i] = lds_u32x4(sbase + OG_SWD + (((i >> 2) & 1) * 4 + (lane & 3)) * 8224 + (i & 3) * 2048 + w8 * 256 + (i >> 3) * 128 + (lane >> 2) * 16);
      #pragma unroll 1
      for (unsigned int spin = 0; spin < (1u << 20) && !__all_sync(0xffffffffu, tagged4(hf)); spin++) hf = ld_tagged4(src);
      const uint4 hv = make_uint4(__float_as_uint(hf.x), __float_as_uint(hf.y), __float_as_uint(hf.z), __float_as_uint(hf.w));
      sts_u32x4(sbase + OG_SH2 + t2 * 16, hv.x, hv.y, hv.z, hv.w);
    }
    named_bar_sync(9, 256);
    if (t2 == 0) mbar_arrive(bar_h2);
    TL_MARK2(13, lane == 0);
    TS(8, lane == 0);
    if (has_moe) {
      const GemvSel sel = gemv_sel(lane);
      {
        float d[4][4];
        #pragma unroll
        for (int c = 0; c < 4; c++) { d[c][0] = 0.f; d[c][1] = 0.f; d[c][2] = 0.f; d[c][3] = 0.f; }
        #pragma unroll
        for (int st = 0; st < 8; st++) {
          const uint2 hb = lds_u32x2(sbase + OG_SH2 + ((lane >> 2) & 1) * 2048 + (w8 * 128 + st * 16 + (lane & 3) * 4) * 2);
          #pragma unroll
          for (int j = 0; j < 4; j++) mma_bf16(d[j], wv[4 * st + j].x, wv[4 * st + j].y, wv[4 * st + j].z, wv[4 * st + j].w, GEMV_B0(j, hb, sel), GEMV_B1(j, hb, sel));
        }
        #pragma unroll
        for (int e = 0; e < 4; e++) d[0][e] = (d[0][e] + d[1][e]) + (d[2][e] + d[3][e]);
        const float4 r = gemv_out(d[0], lane);
        sts_f32x4(sbase + OG_SRED + w8 * 512 + (((lane >> 4) * 2 + (lane & 1)) * 32 + ((lane >> 2) & 3) * 8 + (lane & 2) * 2) * 4, r.x, r.y, r.z, r.w);
      }
      named_bar_sync(9, 256);
      if (t2 < 64) {
        float gp[8], up[8];
        #pragma unroll
        for (int w = 0; w < 8; w++) { gp[w] = lds_f32(sbase + OG_SRED + w * 512 + t2 * 4); up[w] = lds_f32(sbase + OG_SRED + w * 512 + 256 + t2 * 4); }
        const float gs = ((gp[0] + gp[1]) + (gp[2] + gp[3])) + ((gp[4] + gp[5]) + (gp[6] + gp[7]));
        const float us = ((up[0] + up[1]) + (up[2] + up[3])) + ((up[4] + up[5]) + (up[6] + up[7]));
        asm volatile("st.shared.u16 [%0], %1;" :: "r"(sbase + OG_SGU + t2 * 2), "h"((uint16_t)pack_bf16(silu_bf(rbf(gs)) * rbf(us), 0.f)) : "memory");
      }
      named_bar_sync(9, 256);
      TS(9, lane == 0);
      float d[4][4];
      #pragma unroll
      for (int c = 0; c < 4; c++) { d[c][0] = 0.f; d[c][1] = 0.f; d[c][2] = 0.f; d[c][3] = 0.f; }
      #pragma unroll
      for (int st = 0; st < 2; st++) {
        const uint2 g = lds_u32x2(sbase + OG_SGU + ((lane >> 2) & 1) * 64 + st * 32 + (lane & 3) * 8);
        #pragma unroll
        for (int j = 0; j < 4; j++) {
          const uint32_t b0 = GEMV_B0(j, g, sel), b1 = GEMV_B1(j, g, sel);
          mma_bf16(d[j & 1], wd[4 * st + j].x, wd[4 * st + j].y, wd[4 * st + j].z, wd[4 * st + j].w, b0, b1);
          mma_bf16(d[2 + (j & 1)], wd[8 + 4 * st + j].x, wd[8 + 4 * st + j].y, wd[8 + 4 * st + j].z, wd[8 + 4 * st + j].w, b0, b1);
        }
      }
      #pragma unroll
      for (int e = 0; e < 4; e++) { d[0][e] += d[1][e]; d[2][e] += d[3][e]; }
      const float4 y0 = gemv_out(d[0], lane), y1 = gemv_out(d[2], lane);
      float* yp = g_ypart + (size_t)(bx * 2 + (lane & 1)) * T_D + w8 * 128 + (lane >> 2) * 8 + (lane & 2) * 2;
      st_tagged4(yp, y0.x, y0.y, y0.z, y0.w);
      st_tagged4(yp + 64, y1.x, y1.y, y1.z, y1.w);
      if (!YD) { named_bar_sync(9, 256); if (t2 == 0) hint_arrive(CNT_Y); }
    }
    TS(10, lane == 0);
    TL_CLK(4, 1, threadIdx.x == 128);
}

__device__ __forceinline__ void store_warp(Scratch* hm, uint32_t sbase, const CUtensorMap* tmO, int item0, int n_items) {
  if (elect_one()) {
    const uint32_t bars = sbase + AT_SBAR, b_q0 = bars + 80, b_ob = bars + 96, b_ordy = bars + 104, b_acq = bars + 256;
    mbar_wait(bars + 232, 0);
    const uint32_t bx = lds_u32(bars + 240);
    const unsigned int* cnt = &g_hcnt[32 * (1 + OG_MT(bx)) + 2];
    #pragma unroll 1
    for (int q = 0; q < 4 * n_items; q++) {
      const int item = item0 + (q >> 2) * 128, h = (q >> 1) & 1, w = q & 1;
      const bool last = (q >> 2) == n_items - 1;
      mbar_wait(b_ordy + 8 * (q & 3), q >> 2);
      if (q == 4 && item < 192) spin_until(&g_hcnt[32 * (1 + (item & 15)) + 1], (item & 15) < 12 ? 8u : 7u);
      store_o(tmO, (h ? (last ? sbase + AT_SQ + 32768 : sbase + 2 * 32768) : sbase + AT_SQ) + w * 8192, (item >> 4) * 2 + h, (item & 15) * 128 + w * 64);
      if (w) {
        PF(1 + (q >> 1));
        bulk_wait_read<0>();
        mbar_arrive(h ? b_ob : b_q0);
        bulk_wait<0>();
        fence_proxy_async_global();
        red_release_add(&g_hcnt[32 * (1 + (item & 15)) + 2 + (item >> 7)], 1u);
        if (bx < 128 && q == (n_items == 2 ? 5 : 3)) { spin_until(cnt, 16u); mbar_arrive(b_acq); }
      }
    }
    if (bx < 128) { spin_until(&g_hcnt[0], 8u); spin_until(cnt + 1, 16u); mbar_arrive(b_acq + 8); }
  }
}

#define TUNE_PARAM
__device__ __forceinline__ int h_first(int item, int c) { const int j = (item >> 4) + 3 * c; return j >= 7 ? j - 7 : j; }
__global__ void __launch_bounds__(384, 1)
fused_kernel(const bf16* __restrict__ x, const bf16* __restrict__ cvec, const bf16* __restrict__ w_mod, Scratch* hm, uint32_t zero, TUNE_PARAM
            const uint8_t* __restrict__ pf_wo, const bf16* __restrict__ kc, const bf16* __restrict__ vc, const bf16* __restrict__ w_r,
            const bf16* __restrict__ w_gate, const bf16* __restrict__ w_up, const bf16* __restrict__ w_down, bf16* __restrict__ out,
            const __grid_constant__ CUtensorMap tmM, const __grid_constant__ CUtensorMap tmW, const __grid_constant__ CUtensorMap tmK,
            const __grid_constant__ CUtensorMap tmV, const __grid_constant__ CUtensorMap tmO, const __grid_constant__ CUtensorMap tmOl, const __grid_constant__ CUtensorMap tmWo,
            const __grid_constant__ CUtensorMap tmX, const __grid_constant__ CUtensorMap tmOut)
{
  extern __shared__ __align__(1024) uint8_t smem_raw[];
  const uint32_t sbase = smem_u32(smem_raw);
  const uint32_t bars = sbase + AT_SBAR;
  const uint32_t b_full = bars, b_empty = bars + 40;
  const uint32_t b_q0 = bars + 80, b_q1 = bars + 88;
  const uint32_t b_ob = bars + 96;
  const uint32_t b_ordy = bars + 104;
  const uint32_t b_pin = bars + 136;
  const uint32_t b_a0 = bars + 144;
  const uint32_t b_x = bars + 160;
  const uint32_t b_w = bars + 152, b_go = bars + 224;
  const uint32_t b_bx = bars + 232, s_bx = bars + 240;
  const uint32_t b_hs = bars + 464;
  const uint32_t b_tab = bars + 272;
  const int wid = __shfl_sync(0xffffffffu, threadIdx.x >> 5, 0), wg = wid >> 2;
  const bool single = blockIdx.x >= AT_NFULL;
  const int item0 = __shfl_sync(0xffffffffu, blockIdx.x < 128 ? (int)blockIdx.x : (int)blockIdx.x + 124, 0), n_items = __shfl_sync(0xffffffffu, single ? 1 : 2, 0);
  const uint32_t t0 = clock_lo();
  TL_START(3);
  HS(0);
  if (threadIdx.x == 0) {
    if (sbase & 1023u) __trap();
    for (int i = 0; i < 5; i++) { mbar_init(b_full + 8 * i, 1); mbar_init(b_empty + 8 * i, 2); mbar_init(b_hs + 8 * i, i < 2 && !single ? 4 : 1); }
    sts_u32(bars + 504, 5u);
    mbar_init(b_q0, 1); mbar_init(b_q1, 8); mbar_init(b_ob, 1);
    for (int i = 0; i < 4; i++) mbar_init(b_ordy + 8 * i, 4);
    mbar_init(b_pin, 1); mbar_init(b_a0, 8); mbar_init(b_x, 1); mbar_init(b_w, 1); mbar_init(b_go, 1); mbar_init(b_bx, 1);
    for (int i = 0; i < 8; i++) mbar_init(b_tab + 8 * i, i < 2 ? 1 : 2);
    mbar_init(bars + 168, 1); mbar_init(bars + 176, 1); mbar_init(bars + 184, 8); mbar_init(bars + 192, 2);
    mbar_init(bars + 200, 8); mbar_init(bars + 208, 1); mbar_init(bars + 216, 1); mbar_init(bars + 248, 1); mbar_init(bars + 256, 1); mbar_init(bars + 264, 1);
    sts_u32x4(sbase + OG_SMISC + 32, 0x3F803F80u, 0x3F803F80u, 0x3F803F80u, 0x3F803F80u);
    fence_mbar_init();
    if (blockIdx.x < 128) {
      HS(1);
      wait_clock(t0, XDLY);
      mbar_expect_tx(b_x, 32768);
      bulk_load_hint(sbase + 3 * 32768, x + (size_t)blockIdx.x * 16 * T_D, 32768, b_x, pol_normal());
    }
    mbar_arrive(b_tab); mbar_arrive(b_tab + 8);
  }

  if (wg == 0) {
    reg_dealloc<AT_PREG>();
    if (wid == 0) { __syncwarp(); named_bar_arrive(6, 128); named_bar_arrive(11, 160); named_bar_arrive(12, 160); }
    if (wid >= 2) {
      named_bar_sync(6, 128);
      wait_clock(t0, GDLY2);
      gather_table(hm, sbase + 4 * 32768, b_tab, wid & 1, threadIdx.x & 31);
      if (threadIdx.x == 64) PF(0);
      if (threadIdx.x == 96 && !single) { sleep_until(t0, 40000); spin_until(&g_hcnt[32 * (1 + (item0 & 15))], 7u); mbar_arrive(b_w); }
    } else if (wid == 1) {
      named_bar_sync(6, 128);
      if (item0 < 112) {
        const int lane = threadIdx.x & 31;
        #pragma unroll 1
        for (int j0 = h_first(item0, 0), j1 = h_first(item0, 1); j0 < 16 || j1 < 16;) {
          const int c = j1 < j0, j = c ? j1 : j0;
          bf16* hg = hm->o + (size_t)((item0 & 15) * 128 + c * 64 + (lane >> 3)) * O_LD + O_H + (lane & 7) * 8 + j * 64;
          uint32_t src = sbase + AT_SQ - 16384 + c * 8192 + (lane >> 3) * 128 + (((lane ^ (lane >> 3)) & 7) << 4);
          mbar_wait(b_hs + 8 * c, j >= 7 && j < 14);
          #pragma unroll 1
          for (int i = 0; i < 4; i++, hg += 16 * O_LD, src += 2048) {
            uint4 v[4];
            #pragma unroll
            for (int k = 0; k < 4; k++) v[k] = lds_u32x4((src ^ ((k & 1) * 64)) + k * 512);
            #pragma unroll
            for (int k = 0; k < 4; k++) *reinterpret_cast<uint4*>(hg + k * 4 * O_LD) = v[k];
          }
          __syncwarp();
          if (lane == 0) mbar_arrive(b_hs + 16 + 8 * c);
          if (c) j1 += 7; else j0 += 7;
        }
        if (lane == 0) mbar_arrive(b_go);
        if (lane == 0) red_release_add(&g_hcnt[32 * (1 + (item0 & 15))], 1u);
      }
      sleep_until(t0, 26000);
      const uint32_t v = assign_tile(hm, t0, threadIdx.x & 31);
      if (threadIdx.x == 32) { sts_u32(s_bx, v); mbar_arrive(b_bx); }
      __syncwarp();
      store_warp(hm, sbase, &tmO, item0, n_items);
      __syncwarp();
    } else {
     if (elect_one()) {
      const uint64_t pol = policy_evict_first();
      prefetch_tmap(&tmW); prefetch_tmap(&tmX); prefetch_tmap(&tmWo); prefetch_tmap(&tmOl);
      if (single) {
        prefetch_tmap(&tmM);
        #pragma unroll 1
        for (uint32_t i = 0, buf = 0; i < 44; i++) {
          wait_clock(t0, i < 12 ? (blockIdx.x < 128 ? WDLY + W_OFF : WDLY) + (i & 3) * W_GAP + (i >> 2) * W_RND : W_LATE);
          #pragma unroll 1
          for (uint32_t spin = 0, n = 0; spin < (1u << 24) && n <= i; spin++) asm volatile("ld.volatile.shared.u32 %0, [%1];" : "=r"(n) : "r"(bars + 504) : "memory");
          mbar_expect_tx(bars + 464 + buf * 8, 32768);
          tma_load_2d_hint(sbase + (buf + (buf > 2 ? 2 : 0)) * 32768, &tmM, mod_col0(blockIdx.x - AT_NFULL, (int)(i >> 2) - 3), (i & 3) * 256, bars + 464 + buf * 8, pol);
          if (++buf == 5) buf = 0;
        }
        mbar_wait(b_go, 0);
      }
      {
        #pragma unroll 1
        for (int j = 0; j < T_D / 64; j++) {
          const uint32_t fb = b_full + 8 * (j & 3);
          mbar_wait(b_empty + 8 * (j & 3), ((j >> 2) & 1) ^ 1);
          mbar_expect_tx(fb, j == 0 ? 65536 : j == T_D / 64 - 1 ? 32768 : 49152);
          if (j < 2) wait_clock(t0, j ? ST1_T : PRE_T);
          if (j == 3) mbar_wait(b_a0, 0);
          if (j < 4) HS(2 + j);
          tma_load_3d_hint(sbase + (j & 3) * 32768, &tmW, j * 64, (item0 >> 4) * 4, fb, pol);
          if (j == 0) { wait_clock(t0, A_T); tma_load_2d_hint(sbase + AT_SQ, &tmX, 0, (item0 & 15) * 128, fb, pol); }
          if (j < T_D / 64 - 1) tma_load_2d_hint(sbase + AT_SQ + ((j + 1) & 3) * 16384, &tmX, (j + 1) * 64, (item0 & 15) * 128, fb, pol);
        }
      }
      uint32_t slot = 0, ph = 1;
      #pragma unroll 1
      for (int it = 0; it < n_items; it++) {
        const int item = item0 + it * 128, hp = item >> 4, qt = item & 15;
        const bool first = it == 0;
        if (!first) {
          #pragma unroll 1
          for (int j = 0; j < T_D / 64; j++) {
            const uint32_t sl = ring_slot(qp_pos(j, 1)), fb = b_full + 8 * sl;
            mbar_wait(b_empty + 8 * sl, ring_par(qp_pos(j, 1)) ^ ((j >> 2) & 1) ^ 1);
            mbar_expect_tx(fb, 49152);
            tma_load_3d_hint(sbase + sl * 32768, &tmW, j * 64, hp * 4, fb, pol);
            if (j == 0) { mbar_wait(b_q0, 0); mbar_wait(b_q1, 0); mbar_wait(b_w, 0); fence_proxy_async_global(); }
            tma_load_2d_hint(sbase + AT_SQ + (j & 3) * 16384, &tmOl, O_H + j * 64, qt * 128, fb, pol);
          }
        }
        #pragma unroll 1
        for (int j = 0; j < 4 * AT_NBLK; j++) {
          const bool isv = (j > 0 && !(j & 1)) || j == 4 * AT_NBLK - 1;
          const int row = hp * 2 * T_SEQ + (isv ? (j - 1) >> 1 : (j + 1) >> 1) * 128;
          const uint32_t fb = b_full + 8 * slot;
          mbar_wait(b_empty + 8 * slot, ph);
          if (!first && j == 3) mbar_wait(b_ob, 0);
          if (!first && j == 4) hint_arrive(&g_hcnt[32 * (1 + qt) + 1]);
          if (first && j == 4 && item0 < 112) mbar_wait(b_go, 0);
          mbar_expect_tx(fb, 32768);
          tma_load_2d_hint(sbase + slot * 32768, isv ? &tmV : &tmK, 0, row, fb, pol);
          tma_load_2d_hint(sbase + slot * 32768 + 16384, isv ? &tmV : &tmK, 64, row, fb, pol);
          if (it == 1 && isv && j >= 2 * WO_LATE && j < 2 * WO_LATE + 32 && blockIdx.x < 64)
            l2_prefetch_bulk(pf_wo + (size_t)blockIdx.x * 131072 + ((j >> 1) - WO_LATE) * 8192, 8192);
          if (++slot == 5) { slot = 0; ph ^= 1; }
        }
      }
      mbar_wait(b_bx, 0);
      const uint32_t bx = lds_u32(s_bx);
      if (bx < 128) {
        if (single) mbar_wait(b_go, 1);
        tail_producer(hm, bx, sbase, 0, n_items - 1, pol, &tmOl, &tmWo, &tmX, w_down);
      }
     }
    }
    __syncwarp();
    PSV(0, threadIdx.x == 96, t0);
    mbar_wait(b_bx, 0);
    const uint32_t bx = __shfl_sync(0xffffffffu, lds_u32(s_bx), 0);
    if (bx < 128) tail_exchange(hm, bx, sbase, wid, __shfl_sync(0xffffffffu, threadIdx.x, threadIdx.x), &tmOut, out);
  } else {
    if (wg == 1 && blockIdx.x < 128) head_first(hm, sbase + 4 * 32768 + 4096, threadIdx.x - 128, cvec, w_mod);
    named_bar_sync(10 + wg, 160);
    if (wg == 2 && blockIdx.x < 128) head_stats(hm, sbase + 3 * 32768, b_x, threadIdx.x - 256);
    if (single) {
      mod_rest(hm, t0, sbase, bars + 464, threadIdx.x - 128, (int)blockIdx.x - AT_NFULL, cvec, w_r);
      named_bar_sync(5, 256);
      if (threadIdx.x == 128) mbar_arrive(b_go);
    }
    if (wg == 1) { wait_clock(t0, GDLY); head_gather(hm, sbase + 4 * 32768, threadIdx.x - 128); }
    reg_alloc<AT_CREG>();
    const int cwg = wg - 1;
    const int tid = __shfl_sync(0xffffffffu, threadIdx.x, threadIdx.x) & 127;
    const int warp = wid & 3, lane = tid & 31;
    const uint32_t dbase = (sbase & 0x3FFFFu) >> 4;
    const uint32_t k_base = dbase + (1u << 16);
    const uint32_t v_base = dbase + (1024u << 16);
    const uint32_t w_base = dbase + (512u << 16);
    const uint32_t frag = cwg * 8192 + (16 * warp + (lane & 7) + 8 * ((lane >> 3) & 1)) * 128;
    if (cwg == 1) named_bar_arrive(1, 256);
    bool raw = false;
    constexpr int nkb = T_D / 64;
    float acc[128], c0, c1;
    {
      FS(0, 0);
      uint32_t af[2][16], rw[16];
      uint4 tb[4];
      uint32_t xa[4];
      #pragma unroll
      for (int st = 0; st < 4; st++) xa[st] = __shfl_sync(0xffffffffu, (sbase + AT_SQ + frag + (((lane >> 4) ^ (lane & 7)) << 4)) ^ (st * 32), lane);
      const uint32_t xt = __shfl_sync(0xffffffffu, sbase + 4 * 32768 + (lane & 3) * 16, lane);
      auto qp_fetch = [&](int j) {
        #pragma unroll
        for (int st = 0; st < 4; st++) {
          ldmatrix_x4(xa[st] + (j & 3) * 16384, rw[4 * st], rw[4 * st + 1], rw[4 * st + 2], rw[4 * st + 3]);
          tb[st] = lds_u32x4(xt + (j & 15) * 256 + st * 64);
        }
      };
      zero_regs(acc);
      #pragma unroll
      for (int i = 0; i < 16; i++) af[1][i] = 0u;
      const float2* stp = hm->stat + (item0 & 15) * 256 + (cwg * 4 + warp) * 32 + (lane & 3) * 8 + (lane >> 2);
      HS(4);
      wait_clock(t0, SDLY);
      float2 sv = ld_tagged2(stp);
      named_bar_sync(5, 256);
      mbar_wait(b_full, 0);
      HS(5);
      qp_fetch(0);
      #pragma unroll 1
      for (unsigned int spin = 0; spin < (1u << 22); spin++) {
        if (__all_sync(0xffffffffu, (__float_as_uint(sv.x) != 0u) & (__float_as_uint(sv.y) != 0u))) break;
        sv = ld_tagged2(stp);
      }
      HS(6);
      if (lane == 0) mbar_arrive(b_a0 + (rw[3] & rw[7] & rw[11] & rw[15] & zero));
      const uint32_t st = ln_stat(sv.x + __shfl_xor_sync(0xffffffffu, sv.x, 1), sv.y + __shfl_xor_sync(0xffffffffu, sv.y, 1)), so = __shfl_xor_sync(0xffffffffu, st, 2);
      const uint32_t sta = (lane & 2) ? so : st, stb = (lane & 2) ? st : so;
      const uint32_t mean_a = __byte_perm(sta, 0u, 0x1010), mean_b = __byte_perm(stb, 0u, 0x1010), sd_a = __byte_perm(sta, 0u, 0x3232), sd_b = __byte_perm(stb, 0u, 0x3232);
      c0 = AT_C * rcp_approx(bfhi(sta)); c1 = AT_C * rcp_approx(bfhi(stb));
      sts_u32(sbase + OG_SMISC + 256 + (cwg * 4 + warp) * 64 + (lane & 28) + (lane & 2) * 16, __float_as_uint((lane & 2) ? c1 : c0));
      int jst = item0 < 112 ? h_first(item0, cwg) : 99;
      #pragma unroll 1
      for (int j2 = 0; j2 < nkb; j2 += 2) {
        #pragma unroll
        for (int u = 0; u < 2; u++) {
          const int j = j2 + u;
          const uint32_t bt = b_tab + 4 * ((j + 1) & 15);
          if (u == 1) {
            #pragma unroll 1
            for (uint32_t z = 0; z < zero; z++)
              #pragma unroll
              for (int i = 0; i < 16; i += 4) sts_u32x4(xt + i * 4, af[1][i], af[1][i + 1], af[1][i + 2], af[1][i + 3]);
          }
          bool ok = mbar_test(b_full + 8 * (j & 3), (j >> 2) & 1);
          if (u == 1) ok &= mbar_test(bt, 0);
          #pragma unroll
          for (int st = 0; st < 4; st++) {
            af[u][4 * st + 0] = bfma2(bsub2(rw[4 * st + 0], mean_a), tb[st].x, bmul2(tb[st].z, sd_a));
            af[u][4 * st + 1] = bfma2(bsub2(rw[4 * st + 1], mean_b), tb[st].x, bmul2(tb[st].z, sd_b));
            af[u][4 * st + 2] = bfma2(bsub2(rw[4 * st + 2], mean_a), tb[st].y, bmul2(tb[st].w, sd_a));
            af[u][4 * st + 3] = bfma2(bsub2(rw[4 * st + 3], mean_b), tb[st].y, bmul2(tb[st].w, sd_b));
          }
          if (!ok || j == jst) {
            if (!ok) { mbar_wait(b_full + 8 * (j & 3), (j >> 2) & 1); if (u == 1) mbar_wait(bt, 0); }
            if (j == jst) {
              if (j >= 7) mbar_wait(b_hs + 16 + 8 * cwg, j >= 14);
              #pragma unroll
              for (int st = 0; st < 4; st++) stmatrix_x4(xa[st] - 16384, af[u][4 * st], af[u][4 * st + 1], af[u][4 * st + 2], af[u][4 * st + 3]);
              __syncwarp();
              if (lane == 0) mbar_arrive(b_hs + 8 * cwg);
              jst += 7;
            }
          }
          qp_fetch(j + 1);
          if (cwg == 1 && j == nkb - 1) named_bar_sync(7, 256);
          const uint32_t b_lo = w_base + (j & 3) * 2048;
          wgmma_fence();
          wgmma_m64n256k16_rs_tb<0>(acc, af[u][0], af[u][1], af[u][2], af[u][3], b_lo, 1);
          wgmma_m64n256k16_rs_tb<128>(acc, af[u][4], af[u][5], af[u][6], af[u][7], b_lo, 1);
          wgmma_m64n256k16_rs_tb<256>(acc, af[u][8], af[u][9], af[u][10], af[u][11], b_lo, 1);
          wgmma_m64n256k16_rs_tb<384>(acc, af[u][12], af[u][13], af[u][14], af[u][15], b_lo, 1);
          wgmma_commit();
          if (cwg == 0 && j == nkb - 1) named_bar_arrive(7, 256);
          if (j == 0) HS(7);
          wgmma_wait<1>();
          if (tid == 0) mbar_arrive(j > 0 ? b_empty + 8 * ((j - 1) & 3) : b_pin);
        }
      }
      wgmma_wait<0>();
      fence_regs(acc);
    }
    uint32_t bx;
    #pragma unroll 1
    for (int it = 0;;) {
      const int item = item0 + it * 128, hp = item >> 4;
      const bool more = it + 1 < n_items;
      const int ta = __shfl_sync(0xffffffffu, 4 * it, 0);
      FS(2 * it, 1);
      PS(1 + 2 * it, threadIdx.x == 256);
      if (tid == 0) mbar_arrive(b_empty + 24);
      float o[64], s[64];
      uint32_t p[32], q[32];
      #pragma unroll
      for (int i = 0; i < 32; i++) q[i] = pack_bf16(acc[2 * i] * ((i & 1) ? c1 : c0), acc[2 * i + 1] * ((i & 1) ? c1 : c0));
      zero_regs(s);
      const uint32_t sq = sbase + AT_SQ + cwg * 8192;
      const bool last_wg1 = cwg == 1 && !more;
      float mc0, mc1, al0 = 1.0f, al1 = 1.0f, l0 = 0.f, l1 = 0.f;
      bool redo0 = false;
      FS(2 * it, 2);
      mbar_wait(b_full + 8 * ring_slot(ta), ring_par(ta));
      named_bar_sync(1 + cwg, 256);
      FS(2 * it, 3);
      issue_qk(s, q, k_base + ring_slot(ta) * 2048);
      named_bar_arrive(1 + (cwg ^ 1), 256);
      const uint32_t rdy = (uint32_t)mbar_test(b_full + 8 * ring_slot(ta + 1), ring_par(ta + 1));
      bool ready = rdy & mbar_test(b_full + 8 * ring_slot(ta + 2), ring_par(ta + 2));
      stage_o(*reinterpret_cast<const float (*)[64]>(&acc[64]), c0, c1, sbase + AT_SQ + 32768 + frag, lane);
      wgmma_wait<0>();
      fence_regs(s);
      if (tid == 0) mbar_arrive(b_empty + 8 * ring_slot(ta));
      mc0 = 0.f; mc1 = 0.f;
      if (it == 0) raw = __all_sync(0xffffffffu, fmaxf(fmaxf(fmaxf(fabsf(s[0]), fabsf(s[10])), fmaxf(fabsf(s[17]), fabsf(s[27]))),
                                                       fmaxf(fmaxf(fabsf(s[36]), fabsf(s[46])), fmaxf(fabsf(s[53]), fabsf(s[63])))) <= 16.0f);
      if (!raw) {
        raw = softmax_mode(s, mc0, mc1);
        if (__builtin_expect(!raw, 0)) softmax_sub(s, mc0, mc1);
      }
      softmax_exp<0, 64>(s);
      stage_qregs(q, sbase + AT_SQ + frag, lane);
      pack_p(p, s);
      zero_regs(o);
      FS(2 * it, 4);
      uint32_t ks = ring_slot(ta + 1), vs = ring_slot(ta + 2), kp = ring_par(ta + 1), vp = ring_par(ta + 2);
      if (!ready) { mbar_wait(b_full + 8 * ks, kp); mbar_wait(b_full + 8 * vs, vp); }
      #pragma unroll 1
      for (int n = 1; n < 2 * AT_NBLK; n++) {
        named_bar_sync(1 + cwg, 256);
        issue_qk(s, q, k_base + ks * 2048);
        if (n == AT_NBLK + 1) {
          if (!redo0) stage_o(o, 1.0f, 1.0f, sbase + AT_SQ + frag, lane);
        }
        issue_pv(o, p, v_base + vs * 2048, (n & 15) != 1);
        if (!(last_wg1 && n == 2 * AT_NBLK - 1)) named_bar_arrive(1 + (cwg ^ 1), 256);
        wgmma_wait<1>();
        fence_regs(s);
        if (tid == 0) mbar_arrive(b_empty + 8 * ks);
        if (__builtin_expect(!raw || (n + 1) >> 1 == AT_NBLK / 2, 0)) {
          if (n == AT_NBLK - 1) {
            #pragma unroll
            for (int J = 0; J < 16; J += 2)
              ldmatrix_x4(sbase + AT_SQ + 32768 + frag + (J >> 3) * 16384 + ((((J & 7) + (lane >> 4)) ^ (lane & 7)) << 4), q[2 * J], q[2 * J + 1], q[2 * J + 2], q[2 * J + 3]);
          }
          if (n == AT_NBLK && lane == 0) mbar_arrive(b_q1);
          if (!raw) {
            const float m0 = mc0, m1 = mc1;
            const bool ok = softmax_mode(s, mc0, mc1);
            if (n == AT_NBLK) raw = ok;
            else {
              mc0 = mc0 - AT_HEAD > m0 ? mc0 : m0; mc1 = mc1 - AT_HEAD > m1 ? mc1 : m1;
              al0 = ex2_approx(m0 - mc0); al1 = ex2_approx(m1 - mc1);
            }
            if (!raw) softmax_sub(s, mc0, mc1);
          }
        }
        softmax_exp<0, AT_SPLIT>(s);
        add_rowsum(p, l0, l1);
        if (tid == 0) {
          uint32_t dep = zero & __float_as_uint(l0) & __float_as_uint(l1);
          #pragma unroll
          for (int i = AT_SPLIT - AT_PIN - PINB; i < AT_SPLIT - PINB; i += 2) dep &= __float_as_uint(s[i]) & __float_as_uint(s[i + 1]);
          mbar_arrive(b_pin + dep);
        }
        wgmma_wait<0>();
        fence_regs(o);
        if (tid == 0) mbar_arrive(b_empty + 8 * vs);
        ks += 2; if (ks >= 5) { ks -= 5; kp ^= 1; }
        vs += 2; if (vs >= 5) { vs -= 5; vp ^= 1; }
        ready = mbar_test(b_full + 8 * ks, kp) & mbar_test(b_full + 8 * vs, vp);
        if (__builtin_expect(n == AT_NBLK, 0)) {
          redo0 = finish_l(l0, l1);
          softmax_exp<AT_SPLIT, 64>(s);
          rescale_o(o, l0, l1);
          pack_p(p, s);
          l0 = 0.f; l1 = 0.f;
        } else {
          softmax_exp<AT_SPLIT, 64>(s);
          pack_p(p, s);
        }
        if (__builtin_expect(!raw || !ready || n == AT_NBLK + 1, 0)) {
        if (n == AT_NBLK + 1 && !redo0) { fence_proxy_async(); __syncwarp(); if (lane == 0) mbar_arrive(b_ordy + 8 * cwg); }
        if (!raw && __any_sync(0xffffffffu, al0 != 1.0f || al1 != 1.0f)) {
          rescale_o(o, al0, al1);
          l0 *= al0; l1 *= al1;
          al0 = 1.0f; al1 = 1.0f;
        }
        if (!ready && n < 2 * AT_NBLK - 1) {
          mbar_wait(b_full + 8 * ks, kp);
          mbar_wait(b_full + 8 * vs, vp);
        }
        }
      }
      FS(2 * it + 1, 5);
      const uint32_t vl = ring_slot(ta + 63);
      vs = ring_slot(ta + 62);
      const uint32_t ob = more ? sbase + vs * 32768 : sbase + AT_SQ + 32768;
      mbar_wait(b_full + 8 * vl, ring_par(ta + 63));
      issue_pv(o, p, v_base + vl * 2048, 1);
      add_rowsum(p, l0, l1);
      #pragma unroll 1
      for (uint32_t z = 0; z < zero; z++) mbar_arrive(b_pin + __float_as_uint(l0) + __float_as_uint(l1));
      const bool overflow = finish_l(l0, l1);
      mbar_wait(b_bx, 0);
      bx = __shfl_sync(0xffffffffu, lds_u32(s_bx), 0);
      mbar_wait(b_empty + 8 * vs, ring_par(ta + 62));
      wgmma_wait<0>();
      fence_regs(o);
      if (tid == 0) mbar_arrive(b_empty + 8 * vl);
      FS(2 * it + 1, 6);
      if (overflow) stage_qregs(q, ob + frag, lane);
      else stage_o(o, l0, l1, ob + frag, lane);
      if (__builtin_expect(overflow || redo0, 0)) {
        __syncwarp();
        #pragma unroll 1
        for (int h = redo0 ? 0 : 1; h < (overflow ? 2 : 1); h++)
          attn_rows_exact(h ? ob + cwg * 8192 : sq, warp, lane, kc + (size_t)(hp * 2 + h) * T_SEQ * T_DH, vc + (size_t)(hp * 2 + h) * T_SEQ * T_DH);
        fence_proxy_async();
        __syncwarp();
        if (lane == 0 && redo0) mbar_arrive(b_ordy + 8 * cwg);
        raw = false;
      }
      fence_proxy_async();
      __syncwarp();
      if (lane == 0) mbar_arrive(b_ordy + 16 + 8 * cwg);
      named_bar_sync(3 + cwg, 128);
      FS(2 * it + 1, 7);
      PS(2 + 2 * it, threadIdx.x == 256);
      if (++it == n_items) break;
      FS(2 * it, 0);
      zero_regs(acc);
      auto ss_step = [&](int j, int accumulate) {
        const uint32_t slot = ring_slot(qp_pos(j, 1));
        mbar_wait(b_full + 8 * slot, ring_par(qp_pos(j, 1)) ^ ((j >> 2) & 1));
        if (cwg == 1 && j == nkb - QP_STAG) named_bar_sync(7, 256);
        const uint32_t a_lo = dbase + ((AT_SQ + cwg * 8192) >> 4) + (1u << 16) + (j & 3) * 1024, b_lo = w_base + slot * 2048;
        wgmma_fence();
        wgmma_m64n256k16_ss_tb<0, 0>(acc, a_lo, b_lo, accumulate);
        wgmma_m64n256k16_ss_tb<2, 128>(acc, a_lo, b_lo, 1);
        wgmma_m64n256k16_ss_tb<4, 256>(acc, a_lo, b_lo, 1);
        wgmma_m64n256k16_ss_tb<6, 384>(acc, a_lo, b_lo, 1);
        wgmma_commit();
        return b_empty + 8 * slot;
      };
      uint32_t prev = ss_step(0, 0);
      c0 = lds_f32(sbase + OG_SMISC + 256 + (cwg * 4 + warp) * 64 + (lane & 28)); c1 = lds_f32(sbase + OG_SMISC + 288 + (cwg * 4 + warp) * 64 + (lane & 28));
      #pragma unroll 1
      for (int j = 1; j < nkb; j++) {
        if (cwg == 1 && j == nkb - QP_STAG) {
          wgmma_wait<0>();
          if (tid == 0) mbar_arrive(prev);
          prev = b_pin;
        }
        const uint32_t cur = ss_step(j, 1);
        if (cwg == 0 && j == nkb - 1) named_bar_arrive(7, 256);
        wgmma_wait<1>();
        if (tid == 0) mbar_arrive(prev);
        prev = cur;
      }
      wgmma_wait<0>();
      fence_regs(acc);
    }
    if (n_items == 1) {
      named_bar_sync(5, 256);
      if (threadIdx.x == 128) {
        #pragma unroll 1
        for (int i = 4; i < 8; i++) {
          mbar_arrive(b_full + 8 * ring_slot(i));
          mbar_arrive(b_empty + 8 * ring_slot(i)); mbar_arrive(b_empty + 8 * ring_slot(i));
        }
        mbar_arrive(b_go);
      }
      named_bar_sync(5, 256);
    }
    TL_CLK(3, 1, threadIdx.x == 128);
    TL_CTA(1, threadIdx.x == 256);
    TL_END(3, tid == 0);
    __syncwarp();
    QDUMP();
    TL_MARK2(19, tid == 0 && !single);
    if (bx < 128) {
      tail_consumer(hm, bx, sbase, tid, wid - 4, w_gate, w_up);
    }
  }
}

typedef CUresult (*PFN_encodeTiled)(CUtensorMap*, CUtensorMapDataType, cuuint32_t, void*, const cuuint64_t*, const cuuint64_t*,
                                    const cuuint32_t*, const cuuint32_t*, CUtensorMapInterleave, CUtensorMapSwizzle,
                                    CUtensorMapL2promotion, CUtensorMapFloatOOBfill);

CUtensorMap make_map_2d(PFN_encodeTiled enc, const void* ptr, uint64_t inner, uint64_t outer, uint64_t stride_bytes, uint32_t box_inner, uint32_t box_outer) {
  CUtensorMap m;
  cuuint64_t gd[2] = {inner, outer}; cuuint64_t gs[1] = {stride_bytes};
  cuuint32_t bx[2] = {box_inner, box_outer}; cuuint32_t es[2] = {1, 1};
  enc(&m, CU_TENSOR_MAP_DATA_TYPE_BFLOAT16, 2, const_cast<void*>(ptr), gd, gs, bx, es, CU_TENSOR_MAP_INTERLEAVE_NONE,
      CU_TENSOR_MAP_SWIZZLE_128B, CU_TENSOR_MAP_L2_PROMOTION_L2_128B, CU_TENSOR_MAP_FLOAT_OOB_FILL_NONE);
  return m;
}

CUtensorMap make_map_3d(PFN_encodeTiled enc, const void* ptr, uint64_t cols, uint64_t rows, uint32_t box_rows, uint32_t chunks) {
  CUtensorMap m;
  cuuint64_t gd[3] = {64, rows, cols / 64}; cuuint64_t gs[2] = {cols * 2, 128};
  cuuint32_t bx[3] = {64, box_rows, chunks}; cuuint32_t es[3] = {1, 1, 1};
  enc(&m, CU_TENSOR_MAP_DATA_TYPE_BFLOAT16, 3, const_cast<void*>(ptr), gd, gs, bx, es, CU_TENSOR_MAP_INTERLEAVE_NONE,
      CU_TENSOR_MAP_SWIZZLE_128B, CU_TENSOR_MAP_L2_PROMOTION_L2_128B, CU_TENSOR_MAP_FLOAT_OOB_FILL_NONE);
  return m;
}

}

extern "C" void kernel_launch(void* const* d_in, const int* in_sizes, int n_in, void* d_out, int out_size) {
  const bf16* x      = (const bf16*)d_in[0];
  const bf16* kc     = (const bf16*)d_in[1];
  const bf16* vc     = (const bf16*)d_in[2];
  const bf16* wq     = (const bf16*)d_in[3];
  const bf16* wo     = (const bf16*)d_in[4];
  const bf16* w_r    = (const bf16*)d_in[6];
  const bf16* w_gate = (const bf16*)d_in[7];
  const bf16* w_up   = (const bf16*)d_in[8];
  const bf16* w_down = (const bf16*)d_in[9];
  const bf16* cvec   = (const bf16*)d_in[10];
  const bf16* w_mod  = (const bf16*)d_in[11];
  bf16* out = (bf16*)d_out;

  static PFN_encodeTiled enc = nullptr;
  static void* p_hm = nullptr;
  if (!enc) {
    void* fn = nullptr; cudaDriverEntryPointQueryResult qres;
    cudaGetDriverEntryPoint("cuTensorMapEncodeTiled", &fn, cudaEnableDefault, &qres);
    enc = (PFN_encodeTiled)fn;
    cudaGetSymbolAddress(&p_hm, g_scr);
    cudaFuncSetAttribute(fused_kernel, cudaFuncAttributeMaxDynamicSharedMemorySize, (int)AT_SMEM);
  }
  const CUtensorMap tm_m   = make_map_2d(enc, w_mod, 6 * T_D, T_D, 6 * T_D * 2, 64, 256);
  const CUtensorMap tm_wq  = make_map_3d(enc, wq, T_DQKV, T_D, 64, 4);
  const CUtensorMap tm_k   = make_map_2d(enc, kc, T_DH, (uint64_t)T_NH * T_SEQ, T_DH * 2, 64, 128);
  const CUtensorMap tm_v   = make_map_2d(enc, vc, T_DH, (uint64_t)T_NH * T_SEQ, T_DH * 2, 64, 128);
  const CUtensorMap tm_ost = make_map_2d(enc, ((Scratch*)p_hm)->o, O_LD, T_SEQ, O_LD * 2, 64, 64);
  const CUtensorMap tm_old = make_map_2d(enc, ((Scratch*)p_hm)->o, O_LD, T_SEQ, O_LD * 2, 64, 128);
  const CUtensorMap tm_wo  = make_map_2d(enc, wo, T_D, T_DQKV, T_D * 2, 64, 64);
  const CUtensorMap tm_x   = make_map_2d(enc, x, T_D, T_SEQ, T_D * 2, 64, 128);
  const CUtensorMap tm_out = make_map_2d(enc, out, T_D, T_SEQ, T_D * 2, 64, 128);

#define TUNE_ARG
  fused_kernel<<<132, 384, AT_SMEM, cudaStreamPerThread>>>(x, cvec, w_mod, (Scratch*)p_hm, 0u, TUNE_ARG (const uint8_t*)wo, kc, vc, w_r, w_gate, w_up, w_down, out,
             tm_m, tm_wq, tm_k, tm_v, tm_ost, tm_old, tm_wo, tm_x, tm_out);
}
```
